```python
import torch

def _softmax(x, axis=-1):
    return torch.softmax(x, dim=axis)
def _gelu(x):
    return torch.nn.functional.gelu(x, approximate="tanh")
def _silu(x):
    return torch.nn.functional.silu(x)
def _sigmoid(x):
    return torch.sigmoid(x)
def _layernorm(x, axis=-1, eps=1e-5):
    m = x.mean(dim=axis, keepdim=True)
    v = x.var(dim=axis, keepdim=True, unbiased=False)
    return (x - m) / torch.sqrt(v + eps)
def _scatter_add(tgt, idx, src, axis=0):
    return tgt.clone().index_add_(axis, idx, src)
def _segment_sum(src, seg, n):
    out = torch.zeros((n,) + src.shape[1:], dtype=src.dtype)
    return out.index_add_(0, seg, src)
def _pad(x, pw):
    flat = tuple(v for pair in reversed(pw) for v in pair)
    return torch.nn.functional.pad(x, flat)

kernel_name = 'concat_heads__sliding_local_dilated__compressed_kv_cla__prompt'

def setup_inputs():

    _w = (lambda a: (lambda t: t.to(torch.bfloat16) if t.is_floating_point() else t)(torch.as_tensor(a)))
    def _A_setup():
        B, S, D = 1, 2048, 1024
        return {
            "x": _w((lambda *s: torch.randn(*s, dtype=torch.bfloat16) * 0.2)(B, S, D)),
            "wqkv": _w((lambda *s: torch.randn(*s, dtype=torch.bfloat16) * 0.2)(D, 3 * D)),
            "wo": _w((lambda *s: torch.randn(*s, dtype=torch.bfloat16) * 0.05)(D, D)),
        }
    _A_in = _A_setup()

    def _B_setup():
        B, H, Sq, Sk, D, M = 1, 32, 2048, 2048, 128, 1024
        Dc = 4 * D
        return {
            "x": _w((lambda *s: torch.randn(*s, dtype=torch.bfloat16) * 0.2)(B, Sq, M)),
            "c_kv": _w((lambda *s: torch.randn(*s, dtype=torch.bfloat16) * 1.6)(B, Sk, Dc)),
            "w_q": _w((lambda *s: torch.randn(*s, dtype=torch.bfloat16) * 3.2)(M, H, D) * (M ** -0.5)),
            "w_uk": _w((lambda *s: torch.randn(*s, dtype=torch.bfloat16) * 3.2)(Dc, H, D) * (Dc ** -0.5)),
            "w_uv": _w((lambda *s: torch.randn(*s, dtype=torch.bfloat16) * 1.6)(Dc, H, D) * (Dc ** -0.5)),
            "w_o": _w((lambda *s: torch.randn(*s, dtype=torch.bfloat16) * 1.6)(H, D, M) * ((H * D) ** -0.5)),
        }
    _B_in = _B_setup()

    return {
        "A_x": _A_in["x"],
        "A_wqkv": _A_in["wqkv"],
        "A_wo": _A_in["wo"],
        "B_x": _B_in["x"],
        "B_c_kv": _B_in["c_kv"],
        "B_w_q": _B_in["w_q"],
        "B_w_uk": _B_in["w_uk"],
        "B_w_uv": _B_in["w_uv"],
        "B_w_o": _B_in["w_o"],
    }

def reference(A_x, A_wqkv, A_wo, B_x, B_c_kv, B_w_q, B_w_uk, B_w_uv, B_w_o):
    def _A_ref(x, wqkv, wo):
        B, S, D = x.shape
        H = 32; Dh = D // H
        W, dil = 8, 2
        qkv = (lambda x, *d: x.permute(*d))((x @ wqkv).reshape(B, S, 3, H, Dh), 2, 0, 3, 1, 4)
        q, k, v = qkv[0], qkv[1], qkv[2]
        scale = Dh ** -0.5
        pos = torch.arange(S)
        off = torch.arange(W) * dil
        idx = pos[:, None] - off[None, :]
        mask = idx >= 0
        idx_c = torch.where(mask, idx, 0).reshape(-1)
        kg = k[:, :, idx_c, :].reshape(B, H, S, W, Dh)
        vg = v[:, :, idx_c, :].reshape(B, H, S, W, Dh)
        logits = torch.einsum("bhsd,bhswd->bhsw", q, kg) * scale
        logits = torch.where(mask[None, None, :, :], logits, -1e9)
        attn = _softmax(logits, axis=-1)
        o = torch.einsum("bhsw,bhswd->bhsd", attn, vg)
        return (lambda x, *d: x.permute(*d))(o, 0, 2, 1, 3).reshape(B, S, D) @ wo

    def _B_ref(x, c_kv, w_q, w_uk, w_uv, w_o):
        B, Sq, M = x.shape[0], x.shape[1], x.shape[2]
        Sk = c_kv.shape[1]
        H, D = w_q.shape[1], w_q.shape[2]
        q = torch.einsum("bqm,mhd->bhqd", x, w_q)
        k = torch.einsum("bkc,chd->bhkd", c_kv, w_uk)
        v = torch.einsum("bkc,chd->bhkd", c_kv, w_uv)
        scores = torch.einsum("bhqd,bhkd->bhqk", q, k) * (D ** -0.5)
        off = Sk - Sq
        qi = torch.arange(Sq)[:, None]
        kj = torch.arange(Sk)[None, :]
        cmask = kj <= (qi + off)
        scores = torch.where(cmask[None, None], scores, -1e9)
        p = _softmax(scores, axis=-1)
        ctx = torch.einsum("bhqk,bhkd->bhqd", p, v)
        return torch.einsum("bhqd,hdm->bqm", ctx, w_o)

    a = _A_ref(A_x, A_wqkv, A_wo)
    b = _B_ref(B_x, B_c_kv, B_w_q, B_w_uk, B_w_uv, B_w_o)
    return torch.concatenate([a, b], axis=-1)
```

```cpp
#define E4 3
#define E2V
#include <cuda_runtime.h>
#include <cuda_bf16.h>
#include <cuda.h>
#include <stdint.h>
#include <type_traits>

namespace {

typedef __nv_bfloat16 bf16;

constexpr int PLANE = 2048 * 64;
__device__ __align__(1024) bf16 g_qkvA[2048 * 3072];
__device__ __align__(1024) bf16 g_q[2048 * 4096];
__device__ __align__(1024) bf16 g_k[2048 * 4096];
__device__ __align__(1024) bf16 g_v[2048 * 4096];
__device__ __align__(1024) bf16 g_ctx[2048 * 4096];
__device__ __align__(1024) bf16 g_oA[2048 * 1024];

__device__ __forceinline__ uint32_t smem_u32(const void* p) { return (uint32_t)__cvta_generic_to_shared(p); }
__device__ __forceinline__ void mbar_init(uint32_t bar, uint32_t cnt) {
  asm volatile("mbarrier.init.shared::cta.b64 [%0], %1;" ::"r"(bar), "r"(cnt) : "memory");
}
__device__ __forceinline__ void mbar_expect_tx(uint32_t bar, uint32_t bytes) {
  asm volatile("mbarrier.arrive.expect_tx.shared::cta.b64 _, [%0], %1;" ::"r"(bar), "r"(bytes) : "memory");
}
__device__ __forceinline__ void mbar_arrive(uint32_t bar) {
  asm volatile("mbarrier.arrive.shared::cta.b64 _, [%0];" ::"r"(bar) : "memory");
}
__device__ __forceinline__ void mbar_arrive_n(uint32_t bar, uint32_t n) {
  asm volatile("mbarrier.arrive.shared::cta.b64 _, [%0], %1;" ::"r"(bar), "r"(n) : "memory");
}
__device__ __forceinline__ void mbar_arrive_cta(uint32_t bar, uint32_t cta) {
  asm volatile("{\n.reg .b32 ra;\nmapa.shared::cluster.u32 ra, %0, %1;\nmbarrier.arrive.shared::cluster.b64 _, [ra];\n}" ::"r"(bar),
               "r"(cta)
               : "memory");
}
template <bool TRAP = true>
__device__ __forceinline__ void mbar_wait(uint32_t bar, uint32_t parity) {
  uint32_t done;
  uint32_t it = 0;
  while (true) {
    asm volatile("{\n.reg .pred p;\nmbarrier.try_wait.parity.shared::cta.b64 p, [%1], %2;\nselp.u32 %0, 1, 0, p;\n}"
                 : "=r"(done)
                 : "r"(bar), "r"(parity)
                 : "memory");
    if (done) break;
    if (++it > (1u << 20)) {
      if (TRAP) __trap();
      else break;
    }
  }
}
template <bool TRAP = true>
__device__ __forceinline__ void mbar_wait_u(uint32_t bar, uint32_t parity) {
  uint32_t it = 0;
  while (true) {
    uint32_t done;
    asm volatile("{\n.reg .pred p, q;\nmbarrier.try_wait.parity.shared::cta.b64 p, [%1], %2;\nvote.sync.all.pred q, p, 0xffffffff;\nselp.u32 %0, 1, 0, q;\n}"
                 : "=r"(done)
                 : "r"(bar), "r"(parity)
                 : "memory");
    if (done) break;
    if (++it > (1u << 20)) {
      if (TRAP) __trap();
      else break;
    }
  }
}
__device__ __forceinline__ void tma_load_2d(uint32_t dst, const CUtensorMap* m, uint32_t bar, int c0, int c1) {
  asm volatile("cp.async.bulk.tensor.2d.shared::cluster.global.mbarrier::complete_tx::bytes [%0], [%1, {%3, %4}], [%2];" ::"r"(dst),
               "l"(m), "r"(bar), "r"(c0), "r"(c1)
               : "memory");
}
__device__ __forceinline__ void tma_load_3d(uint32_t dst, const CUtensorMap* m, uint32_t bar, int c0, int c1, int c2) {
  asm volatile("cp.async.bulk.tensor.3d.shared::cluster.global.mbarrier::complete_tx::bytes [%0], [%1, {%3, %4, %5}], [%2];" ::"r"(dst),
               "l"(m), "r"(bar), "r"(c0), "r"(c1), "r"(c2)
               : "memory");
}
__device__ __forceinline__ void tma_prefetch_3d(const CUtensorMap* m, int c0, int c1, int c2) {
  asm volatile("cp.async.bulk.prefetch.tensor.3d.L2.global.tile [%0, {%1, %2, %3}];" ::"l"(m), "r"(c0), "r"(c1), "r"(c2) : "memory");
}
__device__ __forceinline__ void tma_load_3d_mc(uint32_t dst, const CUtensorMap* m, uint32_t bar, int c0, int c1, int c2, uint16_t mask) {
  asm volatile(
      "cp.async.bulk.tensor.3d.shared::cluster.global.mbarrier::complete_tx::bytes.multicast::cluster [%0], [%1, {%3, %4, %5}], [%2], %6;" ::"r"(dst),
      "l"(m), "r"(bar), "r"(c0), "r"(c1), "r"(c2), "h"(mask)
      : "memory");
}
__device__ __forceinline__ void tma_store_2d(const CUtensorMap* m, uint32_t src, int c0, int c1) {
  asm volatile("cp.async.bulk.tensor.2d.global.shared::cta.bulk_group [%0, {%2, %3}], [%1];" ::"l"(m), "r"(src), "r"(c0), "r"(c1)
               : "memory");
}
__device__ __forceinline__ void prefetch_tmap(const CUtensorMap* m) { asm volatile("prefetch.tensormap [%0];" ::"l"(m) : "memory"); }
__device__ __forceinline__ void cluster_sync_relaxed() {
  asm volatile("barrier.cluster.arrive.relaxed.aligned;\nbarrier.cluster.wait.aligned;" ::: "memory");
}
__device__ __forceinline__ void pdl_wait() { asm volatile("griddepcontrol.wait;" ::: "memory"); }
__device__ __forceinline__ void pdl_launch() { asm volatile("griddepcontrol.launch_dependents;" ::: "memory"); }
__device__ __forceinline__ uint32_t cluster_rank() {
  uint32_t r;
  asm volatile("mov.u32 %0, %%cluster_ctarank;" : "=r"(r));
  return r;
}
__device__ __forceinline__ uint64_t mkdesc(uint32_t addr, uint32_t lbo, uint32_t sbo) {
  uint64_t d = 0;
  d |= (uint64_t)((addr & 0x3FFFF) >> 4);
  d |= (uint64_t)(lbo >> 4) << 16;
  d |= (uint64_t)(sbo >> 4) << 32;
  d |= (uint64_t)1 << 62;
  return d;
}
__device__ __forceinline__ uint32_t pack_bf16(float lo, float hi) {
  uint32_t r;
  asm("cvt.rn.bf16x2.f32 %0, %1, %2;" : "=r"(r) : "f"(hi), "f"(lo));
  return r;
}
__device__ __forceinline__ float ex2(float x) {
  float y;
  asm("ex2.approx.ftz.f32 %0, %1;" : "=f"(y) : "f"(x));
  return y;
}
__device__ __forceinline__ float rcp(float x) {
  float y;
  asm("rcp.approx.ftz.f32 %0, %1;" : "=f"(y) : "f"(x));
  return y;
}
__device__ __forceinline__ void wg_fence() { asm volatile("wgmma.fence.sync.aligned;" ::: "memory"); }
__device__ __forceinline__ void wg_commit() { asm volatile("wgmma.commit_group.sync.aligned;" ::: "memory"); }
template <int N>
__device__ __forceinline__ void wg_wait() {
  asm volatile("wgmma.wait_group.sync.aligned %0;" ::"n"(N) : "memory");
}
template <int N>
__device__ __forceinline__ void fence_regs(float (&d)[N]) {
#pragma unroll
  for (int i = 0; i < N; i++) asm volatile("" : "+f"(d[i])::"memory");
}
template <int N>
__device__ __forceinline__ void fence_regs(uint32_t (&d)[N]) {
#pragma unroll
  for (int i = 0; i < N; i++) asm volatile("" : "+r"(d[i])::"memory");
}

#define R8(a, i) "+f"(a[i]), "+f"(a[i + 1]), "+f"(a[i + 2]), "+f"(a[i + 3]), "+f"(a[i + 4]), "+f"(a[i + 5]), "+f"(a[i + 6]), "+f"(a[i + 7])
#define ACC64 "{%0,%1,%2,%3,%4,%5,%6,%7,%8,%9,%10,%11,%12,%13,%14,%15,%16,%17,%18,%19,%20,%21,%22,%23,%24,%25,%26,%27,%28,%29,%30,%31," \
              "%32,%33,%34,%35,%36,%37,%38,%39,%40,%41,%42,%43,%44,%45,%46,%47,%48,%49,%50,%51,%52,%53,%54,%55,%56,%57,%58,%59,%60,%61,%62,%63}"
#define OP64(d) R8(d, 0), R8(d, 8), R8(d, 16), R8(d, 24), R8(d, 32), R8(d, 40), R8(d, 48), R8(d, 56)

__device__ __forceinline__ void wgmma_n256_ss_tb(float (&d)[128], uint64_t da, uint64_t db, int scale_d) {
  asm volatile(
      "{\n.reg .pred p;\nsetp.ne.b32 p, %130, 0;\n"
      "wgmma.mma_async.sync.aligned.m64n256k16.f32.bf16.bf16 "
      "{%0,%1,%2,%3,%4,%5,%6,%7,%8,%9,%10,%11,%12,%13,%14,%15,%16,%17,%18,%19,%20,%21,%22,%23,%24,%25,%26,%27,%28,%29,%30,%31,"
      "%32,%33,%34,%35,%36,%37,%38,%39,%40,%41,%42,%43,%44,%45,%46,%47,%48,%49,%50,%51,%52,%53,%54,%55,%56,%57,%58,%59,%60,%61,%62,%63,"
      "%64,%65,%66,%67,%68,%69,%70,%71,%72,%73,%74,%75,%76,%77,%78,%79,%80,%81,%82,%83,%84,%85,%86,%87,%88,%89,%90,%91,%92,%93,%94,%95,"
      "%96,%97,%98,%99,%100,%101,%102,%103,%104,%105,%106,%107,%108,%109,%110,%111,%112,%113,%114,%115,%116,%117,%118,%119,%120,%121,%122,%123,%124,%125,%126,%127},"
      "%128, %129, p, 1, 1, 0, 1;\n}\n"
      : OP64(d), R8(d, 64), R8(d, 72), R8(d, 80), R8(d, 88), R8(d, 96), R8(d, 104), R8(d, 112), R8(d, 120)
      : "l"(da), "l"(db), "r"(scale_d));
}
template <int TB>
__device__ __forceinline__ void wgmma_n128_ss(float (&d)[64], uint64_t da, uint64_t db, int scale_d) {
  asm volatile("{\n.reg .pred p;\nsetp.ne.b32 p, %66, 0;\n"
               "wgmma.mma_async.sync.aligned.m64n128k16.f32.bf16.bf16 " ACC64 ", %64, %65, p, 1, 1, 0, %67;\n}\n"
               : OP64(d)
               : "l"(da), "l"(db), "r"(scale_d), "n"(TB));
}
__device__ __forceinline__ void wgmma_n128_rs_tb(float (&d)[64], uint32_t a0, uint32_t a1, uint32_t a2, uint32_t a3, uint64_t db,
                                                 int scale_d) {
  asm volatile("{\n.reg .pred p;\nsetp.ne.b32 p, %69, 0;\n"
               "wgmma.mma_async.sync.aligned.m64n128k16.f32.bf16.bf16 " ACC64 ", {%64,%65,%66,%67}, %68, p, 1, 1, 1;\n}\n"
               : OP64(d)
               : "r"(a0), "r"(a1), "r"(a2), "r"(a3), "l"(db), "r"(scale_d));
}
__device__ __forceinline__ void bar_sync(int id, int n) { asm volatile("bar.sync %0, %1;" ::"r"(id), "r"(n) : "memory"); }
__device__ __forceinline__ void bar_arrive(int id, int n) { asm volatile("bar.arrive %0, %1;" ::"r"(id), "r"(n) : "memory"); }

#define TL(n)
#define PROF_G(k, slot)
#define PROF_C(k, slot)
#define TRACE_DECL
#define TRACE(k)
#define TRACE_END(k)

__device__ __forceinline__ void mma_16816(float (&c)[4], uint32_t a0, uint32_t a1, uint32_t a2, uint32_t a3, uint32_t b0, uint32_t b1) {
  asm volatile("mma.sync.aligned.m16n8k16.row.col.f32.bf16.bf16.f32 {%0,%1,%2,%3}, {%4,%5,%6,%7}, {%8,%9}, {%0,%1,%2,%3};"
               : "+f"(c[0]), "+f"(c[1]), "+f"(c[2]), "+f"(c[3])
               : "r"(a0), "r"(a1), "r"(a2), "r"(a3), "r"(b0), "r"(b1));
}
__device__ __forceinline__ void mma_1688(float (&c)[4], uint32_t a0, uint32_t a1, uint32_t b0) {
  asm volatile("mma.sync.aligned.m16n8k8.row.col.f32.bf16.bf16.f32 {%0,%1,%2,%3}, {%4,%5}, {%6}, {%0,%1,%2,%3};"
               : "+f"(c[0]), "+f"(c[1]), "+f"(c[2]), "+f"(c[3])
               : "r"(a0), "r"(a1), "r"(b0));
}
__device__ __forceinline__ uint32_t movm_t(uint32_t x) {
  uint32_t y;
  asm volatile("movmatrix.sync.aligned.m8n8.trans.b16 %0, %1;" : "=r"(y) : "r"(x));
  return y;
}

__device__ __forceinline__ void ldsm_x4(uint32_t (&r)[4], uint32_t addr) {
  asm volatile("ldmatrix.sync.aligned.m8n8.x4.shared.b16 {%0,%1,%2,%3}, [%4];" : "=r"(r[0]), "=r"(r[1]), "=r"(r[2]), "=r"(r[3]) : "r"(addr) : "memory");
}
__device__ __forceinline__ void ldsm_x4_t(uint32_t (&r)[4], uint32_t addr) {
  asm volatile("ldmatrix.sync.aligned.m8n8.x4.trans.shared.b16 {%0,%1,%2,%3}, [%4];" : "=r"(r[0]), "=r"(r[1]), "=r"(r[2]), "=r"(r[3]) : "r"(addr) : "memory");
}

constexpr int L_Q = 0, L_K = 16384, L_V = 32768, L_BYTES = 3 * 16384 + 2 * 1024;
__device__ __forceinline__ void local_attn_warp(uint32_t base, uint32_t halo, bf16* __restrict__ dst  , int t, bool first,
                                                int lane) {
  const int g = lane >> 2, tq = lane & 3;
  uint32_t q0[2][4], q1[2][4], kk[2][3][4], vv[2][3][4];
  {
    const int r = 16 * t + (lane & 15);
    const uint32_t a = base + L_Q + r * 128;
    const uint32_t b = base + (16 * t - 8) * 128 + (lane & 7) * 128;
    const uint32_t k0 = t == 0 ? halo + (lane & 7) * 128 : b + L_K, v0 = t == 0 ? halo + 1024 + (lane & 7) * 128 : b + L_V;
#pragma unroll
    for (int h = 0; h < 2; h++) {
      ldsm_x4(q0[h], a + (((h * 4 + (lane >> 4)) ^ (r & 7)) << 4));
      ldsm_x4(q1[h], a + (((h * 4 + 2 + (lane >> 4)) ^ (r & 7)) << 4));
      const uint32_t x = ((h * 4 + (lane >> 3)) ^ (lane & 7)) << 4;
#pragma unroll
      for (int jj = 0; jj < 3; jj++) {
        ldsm_x4(kk[h][jj], (jj == 0 ? k0 : b + L_K + jj * 1024) + x);
        ldsm_x4_t(vv[h][jj], (jj == 0 ? v0 : b + L_V + jj * 1024) + x);
      }
    }
  }
  float s[2][3][4];
#pragma unroll
  for (int h = 0; h < 2; h++)
#pragma unroll
    for (int jj = 0; jj < 3; jj++) {
      s[h][jj][0] = s[h][jj][1] = s[h][jj][2] = s[h][jj][3] = 0.f;
      mma_16816(s[h][jj], q0[h][0], q0[h][1], q0[h][2], q0[h][3], kk[h][jj][0], kk[h][jj][1]);
      mma_16816(s[h][jj], q1[h][0], q1[h][1], q1[h][2], q1[h][3], kk[h][jj][2], kk[h][jj][3]);
    }
  const bool h0 = 2 * tq > g, h1 = 2 * tq + 1 > g;
  const uint32_t m = (h0 ? 0xFFFFu : 0u) | (h1 ? 0xFFFF0000u : 0u);
  float u0[2], u1[2], w0[2], w1[2], mu[2], mw[2];
#pragma unroll
  for (int h = 0; h < 2; h++) {
    u0[h] = h0 ? s[h][0][0] : s[h][1][0];
    u1[h] = h1 ? s[h][0][1] : s[h][1][1];
    w0[h] = h0 ? s[h][1][2] : s[h][2][2];
    w1[h] = h1 ? s[h][1][3] : s[h][2][3];
    if (first) {
      if (h0) u0[h] = -INFINITY;
      if (h1) u1[h] = -INFINITY;
    }
    mu[h] = fmaxf(u0[h], u1[h]);
    mw[h] = fmaxf(w0[h], w1[h]);
  }
#pragma unroll
  for (int o = 1; o <= 2; o++)
#pragma unroll
    for (int h = 0; h < 2; h++) {
      mu[h] = fmaxf(mu[h], __shfl_xor_sync(0xffffffffu, mu[h], o));
      mw[h] = fmaxf(mw[h], __shfl_xor_sync(0xffffffffu, mw[h], o));
    }
  const float c = 0.17677669529663687f * 1.4426950408889634f;
  float lu[2], lw[2];
#pragma unroll
  for (int h = 0; h < 2; h++) {
    u0[h] = ex2((u0[h] - mu[h]) * c);
    u1[h] = ex2((u1[h] - mu[h]) * c);
    w0[h] = ex2((w0[h] - mw[h]) * c);
    w1[h] = ex2((w1[h] - mw[h]) * c);
    lu[h] = u0[h] + u1[h];
    lw[h] = w0[h] + w1[h];
  }
#pragma unroll
  for (int o = 1; o <= 2; o++)
#pragma unroll
    for (int h = 0; h < 2; h++) {
      lu[h] += __shfl_xor_sync(0xffffffffu, lu[h], o);
      lw[h] += __shfl_xor_sync(0xffffffffu, lw[h], o);
    }
#pragma unroll
  for (int h = 0; h < 2; h++) {
    const float iu = rcp(lu[h]), iw = rcp(lw[h]);
    const uint32_t pu = pack_bf16(u0[h] * iu, u1[h] * iu), pw = pack_bf16(w0[h] * iw, w1[h] * iw);
    float o[4][4];
#pragma unroll
    for (int cc = 0; cc < 4; cc++) {
      o[cc][0] = o[cc][1] = o[cc][2] = o[cc][3] = 0.f;
      mma_16816(o[cc], pu & m, 0u, pu & ~m, pw & m, vv[h][0][cc], vv[h][1][cc]);
      mma_1688(o[cc], 0u, pw & ~m, vv[h][2][cc]);
    }
    *reinterpret_cast<uint4*>(dst + h * 32) =
        make_uint4(pack_bf16(o[0][0], o[0][1]), pack_bf16(o[1][0], o[1][1]), pack_bf16(o[2][0], o[2][1]), pack_bf16(o[3][0], o[3][1]));
    *reinterpret_cast<uint4*>(dst + h * 32 + 16 * 64) =
        make_uint4(pack_bf16(o[0][2], o[0][3]), pack_bf16(o[1][2], o[1][3]), pack_bf16(o[2][2], o[2][3]), pack_bf16(o[3][2], o[3][3]));
  }
}

constexpr int K1_CLUSTERS = 66;
constexpr int K1_MAXITEMS = 12;
constexpr int K1_STAGES = 4;
constexpr int K1_STAGE_BYTES = 49152;
constexpr int K1_HALO = K1_STAGES * K1_STAGE_BYTES;
constexpr int K1_SMEM = K1_HALO + K1_STAGES * 2048 + 1024;

struct K1Params {
  CUtensorMap mapA[3];
  CUtensorMap mapB[4];
  CUtensorMap mapL, mapLh;
  bf16* out[4];
  bf16* oA;
  uint32_t* flags;
  int l_ctas;
  int l_units;
  uint16_t sched[K1_CLUSTERS * K1_MAXITEMS];
};
#define HANDOVER 2
constexpr uint32_t QKV_FLAG_FULL = 12 * 2;

__device__ uint32_t g_flags[64];

__device__ __forceinline__ void wait_flag(const uint32_t* f, uint32_t target) {
  uint32_t it = 0;
  while (true) {
    uint32_t v;
    asm volatile("ld.acquire.gpu.global.u32 %0, [%1];" : "=r"(v) : "l"(f) : "memory");
    if (v >= target) break;
    __nanosleep(100);
    if (++it > (1u << 18)) break;
  }
}

__global__ __cluster_dims__(2, 1, 1) __launch_bounds__(384, 1) void k1_proj(const __grid_constant__ K1Params p) {
  extern __shared__ uint8_t smem_raw[];
  __shared__ uint64_t bars[2 * K1_STAGES + 2];
  const uint32_t sbase = (smem_u32(smem_raw) + 1023) & ~1023u;
  const uint32_t full0 = smem_u32(&bars[0]), empty0 = smem_u32(&bars[K1_STAGES]), pub = smem_u32(&bars[2 * K1_STAGES]);
  const uint32_t lready = pub + 8;
  const int wg = __reduce_min_sync(0xffffffffu, (int)(threadIdx.x >> 7));
  const uint32_t rank = cluster_rank();
  const int cl = blockIdx.x >> 1;
  if (threadIdx.x == 32) {
    for (int i = 0; i < 3; i++) prefetch_tmap(&p.mapA[i]);
    for (int i = 0; i < 4; i++) prefetch_tmap(&p.mapB[i]);
  }
  if (threadIdx.x == 0) {
    PROF_G(0, 0);
    PROF_C(0, 1);
    const uint32_t item = p.sched[cl * K1_MAXITEMS];
    const int type = item >> 7, mpair = (item >> 4) & 7, nt = item & 15;
    for (int i = 0; i < K1_STAGES; i++) mbar_init(full0 + 8 * i, 1);
    asm volatile("fence.proxy.async.shared::cta;" ::: "memory");
    for (int ks = 0; ks < K1_STAGES; ks++) {
      const uint32_t dst = sbase + ks * K1_STAGE_BYTES;
      mbar_expect_tx(full0 + 8 * ks, K1_STAGE_BYTES);
      tma_load_2d(dst, &p.mapA[type < 2 ? type : 2], full0 + 8 * ks, ks * 64, mpair * 256 + rank * 128);
      tma_load_3d(dst + 16384, &p.mapB[type], full0 + 8 * ks, 0, ks * 64, nt * 4);
      tma_load_3d(dst + 32768, &p.mapB[type], full0 + 8 * ks, 0, ks * 64, nt * 4 + 2);
    }
    for (int i = 0; i < K1_STAGES; i++) mbar_init(empty0 + 8 * i, 4);
    mbar_init(pub, 8);
    mbar_init(lready, 1);
    asm volatile("fence.mbarrier_init.release.cluster;" ::: "memory");
  }
  __syncthreads();
  cluster_sync_relaxed();
  pdl_launch();
  const uint16_t* sched = p.sched + cl * K1_MAXITEMS;
  if (wg == 0) {
    asm volatile("setmaxnreg.dec.sync.aligned.u32 56;");
    if (threadIdx.x == 0) {
      int s = 0;
      uint32_t ph = 0;
      TRACE_DECL;
      uint32_t item = 0xFFFF;
      for (int it = 0; it < K1_MAXITEMS; it++) {
        item = sched[it];
        if (item >= 0xFF00) break;
        const int type = item >> 7, mpair = (item >> 4) & 7, nt = item & 15;
        const CUtensorMap* ma = &p.mapA[type < 2 ? type : 2];
        const CUtensorMap* mb = &p.mapB[type];
        const int nk = type < 2 ? 16 : 8;
        const int row = mpair * 256 + rank * 128;
        for (int ks = it == 0 ? K1_STAGES : 0; ks < nk; ks++) {
          mbar_wait(empty0 + 8 * s, ph);
          const uint32_t dst = sbase + s * K1_STAGE_BYTES;
          mbar_expect_tx(full0 + 8 * s, K1_STAGE_BYTES);
          tma_load_2d(dst, ma, full0 + 8 * s, ks * 64, row);
          tma_load_3d_mc(dst + 16384 + rank * 16384, mb, full0 + 8 * s, 0, ks * 64, nt * 4 + rank * 2, (uint16_t)3);
          if ((ks & 1) == 0) TRACE(0);
          if (++s == K1_STAGES) { s = 0; ph ^= 1; }
        }
      }
      if (item >= 0xFF00 && item != 0xFFFF) {
        const int lidx = (item & 0x7F) * 2 + rank;
        mbar_wait(lready, 0);
        asm volatile("fence.proxy.async;" ::: "memory");
        for (int i = 0; i < p.l_units; i++) {
          const int u = min(lidx + i * p.l_ctas, 255);
          const int blk = u >> 5, par = (u >> 4) & 1, hp = u & 15;
          mbar_wait(empty0 + 8 * s, ph);
          const uint32_t dst = sbase + s * K1_STAGE_BYTES, halo = sbase + K1_HALO + s * 2048;
          mbar_expect_tx(full0 + 8 * s, L_BYTES);
          const int pl = hp * 2 + par;
          tma_load_3d(dst + L_Q, &p.mapL, full0 + 8 * s, 0, blk * 128, pl);
          tma_load_3d(dst + L_K, &p.mapL, full0 + 8 * s, 0, blk * 128, 32 + pl);
          tma_load_3d(halo, &p.mapLh, full0 + 8 * s, 0, blk * 128 - 8, 32 + pl);
          tma_load_3d(dst + L_V, &p.mapL, full0 + 8 * s, 0, blk * 128, 64 + pl);
          tma_load_3d(halo + 1024, &p.mapLh, full0 + 8 * s, 0, blk * 128 - 8, 64 + pl);
          if (++s == K1_STAGES) { s = 0; ph ^= 1; }
        }
      }
      for (int i = 0; i < K1_STAGES; i++) {
        mbar_wait(empty0 + 8 * s, ph);
        if (++s == K1_STAGES) { s = 0; ph ^= 1; }
      }
      TRACE_END(0);
    } else if (threadIdx.x == 32) {
      uint32_t ph = 0;
      for (int it = 0; it < K1_MAXITEMS; it++) {
        const uint32_t item = sched[it];
        if (item >= 0xFF00) break;
        if ((item >> 7) == 0) {
          mbar_wait(pub, ph);
          ph ^= 1;
          __threadfence();
          asm volatile("red.relaxed.gpu.global.add.u32 [%0], 1;" ::"l"(p.flags + ((item >> 4) & 7)) : "memory");
        }
      }
      uint32_t last = 0xFFFF;
      for (int it = 0; it < K1_MAXITEMS; it++) {
        last = sched[it];
        if (last >= 0xFF00) break;
      }
      if (last >= 0xFF00 && last != 0xFFFF) {
        for (int i = 0; i < 8; i++) wait_flag(p.flags + i, QKV_FLAG_FULL);
        mbar_arrive(lready);
      }
    }
  } else {
    asm volatile("setmaxnreg.inc.sync.aligned.u32 224;");
    const int cw = wg - 1;
    const int warp = (threadIdx.x >> 5) & 3, lane = threadIdx.x & 31;
    const int g = lane >> 2, tq = lane & 3;
    float acc[128];
    uint32_t pk[64];
    bf16* po = nullptr;
    int pld8 = 0;
    int ptype = -1;
    int s = 0;
    uint32_t ph = 0;
    const bool signaller = (lane == 0) && (warp < 2);
    auto store_chunk = [&](int a) {
      bf16* q = po + (a >> 1) * PLANE + (a & 1) * 32;
      *reinterpret_cast<uint4*>(q) = make_uint4(pk[8 * a], pk[8 * a + 1], pk[8 * a + 2], pk[8 * a + 3]);
      *reinterpret_cast<uint4*>(q + pld8) = make_uint4(pk[8 * a + 4], pk[8 * a + 5], pk[8 * a + 6], pk[8 * a + 7]);
    };
    auto publish = [&]() {
      if (ptype == 0) {
        __syncwarp();
        if (lane == 0) mbar_arrive(pub);
      }
    };
    uint32_t item = 0xFFFF;
    if (cw == 1) bar_arrive(1, 256);
    mbar_wait_u<false>(full0, 0);
    for (int it = 0; it < K1_MAXITEMS; it++) {
      item = sched[it];
      if (item >= 0xFF00) break;
      const int type = item >> 7, mpair = (item >> 4) & 7, nt = item & 15;
      const int nk = type < 2 ? 16 : 8;
      const bool lastitem = it + 1 == K1_MAXITEMS || sched[it + 1] >= 0xFF00;
      auto kpair = [&](bool first, bool more) {
        const uint32_t base = sbase + s * K1_STAGE_BYTES;
        const uint64_t da = mkdesc(base + cw * 8192, 16, 1024);
        const uint64_t db = mkdesc(base + 16384, 8192, 1024);
        bar_sync(1 + cw, 256);
        wg_fence();
#pragma unroll
        for (int k = 0; k < 4; k++) wgmma_n256_ss_tb(acc, da + k * 2, db + k * 128, !first || k != 0);
        wg_commit();
        mbar_wait_u<false>(full0 + 8 * s + 8, ph);
        wg_fence();
#pragma unroll
        for (int k = 0; k < 4; k++) {
          wgmma_n256_ss_tb(acc, da + (K1_STAGE_BYTES >> 4) + k * 2, db + (K1_STAGE_BYTES >> 4) + k * 128, 1);
          if (k == HANDOVER - 1 || k == 3) wg_commit();
        }
        wg_wait<2>();
        if (signaller) mbar_arrive_cta(empty0 + 8 * s, warp);
        wg_wait<1>();
        bar_arrive(2 - cw, 256);
        const int sp = s;
        s ^= 2;
        if (s == 0) ph ^= 1;
        if (more) mbar_wait_u<false>(full0 + 8 * s, ph);
        wg_wait<0>();
        if (signaller) mbar_arrive_cta(empty0 + 8 * sp + 8, warp);
      };
#pragma unroll
      for (int pr = 0; pr < 4; pr++) {
        kpair(pr == 0, pr < 3 || nk > 8 || !lastitem);
        if (ptype >= 0 && pr < 3) {
          store_chunk(3 * pr);
          store_chunk(3 * pr + 1);
          if (pr < 2) store_chunk(3 * pr + 2);
          else publish();
        }
      }
      for (int pr = 4; pr < nk / 2; pr++) kpair(false, pr + 1 < nk / 2 || !lastitem);
      fence_regs(acc);
      if ((threadIdx.x & 127) == 0) PROF_C(0, 2 + it * 4 + cw * 2);
      if (type == 1) {
#pragma unroll
        for (int i = 0; i < 128; i++) acc[i] *= 0.08838834764831845f * 1.4426950408889634f;
      }
#pragma unroll
      for (int a = 0; a < 8; a++) {
        pk[8 * a + 0] = pack_bf16(acc[16 * a + 0], acc[16 * a + 1]);
        pk[8 * a + 1] = pack_bf16(acc[16 * a + 4], acc[16 * a + 5]);
        pk[8 * a + 2] = pack_bf16(acc[16 * a + 8], acc[16 * a + 9]);
        pk[8 * a + 3] = pack_bf16(acc[16 * a + 12], acc[16 * a + 13]);
        pk[8 * a + 4] = pack_bf16(acc[16 * a + 2], acc[16 * a + 3]);
        pk[8 * a + 5] = pack_bf16(acc[16 * a + 6], acc[16 * a + 7]);
        pk[8 * a + 6] = pack_bf16(acc[16 * a + 10], acc[16 * a + 11]);
        pk[8 * a + 7] = pack_bf16(acc[16 * a + 14], acc[16 * a + 15]);
      }
      const int row = mpair * 256 + rank * 128 + cw * 64 + warp * 16 + g;
      po = p.out[type] + nt * 4 * PLANE + (type == 0 ? (row & 1) * (PLANE / 2) + (row >> 1) * 64 : row * 64) + tq * 8;
      pld8 = type == 0 ? 4 * 64 : 8 * 64;
      ptype = type;
      if ((threadIdx.x & 127) == 0) PROF_C(0, 3 + it * 4 + cw * 2);
    }
    const bool dolocal = item >= 0xFF00 && item != 0xFFFF;
    if (!dolocal || ptype == 0) {
#pragma unroll
      for (int a = 0; a < 8; a++) store_chunk(a);
      publish();
    }
    if (cw == 0) bar_sync(1, 256);
    if (dolocal) {
      const int lidx = (item & 0x7F) * 2 + rank;
      const int t = cw * 4 + warp;
      auto unit = [&](int i) {
        const int u = min(lidx + i * p.l_ctas, 255);
        const int blk = u >> 5, par = (u >> 4) & 1, hp = u & 15;
        mbar_wait_u<false>(full0 + 8 * s, ph);
        local_attn_warp(sbase + s * K1_STAGE_BYTES, sbase + K1_HALO + s * 2048,
                        p.oA + (size_t)hp * PLANE + (blk * 256 + par + 2 * (16 * t + g)) * 64 + tq * 8, t, blk == 0 && t == 0, lane);
        bar_sync(3 + cw, 128);
        if (signaller) mbar_arrive(empty0 + 8 * s);
        if (++s == K1_STAGES) { s = 0; ph ^= 1; }
      };
#pragma unroll
      for (int i = 0; i < 4; i++) {
        if (i < p.l_units) unit(i);
        if (ptype > 0) {
          store_chunk(2 * i);
          store_chunk(2 * i + 1);
        }
      }
      for (int i = 4; i < p.l_units; i++) unit(i);
      if (threadIdx.x == 128) PROF_C(0, 58);
    }
    if (threadIdx.x == 128) { PROF_G(0, 60); PROF_C(0, 61); }
  }
}

constexpr int K2_CTAS = 132;
constexpr int KB_MAXITEMS = 8;
constexpr int KB_KV = 6 * 16384;
constexpr int KB_BAR = KB_KV + 4 * 32768;
constexpr int KB_SMEM = KB_BAR + 256 + 2560 + 256;

struct KBParams {
  CUtensorMap mapQ;
  CUtensorMap mapK, mapV;
  CUtensorMap mapKh, mapVh;
  const bf16 *q, *k, *v;
  bf16* ctx;
  uint32_t* flags;
  uint32_t zero;
  uint16_t sched[K2_CTAS * KB_MAXITEMS];
};

template <int TB>
__device__ __forceinline__ void wgmma_n128_ss_lo(float (&d)[64], uint32_t da, uint32_t db, int scale_d) {
  asm volatile("{\n.reg .pred p;\n.reg .b64 da, db;\n.reg .b32 hi;\nmov.b32 hi, 0x40000040;\nmov.b64 da, {%64, hi};\nmov.b64 db, {%65, hi};\n"
               "setp.ne.b32 p, %66, 0;\n"
               "wgmma.mma_async.sync.aligned.m64n128k16.f32.bf16.bf16 " ACC64 ", da, db, p, 1, 1, 0, %67;\n}\n"
               : OP64(d)
               : "r"(da), "r"(db), "r"(scale_d), "n"(TB));
}
__device__ __forceinline__ void wgmma_n64_ss_lo(float (&d)[64], uint32_t da, uint32_t db, int scale_d) {
  asm volatile("{\n.reg .pred p;\n.reg .b64 da, db;\n.reg .b32 hi;\nmov.b32 hi, 0x40000040;\nmov.b64 da, {%32, hi};\nmov.b64 db, {%33, hi};\n"
               "setp.ne.b32 p, %34, 0;\n"
               "wgmma.mma_async.sync.aligned.m64n64k16.f32.bf16.bf16 "
               "{%0,%1,%2,%3,%4,%5,%6,%7,%8,%9,%10,%11,%12,%13,%14,%15,%16,%17,%18,%19,%20,%21,%22,%23,%24,%25,%26,%27,%28,%29,%30,%31},"
               " da, db, p, 1, 1, 0, 0;\n}\n"
               : R8(d, 0), R8(d, 8), R8(d, 16), R8(d, 24)
               : "r"(da), "r"(db), "r"(scale_d));
}
__device__ __forceinline__ void wgmma_n128_rs_tb_lo(float (&d)[64], uint32_t a0, uint32_t a1, uint32_t a2, uint32_t a3, uint32_t db,
                                                    int scale_d) {
  asm volatile("{\n.reg .pred p;\n.reg .b64 db;\n.reg .b32 hi;\nmov.b32 hi, 0x40000040;\nmov.b64 db, {%68, hi};\n"
               "setp.ne.b32 p, %69, 0;\n"
               "wgmma.mma_async.sync.aligned.m64n128k16.f32.bf16.bf16 " ACC64 ", {%64,%65,%66,%67}, db, p, 1, 1, 1;\n}\n"
               : OP64(d)
               : "r"(a0), "r"(a1), "r"(a2), "r"(a3), "r"(db), "r"(scale_d));
}
__device__ __forceinline__ bool wg_any(int id, bool v) {
  uint32_t r;
  asm volatile("{\n.reg .pred p, q, u;\nsetp.ne.u32 p, %1, 0;\nbar.red.or.pred q, %2, 128, p;\nvote.sync.any.pred u, q, 0xffffffff;\nselp.u32 %0, 1, 0, u;\n}"
               : "=r"(r)
               : "r"((uint32_t)v), "r"(id)
               : "memory");
  return r != 0;
}

#define STAMP(k)
#define STAMP_NEXT()
#define ISTAMP(k)

__device__ __forceinline__ void mbar_arrive_if0(uint32_t bar, uint32_t sel) {
  asm volatile("{\n.reg .pred p;\nsetp.eq.u32 p, %1, 0;\n@p mbarrier.arrive.shared::cta.b64 _, [%0];\n}" ::"r"(bar), "r"(sel) : "memory");
}

__device__ __noinline__ void attn_fallback(const bf16* __restrict__ q, const bf16* __restrict__ k, const bf16* __restrict__ v,
                                              bf16* __restrict__ ctx, int h, int row0, int lane) {
  const int g = lane >> 2, tq = lane & 3;
  const size_t coff = (size_t)h * 2 * PLANE + tq * 8;
  float o[16][4];
#pragma unroll
  for (int i = 0; i < 16; i++) o[i][0] = o[i][1] = o[i][2] = o[i][3] = 0.f;
  float m0 = -INFINITY, m1 = -INFINITY, l0 = 0.f, l1 = 0.f;
#pragma unroll 1
  for (int k0 = 0; k0 < row0 + 16; k0 += 16) {
    float sc[2][4] = {{0.f, 0.f, 0.f, 0.f}, {0.f, 0.f, 0.f, 0.f}};
#pragma unroll 1
    for (int cg = 0; cg < 4; cg++) {
      const uint4 qa = __ldcg(reinterpret_cast<const uint4*>(q + (row0 + g) * 64 + coff + (cg >> 1) * PLANE + (cg & 1) * 32));
      const uint4 qb = __ldcg(reinterpret_cast<const uint4*>(q + (row0 + g + 8) * 64 + coff + (cg >> 1) * PLANE + (cg & 1) * 32));
#pragma unroll
      for (int t = 0; t < 2; t++) {
        const uint4 kk = __ldcg(reinterpret_cast<const uint4*>(k + (k0 + 8 * t + g) * 64 + coff + (cg >> 1) * PLANE + (cg & 1) * 32));
        mma_16816(sc[t], qa.x, qb.x, qa.y, qb.y, kk.x, kk.y);
        mma_16816(sc[t], qa.z, qb.z, qa.w, qb.w, kk.z, kk.w);
      }
    }
    float x0 = -INFINITY, x1 = -INFINITY;
#pragma unroll
    for (int t = 0; t < 2; t++) {
#pragma unroll
      for (int e = 0; e < 2; e++) {
        const int key = k0 + 8 * t + 2 * tq + e;
        if (key > row0 + g) sc[t][e] = -INFINITY;
        if (key > row0 + g + 8) sc[t][2 + e] = -INFINITY;
        x0 = fmaxf(x0, sc[t][e]);
        x1 = fmaxf(x1, sc[t][2 + e]);
      }
    }
    x0 = fmaxf(x0, __shfl_xor_sync(0xffffffffu, x0, 1));
    x1 = fmaxf(x1, __shfl_xor_sync(0xffffffffu, x1, 1));
    x0 = fmaxf(x0, __shfl_xor_sync(0xffffffffu, x0, 2));
    x1 = fmaxf(x1, __shfl_xor_sync(0xffffffffu, x1, 2));
    const float n0 = fmaxf(m0, x0), n1 = fmaxf(m1, x1);
    const float a0 = ex2(m0 - n0), a1 = ex2(m1 - n1);
    m0 = n0;
    m1 = n1;
    l0 *= a0;
    l1 *= a1;
    uint32_t pa[4];
#pragma unroll
    for (int t = 0; t < 2; t++) {
      const float e0 = ex2(sc[t][0] - m0), e1 = ex2(sc[t][1] - m0);
      const float e2 = ex2(sc[t][2] - m1), e3 = ex2(sc[t][3] - m1);
      l0 += e0 + e1;
      l1 += e2 + e3;
      pa[2 * t] = pack_bf16(e0, e1);
      pa[2 * t + 1] = pack_bf16(e2, e3);
    }
#pragma unroll
    for (int cg = 0; cg < 4; cg++) {
      const uint4 va = __ldcg(reinterpret_cast<const uint4*>(v + (k0 + g) * 64 + coff + (cg >> 1) * PLANE + (cg & 1) * 32));
      const uint4 vb = __ldcg(reinterpret_cast<const uint4*>(v + (k0 + 8 + g) * 64 + coff + (cg >> 1) * PLANE + (cg & 1) * 32));
#pragma unroll
      for (int r = 0; r < 4; r++) {
        const uint32_t w0 = r == 0 ? va.x : r == 1 ? va.y : r == 2 ? va.z : va.w;
        const uint32_t w1 = r == 0 ? vb.x : r == 1 ? vb.y : r == 2 ? vb.z : vb.w;
        float(&oo)[4] = o[4 * cg + r];
        oo[0] *= a0;
        oo[1] *= a0;
        oo[2] *= a1;
        oo[3] *= a1;
        mma_16816(oo, pa[0], pa[1], pa[2], pa[3], movm_t(w0), movm_t(w1));
      }
    }
  }
  l0 += __shfl_xor_sync(0xffffffffu, l0, 1);
  l1 += __shfl_xor_sync(0xffffffffu, l1, 1);
  l0 += __shfl_xor_sync(0xffffffffu, l0, 2);
  l1 += __shfl_xor_sync(0xffffffffu, l1, 2);
  const float i0 = 1.f / l0, i1 = 1.f / l1;
  bf16* o0 = ctx + (size_t)h * 2 * PLANE + (row0 + g) * 64 + 2 * tq;
#pragma unroll
  for (int i = 0; i < 16; i++) {
    *reinterpret_cast<uint32_t*>(o0 + (i >> 3) * PLANE + 8 * (i & 7)) = pack_bf16(o[i][0] * i0, o[i][1] * i0);
    *reinterpret_cast<uint32_t*>(o0 + (i >> 3) * PLANE + 8 * 64 + 8 * (i & 7)) = pack_bf16(o[i][2] * i1, o[i][3] * i1);
  }
}

#define SPLIT_DEP 0
#define SPLIT_EARLY 0
#define KB_LIMIT 1.2089258e24f
#define KB_LOW 9.094947e-13f
__device__ __forceinline__ uint32_t fma_bf16x2(uint32_t a, uint32_t b, uint32_t c) {
  uint32_t d;
  asm("fma.rn.bf16x2 %0, %1, %2, %3;" : "=r"(d) : "r"(a), "r"(b), "r"(c));
  return d;
}
__device__ __forceinline__ bool attn_epilogue_checked(float (&O)[64], float l0, float l1, bf16* dst  ) {
  l0 += __shfl_xor_sync(0xffffffffu, l0, 1);
  l1 += __shfl_xor_sync(0xffffffffu, l1, 1);
  l0 += __shfl_xor_sync(0xffffffffu, l0, 2);
  l1 += __shfl_xor_sync(0xffffffffu, l1, 2);
  const float i0 = rcp(l0), i1 = rcp(l1);
  uint32_t z0 = 0, z1 = 0;
#pragma unroll
  for (int a = 0; a < 4; a++) {
    uint4 v0, v1;
    v0.x = pack_bf16(O[16 * a + 0] * i0, O[16 * a + 1] * i0);
    v0.y = pack_bf16(O[16 * a + 4] * i0, O[16 * a + 5] * i0);
    v0.z = pack_bf16(O[16 * a + 8] * i0, O[16 * a + 9] * i0);
    v0.w = pack_bf16(O[16 * a + 12] * i0, O[16 * a + 13] * i0);
    v1.x = pack_bf16(O[16 * a + 2] * i1, O[16 * a + 3] * i1);
    v1.y = pack_bf16(O[16 * a + 6] * i1, O[16 * a + 7] * i1);
    v1.z = pack_bf16(O[16 * a + 10] * i1, O[16 * a + 11] * i1);
    v1.w = pack_bf16(O[16 * a + 14] * i1, O[16 * a + 15] * i1);
    *reinterpret_cast<uint4*>(dst + (a >> 1) * PLANE + (a & 1) * 32) = v0;
    *reinterpret_cast<uint4*>(dst + (a >> 1) * PLANE + (a & 1) * 32 + 8 * 64) = v1;
    z0 = fma_bf16x2(v0.x, v0.y, z0);
    z1 = fma_bf16x2(v1.x, v1.y, z1);
    z0 = fma_bf16x2(v0.z, v0.w, z0);
    z1 = fma_bf16x2(v1.z, v1.w, z1);
  }
  const uint32_t z = ((z0 & 0x7F807F80u) + 0x00800080u) | ((z1 & 0x7F807F80u) + 0x00800080u);
  const bool bad = !(l0 <= KB_LIMIT && l0 >= KB_LOW) || !(l1 <= KB_LIMIT && l1 >= KB_LOW) || (z & 0x80008000u) != 0;
  return !__any_sync(0xffffffffu, bad);
}

struct EpiState { float i0, i1; uint32_t z0, z1; };
__device__ __forceinline__ void epi_begin(EpiState& e, float l0, float l1) {
  l0 += __shfl_xor_sync(0xffffffffu, l0, 1);
  l1 += __shfl_xor_sync(0xffffffffu, l1, 1);
  l0 += __shfl_xor_sync(0xffffffffu, l0, 2);
  l1 += __shfl_xor_sync(0xffffffffu, l1, 2);
  e.i0 = rcp(l0);
  e.i1 = rcp(l1);
  const bool bad = !(l0 <= KB_LIMIT && l0 >= KB_LOW) || !(l1 <= KB_LIMIT && l1 >= KB_LOW);
  e.z0 = bad ? 0x7F807F80u : 0;
  e.z1 = 0;
}
template <int A0, int A1>
__device__ __forceinline__ void epi_part(EpiState& e, float (&O)[64], bf16* dst) {
#pragma unroll
  for (int a = A0; a < A1; a++) {
    uint4 v0, v1;
    v0.x = pack_bf16(O[16 * a + 0] * e.i0, O[16 * a + 1] * e.i0);
    v0.y = pack_bf16(O[16 * a + 4] * e.i0, O[16 * a + 5] * e.i0);
    v0.z = pack_bf16(O[16 * a + 8] * e.i0, O[16 * a + 9] * e.i0);
    v0.w = pack_bf16(O[16 * a + 12] * e.i0, O[16 * a + 13] * e.i0);
    v1.x = pack_bf16(O[16 * a + 2] * e.i1, O[16 * a + 3] * e.i1);
    v1.y = pack_bf16(O[16 * a + 6] * e.i1, O[16 * a + 7] * e.i1);
    v1.z = pack_bf16(O[16 * a + 10] * e.i1, O[16 * a + 11] * e.i1);
    v1.w = pack_bf16(O[16 * a + 14] * e.i1, O[16 * a + 15] * e.i1);
    *reinterpret_cast<uint4*>(dst + (a >> 1) * PLANE + (a & 1) * 32) = v0;
    *reinterpret_cast<uint4*>(dst + (a >> 1) * PLANE + (a & 1) * 32 + 8 * 64) = v1;
    e.z0 = fma_bf16x2(v0.x, v0.y, e.z0);
    e.z1 = fma_bf16x2(v1.x, v1.y, e.z1);
    e.z0 = fma_bf16x2(v0.z, v0.w, e.z0);
    e.z1 = fma_bf16x2(v1.z, v1.w, e.z1);
  }
}
__device__ __forceinline__ bool epi_end(const EpiState& e) {
  const uint32_t z = ((e.z0 & 0x7F807F80u) + 0x00800080u) | ((e.z1 & 0x7F807F80u) + 0x00800080u);
  return !__any_sync(0xffffffffu, (z & 0x80008000u) != 0);
}

__global__ __launch_bounds__(512, 1) void k2_attn3(const __grid_constant__ KBParams p) {
  extern __shared__ __align__(1024) uint8_t smem_kb[];
  const uint32_t sbase = smem_u32(smem_kb);
  if (sbase & 1023) __trap();
  const uint32_t qfull0 = sbase + KB_BAR, qempty0 = qfull0 + 48, kvfull0 = qfull0 + 96, kvempty0 = qfull0 + 128;
  const uint32_t kvbase = sbase + KB_KV;
  const int wg = __reduce_min_sync(0xffffffffu, (int)(threadIdx.x >> 7));
  if (threadIdx.x == 0) {
    for (int i = 0; i < 6; i++) {
      mbar_init(qfull0 + 8 * i, 1);
      mbar_init(qempty0 + 8 * i, 1);
    }
    for (int i = 0; i < 4; i++) {
      mbar_init(kvfull0 + 8 * i, 1);
      mbar_init(kvempty0 + 8 * i, 3);
    }

    asm volatile("fence.mbarrier_init.release.cluster;" ::: "memory");
  }
  __syncthreads();
  if (threadIdx.x == 64) {
    prefetch_tmap(&p.mapQ);
    prefetch_tmap(&p.mapK);
    prefetch_tmap(&p.mapV);
    prefetch_tmap(&p.mapKh);
    prefetch_tmap(&p.mapVh);
  }
  const uint16_t* sched = p.sched + blockIdx.x * KB_MAXITEMS;
  if (wg == 0) {
    asm volatile("setmaxnreg.dec.sync.aligned.u32 32;");
    const int warp = threadIdx.x >> 5;
    if ((threadIdx.x & 31) == 0) {
      auto load_q = [&](uint32_t item, int w, int qb) {
        const int b = max(3 * (int)(item & 15) - 1 + (int)((item >> (9 + 2 * w)) & 3), 0);
        mbar_expect_tx(qfull0 + 8 * qb, 16384);
        tma_load_3d(sbase + qb * 16384, &p.mapQ, qfull0 + 8 * qb, 0, b * 64, ((item >> 4) & 31) * 2);
      };
      if (warp == 0) {
        uint32_t pc = 0;
        PROF_G(1, 0);
        PROF_C(1, 1);
        TRACE_DECL;
        TRACE(1);
        pdl_wait();
        PROF_G(1, 2);
        PROF_C(1, 3);
        load_q(sched[0], 0, 0);
        for (int it = 0; it < KB_MAXITEMS; it++) {
          const uint32_t item = sched[it];
          if (item == 0xFFFF) break;
          const int h = (item >> 4) & 31, g = item & 15;
          const int n = ((3 * g + 1) >> 1) + 1;
          for (int j = 0; j < n; j++) {
            const uint32_t nskip = (j == n - 1 && g > 0) ? 1 + (g & 1) : 0;
            uint32_t sl = pc & 3;
            mbar_wait(kvempty0 + 8 * sl, ((pc >> 2) & 1) ^ 1);
            if (nskip) mbar_arrive_n(kvempty0 + 8 * sl, nskip);
            mbar_expect_tx(kvfull0 + 8 * sl, 32768);
            if (nskip == 2) {
              tma_load_3d(kvbase + sl * 32768, &p.mapKh, kvfull0 + 8 * sl, 0, j * 128, h * 2);
              tma_load_3d(kvbase + sl * 32768 + 16384, &p.mapKh, kvfull0 + 8 * sl, 0, j * 128, h * 2 + 1);
              tma_load_3d(kvbase + sl * 32768 + 8192, &p.mapVh, kvfull0 + 8 * sl, 0, j * 128, h * 2);
              tma_load_3d(kvbase + sl * 32768 + 24576, &p.mapVh, kvfull0 + 8 * sl, 0, j * 128, h * 2 + 1);
              pc++;
              continue;
            }
            tma_load_3d(kvbase + sl * 32768, &p.mapK, kvfull0 + 8 * sl, 0, j * 128, h * 2);
            if (pc == 0) {
              load_q(item, 1, 1);
              load_q(item, 2, 2);
            }
            pc++;
            sl = pc & 3;
            mbar_wait(kvempty0 + 8 * sl, ((pc >> 2) & 1) ^ 1);
            if (nskip) mbar_arrive_n(kvempty0 + 8 * sl, nskip);
            mbar_expect_tx(kvfull0 + 8 * sl, 32768);
            tma_load_3d(kvbase + sl * 32768, &p.mapV, kvfull0 + 8 * sl, 0, j * 128, h * 2);
            TRACE(1);
            pc++;
          }
        }
      } else {
        const int w = warp - 1;
        mbar_wait(kvempty0, 0);
        pdl_wait();
        if (w == 2) {
          __threadfence();
          pdl_launch();
        }
        if (w == 2 && blockIdx.x == 0)
          for (int i = 0; i < 8; i++) p.flags[i] = 0;
        for (int it = 1; it < KB_MAXITEMS; it++) {
          const uint32_t item = sched[it];
          if (item == 0xFFFF) break;
          const int qb = (it & 1) * 3 + w;
          mbar_wait(qempty0 + 8 * qb, ((it >> 1) & 1) ^ 1);
          load_q(item, w, qb);
        }
      }
    }
  } else {
    asm volatile("setmaxnreg.inc.sync.aligned.u32 160;");
    const int cw = wg - 1;
    float O[64], S[64];
    float l0 = 0.f, l1 = 0.f;
    auto turn_qk = [&]() { bar_sync(4 + cw, 256); };
    auto done_qk = [&]() { bar_arrive(7 + (cw == 0 ? 2 : cw - 1), 256); };
    auto turn_pv = [&](uint32_t dep = 0) {
      bar_sync((7 + cw) | dep, 256);
    };
    auto done_pv = [&]() { bar_arrive(4 + (cw == 0 ? 2 : cw - 1), 256); };
    if (cw == 1) done_pv();
    if (cw == 2) { turn_pv(); done_pv(); }
    const uint32_t sel = threadIdx.x & 127;
    const int wq = __reduce_min_sync(0xffffffffu, (int)((threadIdx.x >> 5) & 3));
    auto block = [&](uint32_t item, int w) { return max(3 * (int)(item & 15) - 1 + (int)((item >> (9 + 2 * w)) & 3), 0); };
    uint32_t tc = 0;
    int it = 0;
    uint32_t item = sched[0];
    int rem = (block(item, cw) >> 1) + 1;
    bool bodd = block(item, cw) & 1;
    int idle = 0;
    uint32_t failed = 0;
    uint32_t poff = 0;
    bool first = true, pending = false, end = false;
    EpiState es;
    es.i0 = es.i1 = 0.f;
    es.z0 = es.z1 = 0;
    ISTAMP(0);
    mbar_wait_u<false>(qfull0 + 8 * cw, 0);
    mbar_wait_u<false>(kvfull0, 0);
    ISTAMP(3);
    auto epilogue = [&]() {
      const int lane = threadIdx.x & 31;
      it--; ISTAMP(4); it++;
      if (!attn_epilogue_checked(O, l0, l1, p.ctx + poff + (wq * 16 + (lane >> 2)) * 64 + (lane & 3) * 8)) failed |= 1u << (it - 1);
      it--; ISTAMP(5); it++;
    };
    auto round = [&](auto half_c) {
      constexpr bool HALF = decltype(half_c)::value;
      constexpr int NI = HALF ? 8 : 16;
      const uint32_t qb = (it & 1) * 3 + cw;
      const uint32_t shared = HALF ? (item & 1) & (item >> (10 + 2 * cw)) : 0;
      const uint32_t tv = tc + 1 - shared;
      {
        const uint32_t dq = ((sbase >> 4) + qb * 1024) | (1u << 16);
        const uint32_t dk = ((kvbase >> 4) + (tc & 3) * 2048) | (1u << 16);
        turn_qk();
        STAMP(0);
        wg_fence();
#pragma unroll
        for (int k = 0; k < 8; k++) {
          if (HALF) wgmma_n64_ss_lo(S, dq + (k >> 2) * 512 + (k & 3) * 2, dk + (k >> 2) * 1024 + (k & 3) * 2, k != 0);
          else wgmma_n128_ss_lo<0>(S, dq + (k >> 2) * 512 + (k & 3) * 2, dk + (k >> 2) * 1024 + (k & 3) * 2, k != 0);
        }
        wg_commit();
        done_qk();
      }
      if (pending) {
        wg_wait<1>();
        const int lane = threadIdx.x & 31;
        epi_part<E4, 4>(es, O, p.ctx + poff + (wq * 16 + (lane >> 2)) * 64 + (lane & 3) * 8);
        if (!epi_end(es)) failed |= 1u << (it - 1);
        pending = false;
      }
      wg_wait<0>();
#pragma unroll
      for (int i = 0; i < 4 * NI; i++) asm volatile("" : "+f"(S[i])::"memory");
      STAMP(1);
      mbar_arrive_if0(kvempty0 + 8 * (tc & 3), sel | shared);
      if (HALF || rem == 1) {
        mbar_arrive_if0(qempty0 + 8 * qb, sel);
        const int lane = threadIdx.x & 31;
        const int row = wq * 16 + (lane >> 2) - 2 * (lane & 3);
#pragma unroll
        for (int i = 0; i < 8; i++) {
#pragma unroll
          for (int e = 0; e < 2; e++) {
            if (8 * i + e > row) S[4 * (NI - 8 + i) + e] = -INFINITY;
            if (8 * i + e > row + 8) S[4 * (NI - 8 + i) + 2 + e] = -INFINITY;
          }
        }
      }
      uint32_t P[2 * NI];
#define SPLIT 0
      constexpr int N1 = HALF ? NI : NI - SPLIT;
      float s0 = 0.f, s1 = 0.f, t0 = 0.f, t1 = 0.f;
      auto soft = [&](int i) {
        const float e0 = ex2(S[4 * i + 0]);
        const float e1 = ex2(S[4 * i + 1]);
        const float e2 = ex2(S[4 * i + 2]);
        const float e3 = ex2(S[4 * i + 3]);
        s0 += e0;
        t0 += e1;
        s1 += e2;
        t1 += e3;
        P[2 * i] = pack_bf16(e0, e1);
        P[2 * i + 1] = pack_bf16(e2, e3);
      };
#pragma unroll
      for (int i = 0; i < N1; i++) soft(i);
      if (N1 == NI) {
        l0 += s0 + t0;
        l1 += s1 + t1;
      }
      fence_regs(O);
#pragma unroll
      for (int i = 0; i < 2 * N1; i++) asm volatile("" : "+r"(P[i])::"memory");
      STAMP(2);
      mbar_wait_u<false>(kvfull0 + 8 * (tv & 3), (tv >> 2) & 1);
      if (N1 == NI) turn_pv(((__float_as_uint(l0) ^ __float_as_uint(l1)) ^ P[2 * NI - 1]) & p.zero);
      else turn_pv(((__float_as_uint(s0) ^ __float_as_uint(s1)) ^ (__float_as_uint(t0) ^ __float_as_uint(t1)) ^ P[2 * N1 - 1]) & p.zero);
      STAMP(3);
      wg_fence();
      const uint32_t dv = ((kvbase >> 4) + (tv & 3) * 2048 + shared * 512) | (1024u << 16);
#pragma unroll
      for (int k = 0; k < N1 / 2; k++)
        wgmma_n128_rs_tb_lo(O, P[4 * k], P[4 * k + 1], P[4 * k + 2], P[4 * k + 3], dv + k * 128, k != 0 || !first);
      wg_commit();
      if (N1 < NI) {
#pragma unroll
        for (int i = 4 * N1; i < 4 * NI; i++) asm volatile("" : "+f"(S[i])::"memory");
#pragma unroll
        for (int i = N1; i < NI; i++) soft(i);
        l0 += s0 + t0;
        l1 += s1 + t1;
#pragma unroll
        for (int i = 2 * N1; i < 2 * NI; i++) asm volatile("" : "+r"(P[i])::"memory");
        wg_fence();
#pragma unroll
        for (int k = N1 / 2; k < NI / 2; k++)
          wgmma_n128_rs_tb_lo(O, P[4 * k], P[4 * k + 1], P[4 * k + 2], P[4 * k + 3], dv + k * 128, 1);
        wg_commit();
      }
      done_pv();
      STAMP(4);
      first = false;
      tc = tv + 1;
      rem--;
      if (HALF || rem == 0) {
        const int b = block(item, cw);
        poff = ((item >> 4) & 31) * (2 * PLANE) + b * (64 * 64);
        idle += (block(item, 0) >> 1) - (b >> 1);
        const uint32_t skip = (b >> 1) < ((3 * (int)(item & 15) + 1) >> 1) ? 2 - (item & 1) : 0;
        pending = first = true;
        it++;
        item = it < KB_MAXITEMS ? sched[it] : 0xFFFFu;
        end = item == 0xFFFF;
        ISTAMP(0);
        if (!end) {
          if (skip) tc += skip;
          ISTAMP(1);
          rem = (block(item, cw) >> 1) + 1;
          bodd = block(item, cw) & 1;
          mbar_wait_u<false>(qfull0 + 8 * ((it & 1) * 3 + cw), (it >> 1) & 1);
          ISTAMP(2);
        }
      }
      if (!end) mbar_wait_u<false>(kvfull0 + 8 * (tc & 3), (tc >> 2) & 1);
      wg_wait<0>();
      fence_regs(O);
      STAMP(5);
      STAMP_NEXT();
      mbar_arrive_if0(kvempty0 + 8 * (tv & 3), sel);
      if ((HALF || first) && !end) {
        const int lane = threadIdx.x & 31;
        epi_begin(es, l0, l1);
        epi_part<0, E4>(es, O, p.ctx + poff + (wq * 16 + (lane >> 2)) * 64 + (lane & 3) * 8);
        l0 = l1 = 0.f;
      }
    };
    while (true) {
      if (rem == 1 && !bodd) round(std::true_type{});
      else round(std::false_type{});
      if (end) {
        if (idle > 0) {
          turn_qk();
          done_qk();
          turn_pv();
          done_pv();
        }
        if (cw == 0) {
          turn_qk();
          done_qk();
        }
        if (cw == 1) turn_qk();
        epilogue();
        __syncwarp();
        for (int j = 0; failed >> j; j++) {
          if ((failed >> j) & 1) {
            const uint32_t fi = sched[j];
            attn_fallback(p.q, p.k, p.v, p.ctx, (fi >> 4) & 31, block(fi, cw) * 64 + wq * 16, threadIdx.x & 31);
          }
        }
        break;
      }
    }
  }
}

constexpr int K3_STAGES = 6;
constexpr int K3_STAGE_BYTES = 32768;
constexpr int K3_SMEM = K3_STAGES * K3_STAGE_BYTES + 32768 + 1024;

struct K3Params {
  CUtensorMap mapA[2];
  CUtensorMap mapB[2];
  CUtensorMap mapO;
};

__global__ __cluster_dims__(2, 1, 1) __launch_bounds__(384, 1) void k3_outproj(const __grid_constant__ K3Params p) {
  extern __shared__ uint8_t smem_raw[];
  __shared__ uint64_t bars[2 * K3_STAGES];
  const uint32_t sbase = (smem_u32(smem_raw) + 1023) & ~1023u;
  const uint32_t full0 = smem_u32(&bars[0]), empty0 = smem_u32(&bars[K3_STAGES]);
  const int wg = __shfl_sync(0xffffffffu, (int)(threadIdx.x >> 7), 0);
  const uint32_t rank = cluster_rank();
  const int cl = blockIdx.x >> 1;
  const int mpair = cl >> 3, nt = cl & 7;
  if (threadIdx.x == 0) {
    PROF_G(2, 0);
    PROF_C(2, 1);
    for (int i = 0; i < K3_STAGES; i++) {
      mbar_init(full0 + 8 * i, 1);
      mbar_init(empty0 + 8 * i, 4);
    }
    asm volatile("fence.mbarrier_init.release.cluster;" ::: "memory");
  }
  if (threadIdx.x == 32) {
    prefetch_tmap(&p.mapA[0]);
    prefetch_tmap(&p.mapB[0]);
    prefetch_tmap(&p.mapO);
    prefetch_tmap(&p.mapA[1]);
    prefetch_tmap(&p.mapB[1]);
  }
  __syncthreads();
  cluster_sync_relaxed();
  if (wg == 0) {
    asm volatile("setmaxnreg.dec.sync.aligned.u32 40;");
    if (threadIdx.x == 0) {
      int s = 0;
      uint32_t ph = 1;
      const int row = mpair * 256 + rank * 128;
      TRACE_DECL;
      for (int t = 0; t < 2; t++) {
        const int nk = t == 0 ? 16 : 64;
        if (t == 1) pdl_wait();
        if (t == 1) PROF_G(2, 20);
        for (int ks = 0; ks < nk; ks++) {
          mbar_wait(empty0 + 8 * s, ph);
          const uint32_t dst = sbase + s * K3_STAGE_BYTES;
          {
          mbar_expect_tx(full0 + 8 * s, K3_STAGE_BYTES);
          tma_load_3d(dst, &p.mapA[t], full0 + 8 * s, 0, row, ks);
          tma_load_3d_mc(dst + 16384 + rank * 8192, &p.mapB[t], full0 + 8 * s, 0, ks * 64, nt * 2 + rank, (uint16_t)3);
          }
          if ((ks & 3) == 0) TRACE(2);
          if (++s == K3_STAGES) { s = 0; ph ^= 1; }
        }
      }
      for (int i = 0; i < K3_STAGES; i++) {
        mbar_wait(empty0 + 8 * s, ph);
        if (++s == K3_STAGES) { s = 0; ph ^= 1; }
      }
      TRACE_END(2);
    }
  } else {
    asm volatile("setmaxnreg.inc.sync.aligned.u32 232;");
    const int cw = wg - 1;
    const int warp = (threadIdx.x >> 5) & 3, lane = threadIdx.x & 31;
    float acc[64];
    int s = 0;
    uint32_t ph = 0;
    const bool signaller = (lane == 0) && (warp < 2);
    const uint32_t stg = sbase + K3_STAGES * K3_STAGE_BYTES + (cw * 4 + warp) * 4096;
    for (int t = 0; t < 2; t++) {
      const int nk = t == 0 ? 16 : 64;
      int prev = 0;
      for (int ks = 0; ks < nk; ks++) {
        mbar_wait(full0 + 8 * s, ph);
        const uint32_t base = sbase + s * K3_STAGE_BYTES;
        const uint64_t da = mkdesc(base + cw * 8192, 16, 1024);
        const uint64_t db = mkdesc(base + 16384, 8192, 1024);
        wg_fence();
#pragma unroll
        for (int k = 0; k < 4; k++) wgmma_n128_ss<1>(acc, da + k * 2, db + k * 128, (ks | k) != 0);
        wg_commit();
        if (ks > 0) {
          wg_wait<1>();
          if (signaller) mbar_arrive_cta(empty0 + 8 * prev, warp);
        }
        prev = s;
        if (++s == K3_STAGES) { s = 0; ph ^= 1; }
      }
      wg_wait<0>();
      if (signaller) mbar_arrive_cta(empty0 + 8 * prev, warp);
      fence_regs(acc);
      if ((threadIdx.x & 127) == 0) PROF_C(2, 2 + t * 4 + cw * 2);
      if (t == 1) {
        if (lane == 0) asm volatile("cp.async.bulk.wait_group.read 0;" ::: "memory");
        __syncwarp();
      }
      const int srow = (lane & 7) + ((lane >> 3) & 1) * 8;
#pragma unroll
      for (int jj = 0; jj < 8; jj++) {
        const uint32_t r0 = pack_bf16(acc[8 * jj + 0], acc[8 * jj + 1]);
        const uint32_t r1 = pack_bf16(acc[8 * jj + 2], acc[8 * jj + 3]);
        const uint32_t r2 = pack_bf16(acc[8 * jj + 4], acc[8 * jj + 5]);
        const uint32_t r3 = pack_bf16(acc[8 * jj + 6], acc[8 * jj + 7]);
        const int chunk = (2 * jj + (lane >> 4)) & 7;
        const uint32_t addr = stg + (jj >> 2) * 2048 + srow * 128 + ((chunk ^ (srow & 7)) << 4);
        asm volatile("stmatrix.sync.aligned.m8n8.x4.shared.b16 [%0], {%1,%2,%3,%4};" ::"r"(addr), "r"(r0), "r"(r1), "r"(r2), "r"(r3)
                     : "memory");
      }
      asm volatile("fence.proxy.async.shared::cta;" ::: "memory");
      __syncwarp();
      if (lane == 0) {
        const int orow = mpair * 256 + rank * 128 + cw * 64 + warp * 16;
        const int ocol = t * 1024 + nt * 128;
        tma_store_2d(&p.mapO, stg, ocol, orow);
        tma_store_2d(&p.mapO, stg + 2048, ocol + 64, orow);
        asm volatile("cp.async.bulk.commit_group;" ::: "memory");
      }
      if ((threadIdx.x & 127) == 0) PROF_C(2, 3 + t * 4 + cw * 2);
    }
    if (threadIdx.x == 128) { PROF_G(2, 60); PROF_C(2, 61); }
    if (lane == 0) asm volatile("cp.async.bulk.wait_group.read 0;" ::: "memory");
  }
}

typedef CUresult (*EncodeFn)(CUtensorMap*, CUtensorMapDataType, cuuint32_t, void*, const cuuint64_t*, const cuuint64_t*,
                             const cuuint32_t*, const cuuint32_t*, CUtensorMapInterleave, CUtensorMapSwizzle, CUtensorMapL2promotion,
                             CUtensorMapFloatOOBfill);

void make_map(EncodeFn enc, CUtensorMap* m, const void* ptr, int rank, const uint64_t* dims, const uint64_t* strides,
              const uint32_t* box) {
  cuuint64_t gd[3], gs[2];
  cuuint32_t bd[3], es[3] = {1, 1, 1};
  for (int i = 0; i < rank; i++) {
    gd[i] = dims[i];
    bd[i] = box[i];
  }
  for (int i = 0; i + 1 < rank; i++) gs[i] = strides[i];
  enc(m, CU_TENSOR_MAP_DATA_TYPE_BFLOAT16, rank, const_cast<void*>(ptr), gd, gs, bd, es, CU_TENSOR_MAP_INTERLEAVE_NONE,
      CU_TENSOR_MAP_SWIZZLE_128B, CU_TENSOR_MAP_L2_PROMOTION_L2_128B, CU_TENSOR_MAP_FLOAT_OOB_FILL_NONE);
}
void map_2d(EncodeFn enc, CUtensorMap* m, const void* ptr, uint64_t rows, uint64_t cols, uint32_t boxrows) {
  uint64_t dims[2] = {cols, rows}, strides[1] = {cols * 2};
  uint32_t box[2] = {64, boxrows};
  make_map(enc, m, ptr, 2, dims, strides, box);
}
void map_planes(EncodeFn enc, CUtensorMap* m, const void* ptr, uint64_t rows, uint64_t planes, uint32_t boxrows, uint32_t boxplanes) {
  uint64_t dims[3] = {64, rows, planes}, strides[2] = {128, rows * 128};
  uint32_t box[3] = {64, boxrows, boxplanes};
  make_map(enc, m, ptr, 3, dims, strides, box);
}
void map_3d(EncodeFn enc, CUtensorMap* m, const void* ptr, uint64_t rows, uint64_t cols, uint32_t boxrows, uint32_t boxblk) {
  uint64_t dims[3] = {64, rows, cols / 64}, strides[2] = {cols * 2, 128};
  uint32_t box[3] = {64, boxrows, boxblk};
  make_map(enc, m, ptr, 3, dims, strides, box);
}

struct HostState {
  K1Params k1;
  KBParams kb;
  K3Params k3;
  const void* in[9];
  void* out;
  bool valid;
};
HostState g_hs;

int build_k1_sched(uint16_t* sched) {
#define K1_A_AFTER 9
  int order[480], n = 0;
  for (int nt = 0; nt < 16; nt++) {
    if (nt == K1_A_AFTER)
      for (int mp = 0; mp < 8; mp++)
        for (int j = 0; j < 12; j++) order[n++] = (0 << 7) | (mp << 4) | j;
    for (int mp = 0; mp < 8; mp++) order[n++] = (1 << 7) | (mp << 4) | nt;
    for (int mp = 0; mp < 8; mp++) order[n++] = (2 << 7) | (mp << 4) | nt;
    for (int mp = 0; mp < 8; mp++) order[n++] = (3 << 7) | (mp << 4) | nt;
  }
  int load[K1_CLUSTERS] = {0}, cnt[K1_CLUSTERS] = {0};
  for (int i = 0; i < K1_CLUSTERS * K1_MAXITEMS; i++) sched[i] = 0xFFFF;
  int ord2[480], m = 0;
  const int tail_start = 96 + 13 * 24;
  for (int i = 0; i < tail_start; i++) ord2[m++] = order[i];
  for (int i = tail_start; i < 480; i++)
    if ((order[i] >> 7) == 1) ord2[m++] = order[i];
  for (int i = tail_start; i < 480; i++)
    if ((order[i] >> 7) != 1) ord2[m++] = order[i];
  for (int i = 0; i < 480; i++) {
    int best = 0;
    for (int c = 1; c < K1_CLUSTERS; c++)
      if (load[c] < load[best]) best = c;
    const int type = ord2[i] >> 7;
    load[best] += type < 2 ? 2 : 1;
    sched[best * K1_MAXITEMS + cnt[best]++] = (uint16_t)ord2[i];
  }
  int maxload = 0, nl = 0;
  for (int c = 0; c < K1_CLUSTERS; c++) maxload = load[c] > maxload ? load[c] : maxload;
  for (int c = 0; c < K1_CLUSTERS; c++)
    if (load[c] < maxload) sched[c * K1_MAXITEMS + cnt[c]] = (uint16_t)(0xFF00 | nl++);
  return nl;
}

void build_kb_sched(uint16_t* sched) {
  static const signed char bins[33][4] = {
      {4, 9, 0, -1}, {7, 7, -1, -1}, {10, 4, -1, -1}, {9, 3, 1, -1},  {8, 6, -1, -1},  {4, 10, -1, -1}, {2, 2, 9, -1},
      {6, 5, 2, -1}, {7, 5, 1, -1},  {7, 1, 5, -1},   {6, 4, 3, -1},  {10, 3, 0, -1},  {9, 3, 1, -1},   {8, 6, -1, -1},
      {10, 3, 0, -1}, {9, 2, 2, -1}, {4, 10, -1, -1}, {7, 5, 1, -1},  {9, 3, 1, -1},   {3, 1, 9, -1},   {6, 8, -1, -1},
      {10, 3, 0, -1}, {4, 7, 2, -1}, {8, 5, 0, -1},   {7, 0, 6, -1},  {7, 1, 5, -1},   {8, 0, 5, -1},   {8, 6, -1, -1},
      {6, 8, -1, -1}, {9, 2, 2, -1}, {4, 10, -1, -1}, {8, 5, 0, -1},  {10, 4, -1, -1}};
  static const int weight[11] = {2, 7, 11, 16, 20, 25, 29, 34, 38, 43, 47};
  int grp[K2_CTAS][4], start[K2_CTAS][4];
  for (int c = 0; c < K2_CTAS; c++) {
    const signed char* b = bins[c % 33];
    int n = 0;
    while (n < 4 && b[n] >= 0) n++;
    int t = 0;
    for (int i = 0; i < 4; i++) {
      grp[c][i] = i < n ? b[(i + c / 33) % n] : -1;
      start[c][i] = t;
      if (i < n) t += weight[grp[c][i]] + 1;
    }
  }
  for (int i = 0; i < K2_CTAS * KB_MAXITEMS; i++) sched[i] = 0xFFFF;
  for (int g = 0; g < 11; g++) {
    bool used[K2_CTAS][4] = {};
    for (int h = 31; h >= 0; h--) {
      int bc = -1, bi = 0;
      for (int c = 0; c < K2_CTAS; c++)
        for (int i = 0; i < 4; i++)
          if (grp[c][i] == g && !used[c][i] && (bc < 0 || start[c][i] < start[bc][bi])) { bc = c; bi = i; }
      used[bc][bi] = true;
      sched[bc * KB_MAXITEMS + bi] = (uint16_t)((h << 4) | g);
    }
  }
  static const int perms[6][3] = {{0, 1, 2}, {0, 2, 1}, {1, 0, 2}, {1, 2, 0}, {2, 0, 1}, {2, 1, 0}};
  for (int c = 0; c < K2_CTAS; c++) {
    int f[3] = {0, 0, 0};
    for (int i = 0; i < 4 && grp[c][i] >= 0; i++) {
      const int g = grp[c][i];
      for (int q = 0; q < 6; q++) {
        int nf[3];
        for (int w = 0; w < 3; w++) {
          const int b = 3 * g - 1 + perms[q][w];
          nf[w] = f[w] + ((b < 0 ? 0 : b) >> 1) + 1;
        }
        if (nf[0] >= nf[1] && nf[1] >= nf[2] && nf[0] - nf[2] <= 1) {
          for (int w = 0; w < 3; w++) f[w] = nf[w];
          sched[c * KB_MAXITEMS + i] |= (uint16_t)((perms[q][0] << 9) | (perms[q][1] << 11) | (perms[q][2] << 13));
          break;
        }
      }
    }
  }
}

void setup(void* const* d_in, void* d_out) {
  void* fn = nullptr;
  cudaDriverEntryPointQueryResult qr;
  cudaGetDriverEntryPoint("cuTensorMapEncodeTiled", &fn, cudaEnableDefault, &qr);
  EncodeFn enc = (EncodeFn)fn;
  void *qkvA, *q, *k, *v, *ctx, *oA, *flags;
  cudaGetSymbolAddress(&flags, g_flags);
  cudaGetSymbolAddress(&qkvA, g_qkvA);
  cudaGetSymbolAddress(&q, g_q);
  cudaGetSymbolAddress(&k, g_k);
  cudaGetSymbolAddress(&v, g_v);
  cudaGetSymbolAddress(&ctx, g_ctx);
  cudaGetSymbolAddress(&oA, g_oA);
  HostState& hs = g_hs;
  map_2d(enc, &hs.k1.mapA[0], d_in[0], 2048, 1024, 128);
  map_2d(enc, &hs.k1.mapA[1], d_in[3], 2048, 1024, 128);
  map_2d(enc, &hs.k1.mapA[2], d_in[4], 2048, 512, 128);
  map_3d(enc, &hs.k1.mapB[0], d_in[1], 1024, 3072, 64, 2);
  map_3d(enc, &hs.k1.mapB[1], d_in[5], 1024, 4096, 64, 2);
  map_3d(enc, &hs.k1.mapB[2], d_in[6], 512, 4096, 64, 2);
  map_3d(enc, &hs.k1.mapB[3], d_in[7], 512, 4096, 64, 2);
  hs.k1.out[0] = (bf16*)qkvA;
  hs.k1.out[1] = (bf16*)q;
  hs.k1.out[2] = (bf16*)k;
  hs.k1.out[3] = (bf16*)v;
  hs.k1.oA = (bf16*)oA;
  hs.k1.flags = (uint32_t*)flags;
  hs.kb.flags = (uint32_t*)flags;
  map_planes(enc, &hs.k1.mapL, qkvA, 1024, 96, 128, 1);
  map_planes(enc, &hs.k1.mapLh, qkvA, 1024, 96, 8, 1);
  const int nl = build_k1_sched(hs.k1.sched);
  hs.k1.l_ctas = 2 * nl;
  hs.k1.l_units = (256 + 2 * nl - 1) / (2 * nl);
  map_planes(enc, &hs.kb.mapQ, q, 2048, 64, 64, 2);
  map_planes(enc, &hs.kb.mapK, k, 2048, 64, 128, 2);
  map_planes(enc, &hs.kb.mapV, v, 2048, 64, 128, 2);
  map_planes(enc, &hs.kb.mapKh, k, 2048, 64, 64, 1);
  map_planes(enc, &hs.kb.mapVh, v, 2048, 64, 64, 1);
  hs.kb.q = (const bf16*)q;
  hs.kb.k = (const bf16*)k;
  hs.kb.v = (const bf16*)v;
  hs.kb.ctx = (bf16*)ctx;
  build_kb_sched(hs.kb.sched);
  cudaFuncSetAttribute(k2_attn3, cudaFuncAttributeMaxDynamicSharedMemorySize, KB_SMEM);
  map_planes(enc, &hs.k3.mapA[0], oA, 2048, 16, 128, 1);
  map_planes(enc, &hs.k3.mapA[1], ctx, 2048, 64, 128, 1);
  map_3d(enc, &hs.k3.mapB[0], d_in[2], 1024, 1024, 64, 1);
  map_3d(enc, &hs.k3.mapB[1], d_in[8], 4096, 1024, 64, 1);
  map_2d(enc, &hs.k3.mapO, d_out, 2048, 2048, 16);
  cudaFuncSetAttribute(k1_proj, cudaFuncAttributeMaxDynamicSharedMemorySize, K1_SMEM);
  cudaFuncSetAttribute(k3_outproj, cudaFuncAttributeMaxDynamicSharedMemorySize, K3_SMEM);
  for (int i = 0; i < 9; i++) hs.in[i] = d_in[i];
  hs.out = d_out;
  hs.valid = true;
}

}

extern "C" void kernel_launch(void* const* d_in, const int* in_sizes, int n_in, void* d_out, int out_size) {
  (void)in_sizes;
  (void)n_in;
  (void)out_size;
  bool ok = g_hs.valid && g_hs.out == d_out;
  for (int i = 0; ok && i < 9; i++) ok = g_hs.in[i] == d_in[i];
  if (!ok) setup(d_in, d_out);
  k1_proj<<<K1_CLUSTERS * 2, 384, K1_SMEM, cudaStreamPerThread>>>(g_hs.k1);
  cudaLaunchAttribute at[1];
  at[0].id = cudaLaunchAttributeProgrammaticStreamSerialization;
  at[0].val.programmaticStreamSerializationAllowed = 1;
  cudaLaunchConfig_t cfg = {};
  cfg.stream = cudaStreamPerThread;
  cfg.attrs = at;
  cfg.numAttrs = 1;
  cfg.gridDim = dim3(K2_CTAS);
  cfg.blockDim = dim3(512);
  cfg.dynamicSmemBytes = KB_SMEM;
  cudaLaunchKernelEx(&cfg, k2_attn3, g_hs.kb);
  cfg.gridDim = dim3(128);
  cfg.blockDim = dim3(384);
  cfg.dynamicSmemBytes = K3_SMEM;
  cudaLaunchKernelEx(&cfg, k3_outproj, g_hs.k3);
}
```

```cpp
#include <cuda_runtime.h>
#include <cuda_bf16.h>
#include <cuda.h>
#include <stdint.h>
#include <type_traits>

namespace {

typedef __nv_bfloat16 bf16;

__device__ __forceinline__ uint32_t smem_u32(const void* p) { return (uint32_t)__cvta_generic_to_shared(p); }
__device__ __forceinline__ void mbar_init(uint32_t bar, uint32_t cnt) {
  asm volatile("mbarrier.init.shared::cta.b64 [%0], %1;" ::"r"(bar), "r"(cnt) : "memory");
}
__device__ __forceinline__ void mbar_expect_tx(uint32_t bar, uint32_t bytes) {
  asm volatile("mbarrier.arrive.expect_tx.shared::cta.b64 _, [%0], %1;" ::"r"(bar), "r"(bytes) : "memory");
}
__device__ __forceinline__ void mbar_arrive_n(uint32_t bar, uint32_t n) {
  asm volatile("mbarrier.arrive.shared::cta.b64 _, [%0], %1;" ::"r"(bar), "r"(n) : "memory");
}
__device__ __forceinline__ void mbar_arrive_if0(uint32_t bar, uint32_t sel) {
  asm volatile("{\n.reg .pred p;\nsetp.eq.u32 p, %1, 0;\n@p mbarrier.arrive.shared::cta.b64 _, [%0];\n}" ::"r"(bar), "r"(sel) : "memory");
}
__device__ __forceinline__ void mbar_arrive_cta_if0(uint32_t bar, uint32_t cta, uint32_t sel) {
  asm volatile("{\n.reg .pred p;\n.reg .b32 ra;\nsetp.eq.u32 p, %2, 0;\nmapa.shared::cluster.u32 ra, %0, %1;\n"
               "@p mbarrier.arrive.shared::cluster.b64 _, [ra];\n}" ::"r"(bar),
               "r"(cta), "r"(sel)
               : "memory");
}
__device__ __forceinline__ void mbar_wait(uint32_t bar, uint32_t parity) {
  uint32_t done;
  uint32_t it = 0;
  while (true) {
    asm volatile("{\n.reg .pred p;\nmbarrier.try_wait.parity.shared::cta.b64 p, [%1], %2, 1000;\nselp.u32 %0, 1, 0, p;\n}"
                 : "=r"(done)
                 : "r"(bar), "r"(parity)
                 : "memory");
    if (done) break;
    if (++it > (1u << 20)) __trap();
  }
}
__device__ __forceinline__ void mbar_wait_u(uint32_t bar, uint32_t parity) {
  uint32_t it = 0;
  while (true) {
    uint32_t done;
    asm volatile("{\n.reg .pred p, q;\nmbarrier.try_wait.parity.shared::cta.b64 p, [%1], %2;\nvote.sync.all.pred q, p, 0xffffffff;\nselp.u32 %0, 1, 0, q;\n}"
                 : "=r"(done)
                 : "r"(bar), "r"(parity)
                 : "memory");
    if (done) break;
    if (++it > (1u << 20)) break;
  }
}
#define DECLARE_READY() asm volatile(".reg .pred RDYA, RDYB;")
__device__ __forceinline__ void test_a(uint32_t bar, uint32_t parity) {
  asm volatile("mbarrier.test_wait.parity.shared::cta.b64 RDYA, [%0], %1;" ::"r"(bar), "r"(parity) : "memory");
}
__device__ __forceinline__ void test_b(uint32_t bar, uint32_t parity) {
  asm volatile("mbarrier.test_wait.parity.shared::cta.b64 RDYB, [%0], %1;" ::"r"(bar), "r"(parity) : "memory");
}
__device__ __forceinline__ uint32_t ready_b(uint32_t dep = 0) {
  uint32_t r;
  asm volatile("{\n.reg .pred q;\nsetp.eq.and.u32 q, %1, 0, RDYB;\nvote.sync.all.pred q, q, 0xffffffff;\nselp.u32 %0, 1, 0, q;\n}" : "=r"(r) : "r"(dep) : "memory");
  return r;
}
__device__ __forceinline__ uint32_t ready_ab() {
  uint32_t r;
  asm volatile("{\n.reg .pred q;\nand.pred q, RDYA, RDYB;\nvote.sync.all.pred q, q, 0xffffffff;\nselp.u32 %0, 1, 0, q;\n}" : "=r"(r)::"memory");
  return r;
}
__device__ __forceinline__ void tma_load_3d(uint32_t dst, const CUtensorMap* m, uint32_t bar, int c0, int c1, int c2) {
  asm volatile("cp.async.bulk.tensor.3d.shared::cluster.global.mbarrier::complete_tx::bytes [%0], [%1, {%3, %4, %5}], [%2];" ::"r"(dst),
               "l"(m), "r"(bar), "r"(c0), "r"(c1), "r"(c2)
               : "memory");
}
__device__ __forceinline__ void tma_load_3d_mc(uint32_t dst, const CUtensorMap* m, uint32_t bar, int c0, int c1, int c2, uint16_t mask) {
  asm volatile(
      "cp.async.bulk.tensor.3d.shared::cluster.global.mbarrier::complete_tx::bytes.multicast::cluster [%0], [%1, {%3, %4, %5}], [%2], %6;" ::"r"(dst),
      "l"(m), "r"(bar), "r"(c0), "r"(c1), "r"(c2), "h"(mask)
      : "memory");
}
__device__ __forceinline__ void tma_load_5d(uint32_t dst, const CUtensorMap* m, uint32_t bar, int c0, int c4) {
  asm volatile("cp.async.bulk.tensor.5d.shared::cluster.global.mbarrier::complete_tx::bytes [%0], [%1, {%3, 0, 0, 0, %4}], [%2];" ::"r"(dst),
               "l"(m), "r"(bar), "r"(c0), "r"(c4)
               : "memory");
}
__device__ __forceinline__ void bulk_load(uint32_t dst, const void* src, uint32_t bytes, uint32_t bar) {
  asm volatile("cp.async.bulk.shared::cluster.global.mbarrier::complete_tx::bytes [%0], [%1], %2, [%3];" ::"r"(dst), "l"(src), "r"(bytes), "r"(bar)
               : "memory");
}
__device__ __forceinline__ void bulk_load_mc(uint32_t dst, const void* src, uint32_t bytes, uint32_t bar, uint16_t mask) {
  asm volatile("cp.async.bulk.shared::cluster.global.mbarrier::complete_tx::bytes.multicast::cluster [%0], [%1], %2, [%3], %4;" ::"r"(dst),
               "l"(src), "r"(bytes), "r"(bar), "h"(mask)
               : "memory");
}
__device__ __forceinline__ void tma_store_2d(const CUtensorMap* m, uint32_t src, int c0, int c1) {
  asm volatile("cp.async.bulk.tensor.2d.global.shared::cta.bulk_group [%0, {%2, %3}], [%1];" ::"l"(m), "r"(src), "r"(c0), "r"(c1)
               : "memory");
}
__device__ __forceinline__ void prefetch_tmap(const CUtensorMap* m) { asm volatile("prefetch.tensormap [%0];" ::"l"(m) : "memory"); }
__device__ __forceinline__ void cluster_sync_relaxed() {
  asm volatile("barrier.cluster.arrive.relaxed.aligned;\nbarrier.cluster.wait.aligned;" ::: "memory");
}
__device__ __forceinline__ uint32_t pack_bf16(float lo, float hi) {
  uint32_t r;
  asm("cvt.rn.bf16x2.f32 %0, %1, %2;" : "=r"(r) : "f"(hi), "f"(lo));
  return r;
}
__device__ __forceinline__ float ex2(float x) {
  float y;
  asm("ex2.approx.ftz.f32 %0, %1;" : "=f"(y) : "f"(x));
  return y;
}
__device__ __forceinline__ float rcp(float x) {
  float y;
  asm("rcp.approx.ftz.f32 %0, %1;" : "=f"(y) : "f"(x));
  return y;
}
__device__ __forceinline__ uint32_t fma_bf16x2(uint32_t a, uint32_t b, uint32_t c) {
  uint32_t d;
  asm("fma.rn.bf16x2 %0, %1, %2, %3;" : "=r"(d) : "r"(a), "r"(b), "r"(c));
  return d;
}
__device__ __forceinline__ void wg_fence() { asm volatile("wgmma.fence.sync.aligned;" ::: "memory"); }
__device__ __forceinline__ void wg_commit() { asm volatile("wgmma.commit_group.sync.aligned;" ::: "memory"); }
template <int N>
__device__ __forceinline__ void wg_wait() {
  asm volatile("wgmma.wait_group.sync.aligned %0;" ::"n"(N) : "memory");
}
template <int N>
__device__ __forceinline__ void fence_regs(float (&d)[N]) {
#pragma unroll
  for (int i = 0; i < N; i++) asm volatile("" : "+f"(d[i])::"memory");
}
__device__ __forceinline__ void bar_sync(int id, int n) { asm volatile("bar.sync %0, %1;" ::"r"(id), "r"(n) : "memory"); }
__device__ __forceinline__ void bar_arrive(int id, int n) { asm volatile("bar.arrive %0, %1;" ::"r"(id), "r"(n) : "memory"); }

#define R8(a, i) "+f"(a[i]), "+f"(a[i + 1]), "+f"(a[i + 2]), "+f"(a[i + 3]), "+f"(a[i + 4]), "+f"(a[i + 5]), "+f"(a[i + 6]), "+f"(a[i + 7])
#define OP32(d, o) R8(d, o), R8(d, o + 8), R8(d, o + 16), R8(d, o + 24)
#define L32A "%0,%1,%2,%3,%4,%5,%6,%7,%8,%9,%10,%11,%12,%13,%14,%15,%16,%17,%18,%19,%20,%21,%22,%23,%24,%25,%26,%27,%28,%29,%30,%31"
#define L32B "%32,%33,%34,%35,%36,%37,%38,%39,%40,%41,%42,%43,%44,%45,%46,%47,%48,%49,%50,%51,%52,%53,%54,%55,%56,%57,%58,%59,%60,%61,%62,%63"
#define L32C "%64,%65,%66,%67,%68,%69,%70,%71,%72,%73,%74,%75,%76,%77,%78,%79,%80,%81,%82,%83,%84,%85,%86,%87,%88,%89,%90,%91,%92,%93,%94,%95"
#define L32D "%96,%97,%98,%99,%100,%101,%102,%103,%104,%105,%106,%107,%108,%109,%110,%111,%112,%113,%114,%115,%116,%117,%118,%119,%120,%121,%122,%123,%124,%125,%126,%127"
#define WG_PRE(a, b, s, ha, hb) "{\n.reg .pred p;\n.reg .b64 da, db;\nmov.b64 da, {" a ", " ha "};\nmov.b64 db, {" b ", " hb "};\nsetp.ne.b32 p, " s ", 0;\n"

constexpr uint32_t HI128 = 0x40000040;
constexpr uint32_t HI64 = 0x80000080;
template <int TB>
__device__ __forceinline__ void wgmma_n128(float (&d)[64], uint32_t da, uint32_t ha, uint32_t db, uint32_t hb, int scale_d) {
  asm volatile(WG_PRE("%64", "%65", "%66", "%67", "%68") "wgmma.mma_async.sync.aligned.m64n128k16.f32.bf16.bf16 {" L32A "," L32B "}, da, db, p, 1, 1, 0, %69;\n}\n"
               : OP32(d, 0), OP32(d, 32)
               : "r"(da), "r"(db), "r"(scale_d), "r"(ha), "r"(hb), "n"(TB));
}
__device__ __forceinline__ void wgmma_n192_tb(float (&d)[96], uint32_t da, uint32_t db, int scale_d) {
  asm volatile(WG_PRE("%96", "%97", "%98", "%99", "%99") "wgmma.mma_async.sync.aligned.m64n192k16.f32.bf16.bf16 {" L32A "," L32B "," L32C "}, da, db, p, 1, 1, 0, 1;\n}\n"
               : OP32(d, 0), OP32(d, 32), OP32(d, 64)
               : "r"(da), "r"(db), "r"(scale_d), "r"(HI128));
}
__device__ __forceinline__ void wgmma_n64(float (&d)[64], uint32_t da, uint32_t db, int scale_d) {
  asm volatile(WG_PRE("%32", "%33", "%34", "%35", "%35") "wgmma.mma_async.sync.aligned.m64n64k16.f32.bf16.bf16 {" L32A "}, da, db, p, 1, 1, 0, 0;\n}\n"
               : OP32(d, 0)
               : "r"(da), "r"(db), "r"(scale_d), "r"(HI64));
}
__device__ __forceinline__ void wgmma_n128_rs_tb(float (&d)[64], uint32_t a0, uint32_t a1, uint32_t a2, uint32_t a3, uint32_t db, int scale_d) {
  asm volatile("{\n.reg .pred p;\n.reg .b64 db;\nmov.b64 db, {%68, %70};\nsetp.ne.b32 p, %69, 0;\n"
               "wgmma.mma_async.sync.aligned.m64n128k16.f32.bf16.bf16 {" L32A "," L32B "}, {%64,%65,%66,%67}, db, p, 1, 1, 1;\n}\n"
               : OP32(d, 0), OP32(d, 32)
               : "r"(a0), "r"(a1), "r"(a2), "r"(a3), "r"(db), "r"(scale_d), "r"(HI64));
}
__device__ __forceinline__ void mma_16816(float (&c)[4], uint32_t a0, uint32_t a1, uint32_t a2, uint32_t a3, uint32_t b0, uint32_t b1) {
  asm volatile("mma.sync.aligned.m16n8k16.row.col.f32.bf16.bf16.f32 {%0,%1,%2,%3}, {%4,%5,%6,%7}, {%8,%9}, {%0,%1,%2,%3};"
               : "+f"(c[0]), "+f"(c[1]), "+f"(c[2]), "+f"(c[3])
               : "r"(a0), "r"(a1), "r"(a2), "r"(a3), "r"(b0), "r"(b1));
}
__device__ __forceinline__ void mma_1688(float (&c)[4], uint32_t a0, uint32_t a1, uint32_t b0) {
  asm volatile("mma.sync.aligned.m16n8k8.row.col.f32.bf16.bf16.f32 {%0,%1,%2,%3}, {%4,%5}, {%6}, {%0,%1,%2,%3};"
               : "+f"(c[0]), "+f"(c[1]), "+f"(c[2]), "+f"(c[3])
               : "r"(a0), "r"(a1), "r"(b0));
}
__device__ __forceinline__ void quad_sum(float& l0, float& l1) {
  const uint32_t h0 = __float_as_uint(l0) & 0xFFFFE000u, h1 = __float_as_uint(l1) & 0xFFFFE000u;
  const float r0 = l0 - __uint_as_float(h0), r1 = l1 - __uint_as_float(h1);
  asm volatile("{\n.reg .f32 c1, c3;\nmma.sync.aligned.m16n8k8.row.col.f32.tf32.tf32.f32 {%0,c1,%1,c3}, {%2,%3,%4,%5}, {%6,%6}, {%7,%7,%7,%7};\n}"
               : "=f"(l0), "=f"(l1)
               : "r"(h0), "r"(h1), "r"(__float_as_uint(r0)), "r"(__float_as_uint(r1)), "r"(0x3F800000), "f"(0.f));
}
__device__ __forceinline__ uint32_t movm_t(uint32_t x) {
  uint32_t y;
  asm volatile("movmatrix.sync.aligned.m8n8.trans.b16 %0, %1;" : "=r"(y) : "r"(x));
  return y;
}
__device__ __forceinline__ void sts128(uint32_t a, uint32_t x, uint32_t y, uint32_t z, uint32_t w) {
  asm volatile("st.shared.v4.u32 [%0], {%1,%2,%3,%4};" ::"r"(a), "r"(x), "r"(y), "r"(z), "r"(w) : "memory");
}
__device__ __forceinline__ void stg128_if0(uint4* a, uint32_t x, uint32_t y, uint32_t z, uint32_t w, uint32_t sel) {
  asm volatile("{\n.reg .pred p;\nsetp.eq.u32 p, %5, 0;\n@p st.global.v4.u32 [%0], {%1,%2,%3,%4};\n}" ::"l"(a), "r"(x), "r"(y), "r"(z), "r"(w),
               "r"(sel)
               : "memory");
}
__device__ __forceinline__ void lds128(uint32_t a, uint32_t& x, uint32_t& y, uint32_t& z, uint32_t& w) {
  asm volatile("ld.shared.v4.u32 {%0,%1,%2,%3}, [%4];" : "=r"(x), "=r"(y), "=r"(z), "=r"(w) : "r"(a) : "memory");
}

#define KVR 16
constexpr int PLANE = 2048 * 16;
constexpr int PL_Q = 0, PL_KV = 32, PL_OA = PL_KV + 4 * KVR, NPLANES = PL_OA + 8;
__device__ __align__(1024) uint4 g_scr[NPLANES * PLANE];
__device__ uint4 g_carry[16 * 128];
constexpr int F_Q = 0, F_CTX = 256, F_KV = 768, F_TD = 784, F_L = 800, F_CAR = 816, F_EPOCH = 832, F_END = 832 + 132;
__device__ uint32_t g_flags[F_END];

#define NTURN 256

enum { K_Q = 0, K_KV = 1, K_L = 2, K_T = 3, K_OA = 4, K_OB = 5, K_END = 7 };
constexpr int NCLUSTERS = 66, MAXITEMS = 16;
constexpr int A_STAGE = 16384, B_SLOT = 32768;
constexpr int SM_B = 6 * A_STAGE, SM_CARRY = SM_B + 4 * B_SLOT, SM_BAR = SM_CARRY + 2048, SM_TOTAL = SM_BAR + 512;

struct Params {
  CUtensorMap mapA[3];
  CUtensorMap mapB[6];
  CUtensorMap mapO[2];
  uint4* scr;
  uint4* carry;
  uint32_t* flags;
  uint32_t zero;
  uint16_t sched[NCLUSTERS * MAXITEMS];
};

__device__ __forceinline__ bool item_narrow(uint32_t item) { return (item & 0x204) == 0x204; }
__device__ __forceinline__ int item_nk(uint32_t item) {
  const uint32_t kind = item & 7;
  return (kind == K_KV ? 8 : kind == K_OB ? 64 : 16) >> item_narrow(item);
}
__device__ __forceinline__ int item_row(uint32_t kind, int g, int pos) {
  if (kind == K_L || kind == K_OA) return g == 0 ? (pos - 1) * 1024 : 64 * (3 * g - 2 + pos + (g > 5));
  return 64 * (3 * g - 1 + pos);
}

__device__ __forceinline__ void wait_flag(const uint32_t* f, uint32_t target) {
  uint32_t it = 0;
  while (true) {
    uint32_t v;
    asm volatile("ld.acquire.gpu.global.u32 %0, [%1];" : "=r"(v) : "l"(f) : "memory");
    if ((int)(v - target) >= 0) break;
    __nanosleep(40);
    if (++it > (1u << 18)) break;
  }
  asm volatile("fence.proxy.async.global;" ::: "memory");
}
__device__ __forceinline__ uint32_t wait_bit(const uint32_t* f, uint32_t inv, int bit) {
  uint32_t it = 0, v;
  while (true) {
    asm volatile("ld.acquire.gpu.global.u32 %0, [%1];" : "=r"(v) : "l"(f) : "memory");
    v ^= inv;
    if (v >> bit & 1) break;
    __nanosleep(40);
    if (++it > (1u << 18)) break;
  }
  asm volatile("fence.proxy.async.global;" ::: "memory");
  return v;
}
__device__ __forceinline__ void red_add(uint32_t* f) { asm volatile("red.relaxed.gpu.global.add.u32 [%0], 1;" ::"l"(f) : "memory"); }
__device__ __forceinline__ void red_xor(uint32_t* f, uint32_t v) {
  asm volatile("red.relaxed.gpu.global.xor.b32 [%0], %1;" ::"l"(f), "r"(v) : "memory");
}

__device__ __noinline__ void attn_fallback(uint4* q, const uint4* __restrict__ k, int row0, int lane) {
  const int g = lane >> 2, tq = lane & 3;
  q += row0 * 16;
  k += lane ^ (lane >> 3);
  const uint4* v = k + 2 * PLANE;
  float o[16][4];
#pragma unroll
  for (int i = 0; i < 16; i++) o[i][0] = o[i][1] = o[i][2] = o[i][3] = 0.f;
  float m0 = -INFINITY, m1 = -INFINITY, l0 = 0.f, l1 = 0.f;
#pragma unroll 1
  for (int k0 = 0; k0 < row0 + 16; k0 += 16) {
    float sc[2][4] = {{0.f, 0.f, 0.f, 0.f}, {0.f, 0.f, 0.f, 0.f}};
#pragma unroll 1
    for (int cg = 0; cg < 4; cg++) {
      const uint4 qa = __ldcg(q + cg * 32 + (lane ^ (lane >> 3)));
      const uint4 qb = __ldcg(q + 128 + cg * 32 + (lane ^ (lane >> 3)));
#pragma unroll
      for (int t = 0; t < 2; t++) {
        const uint4 kk = __ldcg(k + (k0 + 8 * t) * 16 + cg * 32);
        mma_16816(sc[t], qa.x, qb.x, qa.y, qb.y, kk.x, kk.y);
        mma_16816(sc[t], qa.z, qb.z, qa.w, qb.w, kk.z, kk.w);
      }
    }
    float x0 = -INFINITY, x1 = -INFINITY;
#pragma unroll
    for (int t = 0; t < 2; t++) {
#pragma unroll
      for (int e = 0; e < 2; e++) {
        const int key = k0 + 8 * t + 2 * tq + e;
        if (key > row0 + g) sc[t][e] = -INFINITY;
        if (key > row0 + g + 8) sc[t][2 + e] = -INFINITY;
        x0 = fmaxf(x0, sc[t][e]);
        x1 = fmaxf(x1, sc[t][2 + e]);
      }
    }
    x0 = fmaxf(x0, __shfl_xor_sync(0xffffffffu, x0, 1));
    x1 = fmaxf(x1, __shfl_xor_sync(0xffffffffu, x1, 1));
    x0 = fmaxf(x0, __shfl_xor_sync(0xffffffffu, x0, 2));
    x1 = fmaxf(x1, __shfl_xor_sync(0xffffffffu, x1, 2));
    const float n0 = fmaxf(m0, x0), n1 = fmaxf(m1, x1);
    const float a0 = ex2(m0 - n0), a1 = ex2(m1 - n1);
    m0 = n0;
    m1 = n1;
    l0 *= a0;
    l1 *= a1;
    uint32_t pa[4];
#pragma unroll
    for (int t = 0; t < 2; t++) {
      const float e0 = ex2(sc[t][0] - m0), e1 = ex2(sc[t][1] - m0);
      const float e2 = ex2(sc[t][2] - m1), e3 = ex2(sc[t][3] - m1);
      l0 += e0 + e1;
      l1 += e2 + e3;
      pa[2 * t] = pack_bf16(e0, e1);
      pa[2 * t + 1] = pack_bf16(e2, e3);
    }
#pragma unroll
    for (int cg = 0; cg < 4; cg++) {
      const uint4 va = __ldcg(v + k0 * 16 + cg * 32);
      const uint4 vb = __ldcg(v + k0 * 16 + 128 + cg * 32);
#pragma unroll
      for (int r = 0; r < 4; r++) {
        const uint32_t w0 = r == 0 ? va.x : r == 1 ? va.y : r == 2 ? va.z : va.w;
        const uint32_t w1 = r == 0 ? vb.x : r == 1 ? vb.y : r == 2 ? vb.z : vb.w;
        float(&oo)[4] = o[4 * cg + r];
        oo[0] *= a0;
        oo[1] *= a0;
        oo[2] *= a1;
        oo[3] *= a1;
        mma_16816(oo, pa[0], pa[1], pa[2], pa[3], movm_t(w0), movm_t(w1));
      }
    }
  }
  l0 += __shfl_xor_sync(0xffffffffu, l0, 1);
  l1 += __shfl_xor_sync(0xffffffffu, l1, 1);
  l0 += __shfl_xor_sync(0xffffffffu, l0, 2);
  l1 += __shfl_xor_sync(0xffffffffu, l1, 2);
  const float i0 = 1.f / l0, i1 = 1.f / l1;
  __syncwarp();
  uint32_t* o0 = reinterpret_cast<uint32_t*>(q + g * 4) + tq;
#pragma unroll
  for (int i = 0; i < 16; i++) {
    uint32_t* d = o0 + (i >> 2) * 128 + ((i & 3) ^ (g >> 1)) * 4;
    d[0] = pack_bf16(o[i][0] * i0, o[i][1] * i0);
    d[512] = pack_bf16(o[i][2] * i1, o[i][3] * i1);
  }
}

#define KB_LIMIT 1.2089258e24f
#define KB_LOW 9.094947e-13f
#define NXA 8
#define NP 4

__device__ __forceinline__ void local_attn(const uint32_t (&lo)[24], const uint32_t (&hi)[24], const uint32_t (&hk)[8], const uint32_t (&hv)[8],
                                           uint4* __restrict__ dst, bool first, int lane) {
  const int g = lane >> 2, tq = lane & 3;
  float s[2][3][4];
#pragma unroll
  for (int h = 0; h < 2; h++)
#pragma unroll
    for (int jj = 0; jj < 3; jj++) {
      s[h][jj][0] = s[h][jj][1] = s[h][jj][2] = s[h][jj][3] = 0.f;
#pragma unroll
      for (int st = 0; st < 2; st++) {
        const int c = 4 * h + 2 * st;
        mma_16816(s[h][jj], lo[c], hi[c], lo[c + 1], hi[c + 1], jj == 0 ? hk[c] : jj == 1 ? lo[8 + c] : hi[8 + c],
                  jj == 0 ? hk[c + 1] : jj == 1 ? lo[9 + c] : hi[9 + c]);
      }
    }
  const bool h0 = 2 * tq > g, h1 = 2 * tq + 1 > g;
  const uint32_t m = (h0 ? 0xFFFFu : 0u) | (h1 ? 0xFFFF0000u : 0u);
  float u0[2], u1[2], w0[2], w1[2], mu[2], mw[2];
#pragma unroll
  for (int h = 0; h < 2; h++) {
    u0[h] = h0 ? s[h][0][0] : s[h][1][0];
    u1[h] = h1 ? s[h][0][1] : s[h][1][1];
    w0[h] = h0 ? s[h][1][2] : s[h][2][2];
    w1[h] = h1 ? s[h][1][3] : s[h][2][3];
    if (first) {
      if (h0) u0[h] = -INFINITY;
      if (h1) u1[h] = -INFINITY;
    }
    mu[h] = fmaxf(u0[h], u1[h]);
    mw[h] = fmaxf(w0[h], w1[h]);
  }
#pragma unroll
  for (int o = 1; o <= 2; o++)
#pragma unroll
    for (int h = 0; h < 2; h++) {
      mu[h] = fmaxf(mu[h], __shfl_xor_sync(0xffffffffu, mu[h], o));
      mw[h] = fmaxf(mw[h], __shfl_xor_sync(0xffffffffu, mw[h], o));
    }
  const float c = 0.17677669529663687f * 1.4426950408889634f;
  float lu[2], lw[2];
#pragma unroll
  for (int h = 0; h < 2; h++) {
    u0[h] = ex2((u0[h] - mu[h]) * c);
    u1[h] = ex2((u1[h] - mu[h]) * c);
    w0[h] = ex2((w0[h] - mw[h]) * c);
    w1[h] = ex2((w1[h] - mw[h]) * c);
    lu[h] = u0[h] + u1[h];
    lw[h] = w0[h] + w1[h];
  }
#pragma unroll
  for (int o = 1; o <= 2; o++)
#pragma unroll
    for (int h = 0; h < 2; h++) {
      lu[h] += __shfl_xor_sync(0xffffffffu, lu[h], o);
      lw[h] += __shfl_xor_sync(0xffffffffu, lw[h], o);
    }
#pragma unroll
  for (int h = 0; h < 2; h++) {
    const float iu = rcp(lu[h]), iw = rcp(lw[h]);
    const uint32_t pu = pack_bf16(u0[h] * iu, u1[h] * iu), pw = pack_bf16(w0[h] * iw, w1[h] * iw);
    float o[4][4];
#pragma unroll
    for (int cc = 0; cc < 4; cc++) {
      o[cc][0] = o[cc][1] = o[cc][2] = o[cc][3] = 0.f;
      mma_16816(o[cc], pu & m, 0u, pu & ~m, pw & m, hv[4 * h + cc], lo[16 + 4 * h + cc]);
      mma_1688(o[cc], 0u, pw & ~m, hi[16 + 4 * h + cc]);
    }
    dst[h * 32] = make_uint4(pack_bf16(o[0][0], o[0][1]), pack_bf16(o[1][0], o[1][1]), pack_bf16(o[2][0], o[2][1]), pack_bf16(o[3][0], o[3][1]));
    dst[h * 32 + 128] =
        make_uint4(pack_bf16(o[0][2], o[0][3]), pack_bf16(o[1][2], o[1][3]), pack_bf16(o[2][2], o[2][3]), pack_bf16(o[3][2], o[3][3]));
  }
}

__global__ __cluster_dims__(2, 1, 1) __launch_bounds__(512, 1) void fused_kernel(const __grid_constant__ Params p) {
  extern __shared__ __align__(1024) uint8_t smem_dyn[];
  DECLARE_READY();
  const uint32_t sbase = smem_u32(smem_dyn);
  const uint32_t afull0 = sbase + SM_BAR, aempty0 = afull0 + 48, bfull0 = afull0 + 96, bempty0 = afull0 + 128, carbar = afull0 + 160,
                 pub0 = afull0 + 168;
  const uint32_t bbase = sbase + SM_B;
  const int wg = __reduce_min_sync(0xffffffffu, (int)(threadIdx.x >> 7));
  const uint32_t rank = blockIdx.x & 1;
  const uint16_t* sched = p.sched + (blockIdx.x >> 1) * MAXITEMS;

  auto fill_b = [&](uint32_t item, int t, uint32_t pb) {
    const uint32_t kind = item & 7, j = (item >> 7) & 15, sl = pb & 3;
    if (((item >> 3) & 15) == 0) mbar_arrive_n(bempty0 + 8 * sl, 1);
    mbar_expect_tx(bfull0 + 8 * sl, kind == K_L ? 24576 : 32768);
    const uint32_t nt = kind == K_KV ? j : 2 * j + rank, dst = bbase + sl * B_SLOT;
    const uint32_t cb = item_narrow(item) ? nt - 8 : nt * 2 + (t & 1), ks = item_narrow(item) ? t : t >> 1;
    if (kind == K_OA) {
      tma_load_5d(dst, &p.mapB[K_OA], bfull0 + 8 * sl, cb * 128, ks * 4);
      tma_load_5d(dst + 16384, &p.mapB[K_OA], bfull0 + 8 * sl, cb * 128 + 64, ks * 4);
    } else if (kind == K_L) {
      tma_load_3d(dst, &p.mapB[K_L], bfull0 + 8 * sl, nt * 64, t * 64, 0);
    } else {
      tma_load_3d(dst, &p.mapB[kind == K_KV ? 1 + 2 * rank : kind], bfull0 + 8 * sl, 0, ks * 128, cb * 2);
    }
  };
  auto fill_a = [&](uint32_t item, int d, int pos, uint32_t u, bool mc) {
    const uint32_t kind = item & 7;
    const int row = item_row(kind, (item >> 3) & 15, pos);
    const uint32_t dst = sbase + u * A_STAGE, bar = afull0 + 8 * u;
    mbar_expect_tx(bar, A_STAGE);
    if (kind >= K_OA) {
      bulk_load_mc(dst + rank * 8192, p.scr + ((kind == K_OA ? PL_OA : PL_Q) + d) * PLANE + row * 16 + rank * 512, 8192, bar, (uint16_t)3);
    } else {
      const int blk = 2 * d + (kind == K_L ? (row >> 10) * 16 : 0), r = kind == K_L ? row & 1023 : row;
      if (mc) {
        tma_load_3d_mc(dst + rank * 8192, &p.mapA[kind], bar, 0, r, blk + rank, (uint16_t)3);
      } else {
        tma_load_3d(dst, &p.mapA[kind], bar, 0, r, blk);
        tma_load_3d(dst + 8192, &p.mapA[kind], bar, 0, r, blk + 1);
      }
    }
  };
  if (threadIdx.x == 0) {
    for (int i = 0; i < 4; i++) {
      mbar_init(bfull0 + 8 * i, 1);
      mbar_init(bempty0 + 8 * i, 3);
    }
    asm volatile("fence.proxy.async.shared::cta;" ::: "memory");
    for (int t = 0; t < 4; t++) fill_b(sched[0], t, t);
  } else if (threadIdx.x == 32) {
    for (int i = 0; i < 6; i++) {
      mbar_init(afull0 + 8 * i, 1);
      mbar_init(aempty0 + 8 * i, 2);
    }
    asm volatile("fence.proxy.async.shared::cta;" ::: "memory");
    const int g0 = ((sched[0] >> 3) & 15) == 0;
    for (int w = 0; w + g0 < 3; w++) fill_a(sched[0], 0, w + g0, 2 * w, false);
    asm volatile("fence.mbarrier_init.release.cluster;" ::: "memory");
  } else if (threadIdx.x == 64) {
    mbar_init(carbar, 1);
    for (int i = 0; i < MAXITEMS; i++) mbar_init(pub0 + 8 * i, 12);
  }
  __syncthreads();
  cluster_sync_relaxed();

  if (wg == 0) {
    asm volatile("setmaxnreg.dec.sync.aligned.u32 32;");
    if (threadIdx.x == 0) {
      const uint32_t e = __ldcg(p.flags + F_EPOCH + blockIdx.x) + 1;
      uint32_t pb = 4;
      for (int it = 0; it < MAXITEMS; it++) {
        const uint32_t item = sched[it];
        const uint32_t kind = item & 7;
        if (kind == K_END) break;
        if (kind != K_T) {
          const int nk = item_nk(item);
          for (int t = it == 0 ? 4 : 0; t < nk; t++, pb++) {
            mbar_wait(bempty0 + 8 * (pb & 3), ((pb >> 2) & 1) ^ 1);
            fill_b(item, t, pb);
          }
        } else {
          const int g = (item >> 3) & 15, j = (item >> 7) & 15;
          const uint4* src = p.scr + (PL_KV + (j % KVR) * 4 + rank) * PLANE;
          const int n = ((3 * g + 1) >> 1) + 1;
          wait_flag(p.flags + F_KV + j, 22 * e);
          for (int t = 0; t < n; t++, src += 2048) {
            const uint32_t nskip = t == n - 1 ? 1 + (g & 1) : 0;
            uint32_t sl = pb & 3;
            mbar_wait(bempty0 + 8 * sl, ((pb >> 2) & 1) ^ 1);
            if (nskip) mbar_arrive_n(bempty0 + 8 * sl, nskip);
            mbar_expect_tx(bfull0 + 8 * sl, 32768);
            pb++;
            if (nskip == 2) {
              bulk_load(bbase + sl * B_SLOT, src, 16384, bfull0 + 8 * sl);
              bulk_load(bbase + sl * B_SLOT + 16384, src + 2 * PLANE, 16384, bfull0 + 8 * sl);
              continue;
            }
            bulk_load(bbase + sl * B_SLOT, src, 32768, bfull0 + 8 * sl);
            sl = pb & 3;
            mbar_wait(bempty0 + 8 * sl, ((pb >> 2) & 1) ^ 1);
            if (nskip) mbar_arrive_n(bempty0 + 8 * sl, nskip);
            mbar_expect_tx(bfull0 + 8 * sl, 32768);
            bulk_load(bbase + sl * B_SLOT, src + 2 * PLANE, 32768, bfull0 + 8 * sl);
            pb++;
          }
        }
      }
    } else if (threadIdx.x == 32) {
      const uint32_t e = __ldcg(p.flags + F_EPOCH + blockIdx.x) + 1;
      uint32_t pk = ((sched[0] >> 3) & 15) == 0 ? 0x0101 : 0x010101;
      auto next_stage = [&](uint32_t w) {
        const uint32_t n = pk >> (8 * w), u = 2 * w + (n & 1);
        mbar_wait(aempty0 + 8 * u, ((n >> 1) & 1) ^ 1);
        pk += 1u << (8 * w);
        return u;
      };
      for (int it = 0; it < MAXITEMS; it++) {
        const uint32_t item = sched[it];
        const uint32_t kind = item & 7;
        if (kind == K_END) break;
        const int g = (item >> 3) & 15, j = (item >> 7) & 15;
        const int nd = kind == K_T ? 1 : item_nk(kind) >> 1;
        if (kind == K_KV && j >= KVR) wait_flag(p.flags + F_TD + j - KVR, 22 * e);
        if (kind == K_OA) wait_flag(p.flags + F_L + g, 16 * e);
        if (kind == K_T) wait_flag(p.flags + F_Q + j * 16 + g, e);
        uint32_t heads = 0;
        for (int d = it == 0; d < nd; d++) {
          if (kind == K_OB && !(heads >> d & 1)) heads = wait_bit(p.flags + F_CTX + g * 32, (e & 1) - 1, d);
          for (int rho = 0; rho < 3 - (g == 0); rho++) {
            uint32_t w = rho + 3 - (item >> 11);
            if (w >= 3) w -= 3;
            const uint32_t u = next_stage(w);
            if (kind == K_T) {
              mbar_expect_tx(afull0 + 8 * u, A_STAGE);
              bulk_load(sbase + u * A_STAGE, p.scr + (PL_Q + 2 * j + rank) * PLANE + (3 * g + 1 - rho) * 1024, A_STAGE, afull0 + 8 * u);
            } else {
              fill_a(item, d, rho + (g == 0), u, true);
            }
          }
        }
      }
      for (int i = 0; i < 6; i++) next_stage(i >> 1);
    } else if (threadIdx.x == 64) {
      for (int it = 0; it < MAXITEMS; it++) {
        const uint32_t item = sched[it];
        const uint32_t kind = item & 7;
        const int g = (item >> 3) & 15, j = (item >> 7) & 15;
        mbar_wait(pub0 + 8 * (kind == K_END ? MAXITEMS - 1 : it), 0);
        if (kind == K_END) break;
        if (kind >= K_OA) continue;
        asm volatile("fence.acq_rel.gpu;" ::: "memory");
        if (kind == K_Q) red_add(p.flags + F_Q + (2 * j + rank) * 16 + g);
        if (kind == K_KV) red_add(p.flags + F_KV + j);
        if (kind == K_L) {
          red_add(p.flags + F_L + g);
          if (g == 0) red_add(p.flags + F_CAR + 2 * j + rank);
        }
        if (kind == K_T) {
          red_xor(p.flags + F_CTX + g * 32, 1u << (2 * j + rank));
          red_add(p.flags + F_TD + j);
        }
      }
      red_add(p.flags + F_EPOCH + blockIdx.x);
    } else if (threadIdx.x == 96) {
      for (int i = 0; i < 3; i++) prefetch_tmap(&p.mapA[i]);
      for (int i = 0; i < 6; i++) prefetch_tmap(&p.mapB[i]);
      prefetch_tmap(&p.mapO[0]);
      prefetch_tmap(&p.mapO[1]);
    }
  } else {
    asm volatile("setmaxnreg.inc.sync.aligned.u32 160;");
    const int cw = wg - 1;
    const int wq = __reduce_min_sync(0xffffffffu, (int)((threadIdx.x >> 5) & 3));
    auto turn = [&](uint32_t dep = 0) {
      bar_sync((1 + cw) | dep, NTURN);
    };
    auto pass = [&]() { bar_arrive(cw == 0 ? 3 : cw, NTURN); };
    auto rank_of = [&](uint32_t item) {
      const int r = cw + (item >> 11);
      return r >= 3 ? r - 3 : r;
    };
    if (cw == 1) pass();
    if (cw == 2) { turn(); pass(); }
    const uint32_t abase = sbase + cw * (2 * A_STAGE), afull = afull0 + 16 * cw, aempty = aempty0 + 16 * cw;
    const uint32_t adesc = ((abase & 0x3FFFF) >> 4) | (1u << 16), bdesc = (bbase & 0x3FFFF) >> 4;
    uint32_t pa = 0, pb = 0;
    int it = 0;
    uint32_t item = sched[0];
    auto publish = [&](int i, uint32_t skip = 0) {
      __syncwarp();
      mbar_arrive_if0(pub0 + 8 * i, (threadIdx.x & 31) | skip);
    };
    auto test_ab = [&](uint32_t a, uint32_t b) {
      test_a(afull + 8 * (a & 1), (a >> 1) & 1);
      test_b(bfull0 + 8 * (b & 3), (b >> 2) & 1);
    };
    auto wait_ab = [&]() {
      if (!ready_ab()) {
        mbar_wait_u(afull + 8 * (pa & 1), (pa >> 1) & 1);
        mbar_wait_u(bfull0 + 8 * (pb & 3), (pb >> 2) & 1);
      }
    };
    test_ab(0, 0);
    auto gturn = [&](auto second_c, bool hold, auto mma, auto meanwhile) {
      constexpr bool SECOND = decltype(second_c)::value != 0;
      const uint32_t da = adesc + (pa & 1) * (A_STAGE >> 4), db = bdesc + (pb & 3) * (B_SLOT >> 4);
      if (decltype(second_c)::value != 1) wait_ab();
      else if (!ready_b()) mbar_wait_u(bfull0 + 8 * (pb & 3), (pb >> 2) & 1);
      turn();
      wg_fence();
      mma(da, db);
      wg_commit();
      pass();
      if (SECOND) test_ab(pa + 1, pb + 1);
      else test_b(bfull0 + 8 * ((pb + 1) & 3), ((pb + 1) >> 2) & 1);
      meanwhile();
      wg_wait<0>();
      if (SECOND) {
        mbar_arrive_cta_if0(wq < 2 ? aempty + 8 * (pa & 1) : bempty0 + 8 * (pb & 3), wq < 2 ? wq : rank,
                            (threadIdx.x & 31) | (wq == 3) | (hold && wq < 2));
        pa++;
      } else {
        mbar_arrive_if0(bempty0 + 8 * (pb & 3), threadIdx.x & 127);
      }
      __syncwarp();
      pb++;
    };
    constexpr std::true_type YES{};
    constexpr std::false_type NO{};
    constexpr std::integral_constant<int, 2> ONCE{};
    auto nothing = []() {};
    auto idle = [&]() { return ((item >> 3) & 15) == 0 && rank_of(item) == 2; };
    auto skip_item = [&]() {
      const int n = (item & 7) == K_T ? 2 : item_nk(item);
      publish(it);
      for (int i = 2; i < n; i++) {
        turn();
        pass();
      }
      pb += n;
      test_ab(pa, pb);
      item = sched[++it];
    };

    if ((item & 7) == K_L && idle()) skip_item();
    while ((item & 7) == K_L) {
      const int g = (item >> 3) & 15, j = (item >> 7) & 15;
      const int rho = rank_of(item);
      float acc[96];
      auto mma = [&](int kb, bool first) {
        return [&acc, kb, first](uint32_t da, uint32_t db) {
#pragma unroll
          for (int k = 0; k < 4; k++) wgmma_n192_tb(acc, da + kb * 512 + k * 2, (db | (512u << 16)) + k * 128, !(first && k == 0));
        };
      };
      gturn(NO, false, mma(0, true), nothing);
#pragma unroll 1
      for (int d = 7; d > 0; d--) {
        gturn(YES, false, mma(1, false), nothing);
        gturn(NO, false, mma(0, false), nothing);
      }
      gturn(YES, true, mma(1, false), nothing);
      fence_regs(acc);
      const int lane = threadIdx.x & 31;
      uint32_t lo[24], hi[24], hk[8], hv[8];
#pragma unroll
      for (int i = 0; i < 24; i++) {
        lo[i] = pack_bf16(acc[4 * i], acc[4 * i + 1]);
        hi[i] = pack_bf16(acc[4 * i + 2], acc[4 * i + 3]);
      }
#pragma unroll
      for (int i = 16; i < 24; i++) {
        hi[i] = movm_t(hi[i]);
        lo[i] = movm_t(lo[i]);
      }
      const int row = item_row(K_L, g, rho + (g == 0));
      const int b = (row >> 6) & 15;
      const uint32_t xb = abase + ((pa - 1) & 1) * A_STAGE + lane * 16;
      const uint32_t cb = sbase + SM_CARRY + lane * 16;
      if (wq < 3) {
#pragma unroll
        for (int i = 0; i < 4; i++) sts128(xb + wq * 2048 + i * 512, hi[8 + 4 * i], hi[9 + 4 * i], hi[10 + 4 * i], hi[11 + 4 * i]);
      }
#pragma unroll
      for (int i = 0; i < 8; i++) hk[i] = hv[i] = 0;
      if (wq == 0 && b != 0) {
        if (row == 1024 + 64) {
          const uint32_t e = __ldcg(p.flags + F_EPOCH + blockIdx.x) + 1;
          wait_flag(p.flags + F_CAR + 2 * j + rank, e);
          __syncwarp();
          const uint4* c = p.carry + (2 * j + rank) * 128 + lane;
          const uint4 c0 = __ldcg(c), c1 = __ldcg(c + 32), c2 = __ldcg(c + 64), c3 = __ldcg(c + 96);
          hk[0] = c0.x; hk[1] = c0.y; hk[2] = c0.z; hk[3] = c0.w; hk[4] = c1.x; hk[5] = c1.y; hk[6] = c1.z; hk[7] = c1.w;
          hv[0] = c2.x; hv[1] = c2.y; hv[2] = c2.z; hv[3] = c2.w; hv[4] = c3.x; hv[5] = c3.y; hv[6] = c3.z; hv[7] = c3.w;
        } else {
          mbar_wait_u(carbar, (b - 1 - (row >> 10)) & 1);
          lds128(cb, hk[0], hk[1], hk[2], hk[3]);
          lds128(cb + 512, hk[4], hk[5], hk[6], hk[7]);
          lds128(cb + 1024, hv[0], hv[1], hv[2], hv[3]);
          lds128(cb + 1536, hv[4], hv[5], hv[6], hv[7]);
        }
      }
      bar_sync(4 + cw, 128);
      if (wq > 0) {
        const uint32_t a = xb + (wq - 1) * 2048;
        lds128(a, hk[0], hk[1], hk[2], hk[3]);
        lds128(a + 512, hk[4], hk[5], hk[6], hk[7]);
        lds128(a + 1024, hv[0], hv[1], hv[2], hv[3]);
        lds128(a + 1536, hv[4], hv[5], hv[6], hv[7]);
      }
      if (wq == 3) {
        if (row == 1024) {
          uint4* c = p.carry + (2 * j + rank) * 128 + lane;
#pragma unroll
          for (int i = 0; i < 4; i++) c[32 * i] = make_uint4(hi[8 + 4 * i], hi[9 + 4 * i], hi[10 + 4 * i], hi[11 + 4 * i]);
        } else {
#pragma unroll
          for (int i = 0; i < 4; i++) sts128(cb + i * 512, hi[8 + 4 * i], hi[9 + 4 * i], hi[10 + 4 * i], hi[11 + 4 * i]);
          __syncwarp();
          mbar_arrive_if0(carbar, lane);
        }
      }
      bar_sync(4 + cw, 128);
      mbar_arrive_cta_if0(aempty + 8 * ((pa - 1) & 1), wq & 1, lane | (wq >> 1));
      local_attn(lo, hi, hk, hv, p.scr + (PL_OA + j) * PLANE + (row + wq * 16) * 16 + rank * 64 + (lane ^ (lane >> 3)), b == 0 && wq == 0,
                 lane);
      publish(it);
      item = sched[++it];
    }

    float Y[64];
    float sc0, sc1;
    uint32_t done;
    uint4* pdst;
    auto stores = [&](uint4* dst, const uint32_t (&r)[32], uint32_t skip) {
#pragma unroll
      for (int i = 0; i < 8; i++) stg128_if0(dst + (i >> 1) * 32 + (i & 1) * 128, r[4 * i], r[4 * i + 1], r[4 * i + 2], r[4 * i + 3], skip);
    };
    auto pack = [&](uint32_t (&r)[32], const float (&acc)[64], float s0, float s1) {
#pragma unroll
      for (int i = 0; i < 16; i++) {
        r[8 * (i >> 2) + (i & 3)] = pack_bf16(acc[4 * i] * s0, acc[4 * i + 1] * s0);
        r[8 * (i >> 2) + (i & 3) + 4] = pack_bf16(acc[4 * i + 2] * s1, acc[4 * i + 3] * s1);
      }
    };
    auto flush_to = [&](uint32_t (&r)[32]) {
      pack(r, Y, sc0, sc1);
      stores(pdst, r, done);
      publish(it - 1, done);
    };
    auto flush = [&]() {
      uint32_t r[32];
      flush_to(r);
    };
    auto no_pending = [&]() {
      done = 1;
      pdst = p.scr;
      sc0 = sc1 = 0.f;
#pragma unroll
      for (int i = 0; i < 64; i++) Y[i] = 0.f;
    };
    no_pending();
    auto mma128 = [&](auto scr_c, float (&acc)[64], bool keep) {
      return [&acc, keep](uint32_t da, uint32_t db) {
        constexpr bool SCR = decltype(scr_c)::value;
#pragma unroll
        for (int k = 0; k < 8; k++)
          wgmma_n128<1>(acc, da + (k & 1) * 2 + ((k >> 1) & 1) * (SCR ? 32 : 4) + (k >> 2) * (SCR ? 64 : 512), SCR ? HI64 : HI128,
                        (db | (1024u << 16)) + k * 128, HI128, k != 0 || keep);
      };
    };
    auto all_but_last = [&](auto scr_c, float (&X)[64]) {
      int n = item_nk(item);
      gturn(NO, false, mma128(scr_c, X, false), flush);
      gturn(YES, false, mma128(scr_c, Y, false), nothing);
#pragma unroll 1
      while (true) {
        gturn(NO, false, mma128(scr_c, X, true), nothing);
        if ((n -= 2) == 2) break;
        gturn(YES, false, mma128(scr_c, Y, true), nothing);
      }
      fence_regs(X);
    };
    while ((item & 7) < K_OA) {
      if (idle()) {
        flush();
        done = 1;
        skip_item();
        continue;
      }
      const uint32_t kind = item & 7;
      const int g = (item >> 3) & 15, j = (item >> 7) & 15;
      const int rho = rank_of(item);
      if (kind != K_T) {
        float X[64];
        all_but_last(NO, X);
        const int lane = threadIdx.x & 31;
        const int row = item_row(K_Q, g, rho + (g == 0)) + wq * 16;
        sc0 = sc1 = kind == K_Q ? 0.08838834764831845f * 1.4426950408889634f : 1.f;
        pdst = p.scr + ((kind == K_Q ? PL_Q + j * 4 : PL_KV + (j % KVR) * 4) + rank * 2 + 1) * PLANE + row * 16 + (lane ^ (lane >> 3));
        uint32_t rx[32];
        pack(rx, X, sc0, sc1);
        stores(pdst - PLANE, rx, 0);
        item = sched[++it];
        gturn(YES, false, mma128(NO, Y, true), nothing);
        fence_regs(Y);
        test_ab(pa, pb);
        if (p.zero) stores(pdst - PLANE, rx, 0);
        done = 0;
      } else {
        float(&O)[64] = Y;
        float S[64];
        float l0 = 0.f, l1 = 0.f;
        const uint32_t sel = threadIdx.x & 127;
        const int b = 3 * g + 1 - rho;
        enum { FIRST, MID, LAST, HALF };
        auto round = [&](auto mode_c) {
          constexpr int MODE = decltype(mode_c)::value;
          constexpr int NI = MODE == HALF ? 8 : 16;
          const uint32_t shared = MODE == HALF ? rho == 0 : 0;
          const uint32_t tv = pb + 1 - shared;
          {
            const uint32_t dq = adesc + (pa & 1) * (A_STAGE >> 4);
            const uint32_t dk = (bdesc + (pb & 3) * 2048) | (1u << 16);
            wait_ab();
            turn();
            wg_fence();
#pragma unroll
            for (int k = 0; k < 8; k++) {
              if (MODE == HALF) wgmma_n64(S, dq + (k >> 1) * 32 + (k & 1) * 2, dk + (k >> 1) * 32 + (k & 1) * 2, k != 0);
              else wgmma_n128<0>(S, dq + (k >> 1) * 32 + (k & 1) * 2, HI64, dk + (k >> 1) * 32 + (k & 1) * 2, HI64, k != 0);
            }
            wg_commit();
            pass();
          }
          test_b(bfull0 + 8 * (tv & 3), (tv >> 2) & 1);
          if (!ready_b()) mbar_wait_u(bfull0 + 8 * (tv & 3), (tv >> 2) & 1);
          uint32_t r[32];
          if (MODE == FIRST) flush_to(r);
          wg_wait<0>();
#pragma unroll
          for (int i = 0; i < 4 * NI; i++) asm volatile("" : "+f"(S[i])::"memory");
          mbar_arrive_if0(bempty0 + 8 * (pb & 3), sel | shared);
          if (MODE >= LAST) mbar_arrive_cta_if0(aempty + 8 * (pa & 1), wq & 1, (sel & 31) | (wq >> 1));
          uint32_t P[2 * NI];
          if (MODE >= LAST) {
            const int lane = threadIdx.x & 31;
            const int row = wq * 16 + (lane >> 2) - 2 * (lane & 3);
#pragma unroll
            for (int i = 0; i < 8; i++) {
#pragma unroll
              for (int e = 0; e < 2; e++) {
                if (8 * i + e > row) S[4 * (NI - 8 + i) + e] = -INFINITY;
                if (8 * i + e > row + 8) S[4 * (NI - 8 + i) + 2 + e] = -INFINITY;
              }
            }
          }
          float s0 = 0.f, s1 = 0.f, t0 = 0.f, t1 = 0.f;
#pragma unroll
          for (int i = 0; i < NI; i++) {
            const float e0 = ex2(S[4 * i + 0]);
            const float e1 = ex2(S[4 * i + 1]);
            const float e2 = ex2(S[4 * i + 2]);
            const float e3 = ex2(S[4 * i + 3]);
            s0 += e0;
            t0 += e1;
            s1 += e2;
            t1 += e3;
            P[2 * i] = pack_bf16(e0, e1);
            P[2 * i + 1] = pack_bf16(e2, e3);
          }
          l0 += s0 + t0;
          l1 += s1 + t1;
          uint32_t dep = (__float_as_uint(l0) ^ __float_as_uint(l1)) ^ P[2 * NI - 1];
          if (MODE != FIRST) fence_regs(O);
#pragma unroll
          for (int i = 0; i < 2 * NI; i++) asm volatile("" : "+r"(P[i])::"memory");
          turn(dep & p.zero);
          wg_fence();
          const uint32_t dv = (bdesc + (tv & 3) * 2048 + shared * 1024) | (32u << 16);
#pragma unroll
          for (int k = 0; k < NI / 2; k++)
            wgmma_n128_rs_tb(O, P[4 * k], P[4 * k + 1], P[4 * k + 2], P[4 * k + 3], dv + k * 256, k != 0 || MODE != FIRST);
          wg_commit();
          pass();
          pb = tv + 1;
          if (MODE >= LAST) {
            const int nskip = 1 + (g & 1);
            if (rho + nskip >= 3) pb += 3 - nskip;
            pa++;
          } else {
            test_ab(pa, pb);
          }
          if (MODE >= LAST) {
            l0 += __shfl_xor_sync(0xffffffffu, l0, 1);
            l1 += __shfl_xor_sync(0xffffffffu, l1, 1);
            l0 += __shfl_xor_sync(0xffffffffu, l0, 2);
            l1 += __shfl_xor_sync(0xffffffffu, l1, 2);
            sc0 = rcp(l0);
            sc1 = rcp(l1);
          }
          wg_wait<0>();
          fence_regs(O);
          mbar_arrive_if0(bempty0 + 8 * (tv & 3), sel);
        };
        if (b < 2) {
          flush();
#pragma unroll
          for (int i = 0; i < 64; i++) O[i] = 0.f;
        } else {
          round(std::integral_constant<int, FIRST>{});
#pragma unroll 1
          for (int n = b >> 1; --n;) round(std::integral_constant<int, MID>{});
        }
        item = sched[++it];
        if (b & 1) round(std::integral_constant<int, LAST>{});
        else round(std::integral_constant<int, HALF>{});
        test_ab(pa, pb);
        float z[4] = {0.f, 0.f, 0.f, 0.f};
#pragma unroll
        for (int i = 0; i < 32; i++) z[i & 3] = fmaf(O[2 * i], O[2 * i + 1], z[i & 3]);
        const bool bad = !(l0 <= KB_LIMIT && l0 >= KB_LOW) || !(l1 <= KB_LIMIT && l1 >= KB_LOW) ||
                         !(fabsf(z[0]) + fabsf(z[1]) + fabsf(z[2]) + fabsf(z[3]) <= 3e38f);
        const int lane = threadIdx.x & 31;
        pdst = p.scr + (PL_Q + 2 * j + rank) * PLANE + (b * 64 + wq * 16) * 16 + (lane ^ (lane >> 3));
        done = 0;
        if (__any_sync(0xffffffffu, bad)) {
          attn_fallback(p.scr + (PL_Q + 2 * j + rank) * PLANE, p.scr + (PL_KV + (j % KVR) * 4 + rank) * PLANE, b * 64 + wq * 16,
                        threadIdx.x & 31);
          publish(it - 1);
          no_pending();
          test_ab(pa, pb);
        }
      }
    }

    if ((item & 7) == K_END) {
      flush();
    } else if (idle()) {
      flush();
      skip_item();
    } else {
      const uint32_t kind = item & 7;
      const int g = (item >> 3) & 15, j = (item >> 7) & 15;
      const int row = item_row(kind, g, rank_of(item) + (g == 0)) + wq * 16;
      auto epilogue = [&](float (&acc)[64], int cb) {
        const int lane = threadIdx.x & 31;
        const uint32_t stg = abase + ((pa - 1) & 1) * A_STAGE + wq * 4096;
        const int srow = lane & 15;
#pragma unroll
        for (int jj = 0; jj < 8; jj++) {
          const uint32_t r0 = pack_bf16(acc[8 * jj + 0], acc[8 * jj + 1]);
          const uint32_t r1 = pack_bf16(acc[8 * jj + 2], acc[8 * jj + 3]);
          const uint32_t r2 = pack_bf16(acc[8 * jj + 4], acc[8 * jj + 5]);
          const uint32_t r3 = pack_bf16(acc[8 * jj + 6], acc[8 * jj + 7]);
          const int chunk = (2 * jj + (lane >> 4)) & 7;
          const uint32_t addr = stg + (jj >> 2) * 2048 + srow * 128 + ((chunk ^ (srow & 7)) << 4);
          asm volatile("stmatrix.sync.aligned.m8n8.x4.shared.b16 [%0], {%1,%2,%3,%4};" ::"r"(addr), "r"(r0), "r"(r1), "r"(r2), "r"(r3)
                       : "memory");
        }
        asm volatile("fence.proxy.async.shared::cta;" ::: "memory");
        __syncwarp();
        if (lane == 0) {
          const int col = cb * 128 + (kind == K_OA ? (row >> 10) * 2048 : 1024);
          const int r = kind == K_OA ? row & 1023 : row;
          tma_store_2d(&p.mapO[kind - K_OA], stg, col, r);
          tma_store_2d(&p.mapO[kind - K_OA], stg + 2048, col + 64, r);
          asm volatile("cp.async.bulk.commit_group;" ::: "memory");
        }
      };
      float X[64];
      if (item_narrow(item)) {
        int n = item_nk(item);
        gturn(ONCE, false, mma128(YES, X, false), flush);
#pragma unroll 1
        while (--n) gturn(ONCE, false, mma128(YES, X, true), nothing);
        fence_regs(X);
        epilogue(X, 2 * j + rank - 8);
      } else {
        all_but_last(YES, X);
        epilogue(X, 4 * j + 2 * rank);
        gturn(YES, false, mma128(YES, Y, true), nothing);
        fence_regs(Y);
        epilogue(Y, 4 * j + 2 * rank + 1);
      }
      publish(it);
      item = sched[++it];
    }
    const int rho = rank_of(item);
    if (rho == 0) {
      turn();
      pass();
    }
    if (rho == 1) turn();
    publish(MAXITEMS - 1);
    asm volatile("cp.async.bulk.wait_group.read 0;" ::: "memory");
  }
}

typedef CUresult (*EncodeFn)(CUtensorMap*, CUtensorMapDataType, cuuint32_t, void*, const cuuint64_t*, const cuuint64_t*,
                             const cuuint32_t*, const cuuint32_t*, CUtensorMapInterleave, CUtensorMapSwizzle, CUtensorMapL2promotion,
                             CUtensorMapFloatOOBfill);

void make_map(EncodeFn enc, CUtensorMap* m, const void* ptr, uint64_t d0, uint64_t d1, uint64_t d2, uint64_t s1, uint64_t s2, uint32_t b0,
              uint32_t b1, uint32_t b2) {
  cuuint64_t gd[3] = {d0, d1, d2}, gs[2] = {s1, s2};
  cuuint32_t bd[3] = {b0, b1, b2}, es[3] = {1, 1, 1};
  enc(m, CU_TENSOR_MAP_DATA_TYPE_BFLOAT16, d2 ? 3 : 2, const_cast<void*>(ptr), gd, gs, bd, es, CU_TENSOR_MAP_INTERLEAVE_NONE,
      CU_TENSOR_MAP_SWIZZLE_128B, CU_TENSOR_MAP_L2_PROMOTION_L2_128B, CU_TENSOR_MAP_FLOAT_OOB_FILL_NONE);
}

struct HostState {
  Params p;
  const void* in[9];
  void* out;
  bool valid;
};
HostState g_hs;

const uint16_t h_sched[NCLUSTERS * MAXITEMS] = {
    336, 273, 257, 51, 299, 1491, 589, 7, 7, 7, 7, 7, 7, 7, 7, 7,
    64, 936, 593, 443, 147, 923, 1179, 779, 829, 7, 7, 7, 7, 7, 7, 7,
    400, 512, 513, 649, 323, 1689, 1539, 1435, 1987, 36, 7, 7, 7, 7, 7, 7,
    928, 201, 393, 561, 187, 1969, 1873, 1195, 643, 973, 7, 7, 7, 7, 7, 7,
    904, 664, 1065, 1329, 793, 1617, 571, 1947, 917, 7, 7, 7, 7, 7, 7, 7,
    560, 16, 657, 801, 291, 579, 1859, 148, 7, 7, 7, 7, 7, 7, 7, 7,
    208, 337, 137, 1305, 1193, 945, 1569, 1219, 1427, 933, 7, 7, 7, 7, 7, 7,
    816, 81, 1041, 1073, 1081, 785, 539, 1817, 1211, 717, 7, 7, 7, 7, 7, 7,
    688, 313, 145, 75, 1323, 1171, 1555, 1843, 196, 7, 7, 7, 7, 7, 7, 7,
    648, 720, 529, 777, 139, 953, 1043, 1483, 701, 7, 7, 7, 7, 7, 7, 7,
    432, 73, 264, 171, 531, 2001, 939, 1795, 1675, 549, 7, 7, 7, 7, 7, 7,
    320, 49, 153, 721, 1177, 211, 931, 1971, 84, 7, 7, 7, 7, 7, 7, 7,
    536, 840, 681, 817, 1169, 1083, 1163, 1187, 965, 7, 7, 7, 7, 7, 7, 7,
    592, 9, 792, 1049, 1153, 267, 1561, 1961, 827, 853, 7, 7, 7, 7, 7, 7,
    848, 672, 1441, 467, 667, 1747, 204, 7, 7, 7, 7, 7, 7, 7, 7, 7,
    48, 200, 1417, 403, 387, 1457, 1609, 1945, 1419, 1611, 645, 7, 7, 7, 7, 7,
    80, 409, 433, 1473, 689, 905, 595, 1803, 907, 909, 7, 7, 7, 7, 7, 7,
    24, 57, 8, 315, 1713, 803, 1995, 172, 7, 7, 7, 7, 7, 7, 7, 7,
    568, 185, 161, 665, 331, 1705, 1619, 901, 7, 7, 7, 7, 7, 7, 7, 7,
    456, 425, 457, 585, 1233, 1217, 411, 1745, 1467, 845, 7, 7, 7, 7, 7, 7,
    296, 384, 0, 569, 1489, 1091, 811, 1707, 188, 7, 7, 7, 7, 7, 7, 7,
    56, 65, 281, 1289, 1337, 809, 1577, 1921, 659, 1587, 653, 7, 7, 7, 7, 7,
    920, 305, 1105, 1449, 825, 768, 1537, 395, 707, 1155, 981, 7, 7, 7, 7, 7,
    176, 416, 1425, 1345, 307, 1865, 1793, 2003, 68, 7, 7, 7, 7, 7, 7, 7,
    912, 544, 312, 841, 419, 843, 661, 7, 7, 7, 7, 7, 7, 7, 7, 7,
    656, 1, 329, 59, 179, 1833, 1315, 1827, 517, 7, 7, 7, 7, 7, 7, 7,
    408, 25, 465, 67, 651, 1697, 1075, 1723, 60, 7, 7, 7, 7, 7, 7, 7,
    976, 449, 1097, 521, 833, 929, 1067, 1841, 1451, 533, 7, 7, 7, 7, 7, 7,
    464, 520, 1361, 259, 1161, 969, 587, 795, 597, 7, 7, 7, 7, 7, 7, 7,
    392, 160, 1465, 19, 195, 1595, 1963, 76, 7, 7, 7, 7, 7, 7, 7, 7,
    440, 168, 784, 427, 1977, 963, 565, 7, 7, 7, 7, 7, 7, 7, 7, 7,
    328, 193, 129, 577, 713, 1297, 11, 1729, 555, 1443, 797, 7, 7, 7, 7, 7,
    272, 584, 1025, 339, 1849, 1579, 1715, 12, 7, 7, 7, 7, 7, 7, 7, 7,
    800, 952, 1313, 849, 1201, 1601, 547, 1331, 925, 7, 7, 7, 7, 7, 7, 7,
    448, 256, 1057, 705, 1225, 913, 563, 1307, 1291, 1411, 573, 7, 7, 7, 7, 7,
    960, 265, 177, 673, 27, 977, 1107, 1979, 44, 7, 7, 7, 7, 7, 7, 7,
    832, 33, 401, 1353, 283, 937, 3, 1937, 971, 821, 7, 7, 7, 7, 7, 7,
    130, 138, 146, 154, 162, 170, 1035, 683, 725, 7, 7, 7, 7, 7, 7, 7,
    144, 417, 385, 83, 1283, 1929, 1339, 1691, 1939, 20, 7, 7, 7, 7, 7, 7,
    72, 424, 1089, 451, 1363, 789, 7, 7, 7, 7, 7, 7, 7, 7, 7, 7,
    258, 266, 274, 282, 290, 298, 1299, 1699, 805, 7, 7, 7, 7, 7, 7, 7,
    808, 41, 280, 641, 43, 1099, 1851, 156, 7, 7, 7, 7, 7, 7, 7, 7,
    184, 128, 545, 1281, 459, 1355, 669, 7, 7, 7, 7, 7, 7, 7, 7, 7,
    642, 650, 658, 666, 674, 682, 691, 1923, 957, 7, 7, 7, 7, 7, 7, 7,
    32, 152, 697, 203, 1227, 1835, 180, 7, 7, 7, 7, 7, 7, 7, 7, 7,
    576, 321, 304, 163, 1409, 1585, 1737, 1203, 1667, 813, 7, 7, 7, 7, 7, 7,
    770, 778, 786, 794, 802, 810, 1059, 915, 525, 7, 7, 7, 7, 7, 7, 7,
    680, 289, 1033, 1433, 537, 1209, 155, 944, 1739, 28, 7, 7, 7, 7, 7, 7,
    712, 696, 776, 435, 1801, 699, 677, 7, 7, 7, 7, 7, 7, 7, 7, 7,
    178, 186, 194, 202, 210, 979, 949, 7, 7, 7, 7, 7, 7, 7, 7, 7,
    2, 10, 18, 26, 34, 42, 675, 1867, 132, 7, 7, 7, 7, 7, 7, 7,
    40, 209, 297, 553, 1481, 961, 1545, 1673, 1475, 541, 7, 7, 7, 7, 7, 7,
    306, 314, 322, 330, 338, 851, 685, 7, 7, 7, 7, 7, 7, 7, 7, 7,
    386, 394, 402, 410, 418, 426, 899, 819, 1955, 52, 7, 7, 7, 7, 7, 7,
    136, 441, 640, 528, 896, 1985, 1857, 1459, 837, 7, 7, 7, 7, 7, 7, 7,
    434, 442, 450, 458, 466, 723, 557, 7, 7, 7, 7, 7, 7, 7, 7, 7,
    514, 522, 530, 538, 546, 554, 1563, 1875, 4, 7, 7, 7, 7, 7, 7, 7,
    824, 704, 35, 131, 1185, 1593, 1953, 835, 581, 7, 7, 7, 7, 7, 7, 7,
    562, 570, 578, 586, 594, 1665, 1347, 941, 7, 7, 7, 7, 7, 7, 7, 7,
    898, 906, 914, 922, 930, 938, 771, 1571, 1931, 1811, 1683, 164, 7, 7, 7, 7,
    552, 288, 968, 769, 897, 515, 1721, 715, 781, 7, 7, 7, 7, 7, 7, 7,
    818, 826, 834, 842, 850, 1235, 709, 7, 7, 7, 7, 7, 7, 7, 7, 7,
    50, 58, 66, 74, 82, 1681, 955, 1547, 1819, 140, 7, 7, 7, 7, 7, 7,
    192, 17, 169, 1321, 275, 921, 1553, 523, 1825, 947, 693, 7, 7, 7, 7, 7,
    946, 954, 962, 970, 978, 1993, 787, 1603, 773, 7, 7, 7, 7, 7, 7, 7,
    690, 698, 706, 714, 722, 1027, 1809, 1051, 1731, 212, 7, 7, 7, 7, 7, 7,
};

void setup(void* const* d_in, void* d_out) {
  void* fn = nullptr;
  cudaDriverEntryPointQueryResult qr;
  cudaGetDriverEntryPoint("cuTensorMapEncodeTiled", &fn, cudaEnableDefault, &qr);
  EncodeFn enc = (EncodeFn)fn;
  void *scr, *carry, *flags;
  cudaGetSymbolAddress(&scr, g_scr);
  cudaGetSymbolAddress(&carry, g_carry);
  cudaGetSymbolAddress(&flags, g_flags);
  Params& p = g_hs.p;
  make_map(enc, &p.mapA[0], d_in[3], 64, 2048, 16, 2048, 128, 64, 64, 1);
  make_map(enc, &p.mapA[1], d_in[4], 64, 2048, 8, 1024, 128, 64, 64, 1);
  make_map(enc, &p.mapA[2], d_in[0], 64, 1024, 32, 4096, 128, 64, 64, 1);
  make_map(enc, &p.mapB[0], d_in[5], 64, 1024, 64, 8192, 128, 64, 128, 2);
  make_map(enc, &p.mapB[1], d_in[6], 64, 512, 64, 8192, 128, 64, 128, 2);
  make_map(enc, &p.mapB[2], d_in[1], 1024, 1024, 3, 6144, 2048, 64, 64, 3);
  make_map(enc, &p.mapB[3], d_in[7], 64, 512, 64, 8192, 128, 64, 128, 2);
  make_map(enc, &p.mapB[5], d_in[8], 64, 4096, 16, 2048, 128, 64, 128, 2);
  {
    cuuint64_t gd[5] = {1024, 2, 4, 4, 32}, gs[4] = {2048, 8 * 2048, 2 * 2048, 32 * 2048};
    cuuint32_t bd[5] = {64, 2, 4, 4, 4}, es[5] = {1, 1, 1, 1, 1};
    enc(&p.mapB[4], CU_TENSOR_MAP_DATA_TYPE_BFLOAT16, 5, d_in[2], gd, gs, bd, es, CU_TENSOR_MAP_INTERLEAVE_NONE, CU_TENSOR_MAP_SWIZZLE_128B,
        CU_TENSOR_MAP_L2_PROMOTION_L2_128B, CU_TENSOR_MAP_FLOAT_OOB_FILL_NONE);
  }
  make_map(enc, &p.mapO[0], d_out, 4096, 1024, 0, 8192, 0, 64, 16, 1);
  make_map(enc, &p.mapO[1], d_out, 2048, 2048, 0, 4096, 0, 64, 16, 1);
  p.scr = (uint4*)scr;
  p.carry = (uint4*)carry;
  p.flags = (uint32_t*)flags;
  p.zero = 0;
  for (int c = 0; c < NCLUSTERS; c++) {
    int rot = 0;
    for (int i = c * MAXITEMS; i < (c + 1) * MAXITEMS; i++) {
      const int kind = h_sched[i] & 7, g = (h_sched[i] >> 3) & 15;
      p.sched[i] = (uint16_t)(h_sched[i] | rot << 11);
      rot = (rot + (kind == K_T ? 1 + (g & 1) : g == 0)) % 3;
    }
  }
  cudaFuncSetAttribute(fused_kernel, cudaFuncAttributeMaxDynamicSharedMemorySize, SM_TOTAL);
  for (int i = 0; i < 9; i++) g_hs.in[i] = d_in[i];
  g_hs.out = d_out;
  g_hs.valid = true;
}

}

extern "C" void kernel_launch(void* const* d_in, const int* in_sizes, int n_in, void* d_out, int out_size) {
  (void)in_sizes;
  (void)n_in;
  (void)out_size;
  bool ok = g_hs.valid && g_hs.out == d_out;
  for (int i = 0; ok && i < 9; i++) ok = g_hs.in[i] == d_in[i];
  if (!ok) setup(d_in, d_out);
  fused_kernel<<<NCLUSTERS * 2, 512, SM_TOTAL, cudaStreamPerThread>>>(g_hs.p);
}
```

```cpp
#include <cuda_runtime.h>
#include <cuda_bf16.h>
#include <cuda.h>
#include <stdint.h>
#include <type_traits>

namespace {

typedef __nv_bfloat16 bf16;

__device__ __forceinline__ uint32_t smem_u32(const void* p) { return (uint32_t)__cvta_generic_to_shared(p); }
__device__ __forceinline__ void mbar_init(uint32_t bar, uint32_t cnt) {
  asm volatile("mbarrier.init.shared::cta.b64 [%0], %1;" ::"r"(bar), "r"(cnt) : "memory");
}
__device__ __forceinline__ void mbar_expect_tx(uint32_t bar, uint32_t bytes) {
  asm volatile("mbarrier.arrive.expect_tx.shared::cta.b64 _, [%0], %1;" ::"r"(bar), "r"(bytes) : "memory");
}
__device__ __forceinline__ void mbar_arrive_n(uint32_t bar, uint32_t n) {
  asm volatile("mbarrier.arrive.shared::cta.b64 _, [%0], %1;" ::"r"(bar), "r"(n) : "memory");
}
__device__ __forceinline__ void mbar_arrive_if0(uint32_t bar, uint32_t sel) {
  asm volatile("{\n.reg .pred p;\nsetp.eq.u32 p, %1, 0;\n@p mbarrier.arrive.shared::cta.b64 _, [%0];\n}" ::"r"(bar), "r"(sel) : "memory");
}
__device__ __forceinline__ void mbar_arrive_cta_if0(uint32_t bar, uint32_t cta, uint32_t sel) {
  asm volatile("{\n.reg .pred p;\n.reg .b32 ra;\nsetp.eq.u32 p, %2, 0;\nmapa.shared::cluster.u32 ra, %0, %1;\n"
               "@p mbarrier.arrive.shared::cluster.b64 _, [ra];\n}" ::"r"(bar),
               "r"(cta), "r"(sel)
               : "memory");
}
__device__ __forceinline__ void mbar_wait(uint32_t bar, uint32_t parity) {
  uint32_t done;
  uint32_t it = 0;
#pragma unroll 1
  while (true) {
    asm volatile("{\n.reg .pred p;\nmbarrier.try_wait.parity.shared::cta.b64 p, [%1], %2, 1000;\nselp.u32 %0, 1, 0, p;\n}"
                 : "=r"(done)
                 : "r"(bar), "r"(parity)
                 : "memory");
    if (done) break;
    if (++it > (1u << 20)) __trap();
  }
}
__device__ __forceinline__ void mbar_wait_u(uint32_t bar, uint32_t parity) {
  uint32_t it = 0;
#pragma unroll 1
  while (true) {
    uint32_t done;
    asm volatile("{\n.reg .pred p, q;\nmbarrier.try_wait.parity.shared::cta.b64 p, [%1], %2;\nvote.sync.all.pred q, p, 0xffffffff;\nselp.u32 %0, 1, 0, q;\n}"
                 : "=r"(done)
                 : "r"(bar), "r"(parity)
                 : "memory");
    if (done) break;
    if (++it > (1u << 20)) break;
  }
}
#define DECLARE_READY() asm volatile(".reg .pred RDYA, RDYB;")
__device__ __forceinline__ void test_a(uint32_t bar, uint32_t parity) {
  asm volatile("mbarrier.test_wait.parity.shared::cta.b64 RDYA, [%0], %1;" ::"r"(bar), "r"(parity) : "memory");
}
__device__ __forceinline__ void test_b(uint32_t bar, uint32_t parity) {
  asm volatile("mbarrier.test_wait.parity.shared::cta.b64 RDYB, [%0], %1;" ::"r"(bar), "r"(parity) : "memory");
}
__device__ __forceinline__ uint32_t ready_b(uint32_t dep = 0) {
  uint32_t r;
  asm volatile("{\n.reg .pred q;\nsetp.eq.and.u32 q, %1, 0, RDYB;\nvote.sync.all.pred q, q, 0xffffffff;\nselp.u32 %0, 1, 0, q;\n}" : "=r"(r) : "r"(dep) : "memory");
  return r;
}
__device__ __forceinline__ uint32_t ready_ab() {
  uint32_t r;
  asm volatile("{\n.reg .pred q;\nand.pred q, RDYA, RDYB;\nvote.sync.all.pred q, q, 0xffffffff;\nselp.u32 %0, 1, 0, q;\n}" : "=r"(r)::"memory");
  return r;
}
__device__ __forceinline__ void tma_load_3d(uint32_t dst, const CUtensorMap* m, uint32_t bar, int c0, int c1, int c2) {
  asm volatile("cp.async.bulk.tensor.3d.shared::cluster.global.mbarrier::complete_tx::bytes [%0], [%1, {%3, %4, %5}], [%2];" ::"r"(dst),
               "l"(m), "r"(bar), "r"(c0), "r"(c1), "r"(c2)
               : "memory");
}
__device__ __forceinline__ void tma_load_3d_mc(uint32_t dst, const CUtensorMap* m, uint32_t bar, int c0, int c1, int c2, uint16_t mask) {
  asm volatile(
      "cp.async.bulk.tensor.3d.shared::cluster.global.mbarrier::complete_tx::bytes.multicast::cluster [%0], [%1, {%3, %4, %5}], [%2], %6;" ::"r"(dst),
      "l"(m), "r"(bar), "r"(c0), "r"(c1), "r"(c2), "h"(mask)
      : "memory");
}
__device__ __forceinline__ void tma_load_5d(uint32_t dst, const CUtensorMap* m, uint32_t bar, int c0, int c4) {
  asm volatile("cp.async.bulk.tensor.5d.shared::cluster.global.mbarrier::complete_tx::bytes [%0], [%1, {%3, 0, 0, 0, %4}], [%2];" ::"r"(dst),
               "l"(m), "r"(bar), "r"(c0), "r"(c4)
               : "memory");
}
__device__ __forceinline__ void bulk_load(uint32_t dst, const void* src, uint32_t bytes, uint32_t bar) {
  asm volatile("cp.async.bulk.shared::cluster.global.mbarrier::complete_tx::bytes [%0], [%1], %2, [%3];" ::"r"(dst), "l"(src), "r"(bytes), "r"(bar)
               : "memory");
}
__device__ __forceinline__ void bulk_load_mc(uint32_t dst, const void* src, uint32_t bytes, uint32_t bar, uint16_t mask) {
  asm volatile("cp.async.bulk.shared::cluster.global.mbarrier::complete_tx::bytes.multicast::cluster [%0], [%1], %2, [%3], %4;" ::"r"(dst),
               "l"(src), "r"(bytes), "r"(bar), "h"(mask)
               : "memory");
}
__device__ __forceinline__ void prefetch_l2(const void* src, uint32_t bytes) {
  asm volatile("cp.async.bulk.prefetch.L2.global [%0], %1;" ::"l"(src), "r"(bytes) : "memory");
}
__device__ __forceinline__ void tma_store_2d(const CUtensorMap* m, uint32_t src, int c0, int c1) {
  asm volatile("cp.async.bulk.tensor.2d.global.shared::cta.bulk_group [%0, {%2, %3}], [%1];" ::"l"(m), "r"(src), "r"(c0), "r"(c1)
               : "memory");
}
__device__ __forceinline__ void prefetch_tmap(const CUtensorMap* m) { asm volatile("prefetch.tensormap [%0];" ::"l"(m) : "memory"); }
__device__ __forceinline__ void cluster_sync_relaxed() {
  asm volatile("barrier.cluster.arrive.relaxed.aligned;\nbarrier.cluster.wait.aligned;" ::: "memory");
}
__device__ __forceinline__ uint32_t pack_bf16(float lo, float hi) {
  uint32_t r;
  asm("cvt.rn.bf16x2.f32 %0, %1, %2;" : "=r"(r) : "f"(hi), "f"(lo));
  return r;
}
__device__ __forceinline__ float ex2(float x) {
  float y;
  asm("ex2.approx.ftz.f32 %0, %1;" : "=f"(y) : "f"(x));
  return y;
}
__device__ __forceinline__ float rcp(float x) {
  float y;
  asm("rcp.approx.ftz.f32 %0, %1;" : "=f"(y) : "f"(x));
  return y;
}
__device__ __forceinline__ uint32_t fma_bf16x2(uint32_t a, uint32_t b, uint32_t c) {
  uint32_t d;
  asm("fma.rn.bf16x2 %0, %1, %2, %3;" : "=r"(d) : "r"(a), "r"(b), "r"(c));
  return d;
}
__device__ __forceinline__ void wg_fence() { asm volatile("wgmma.fence.sync.aligned;" ::: "memory"); }
__device__ __forceinline__ void wg_commit() { asm volatile("wgmma.commit_group.sync.aligned;" ::: "memory"); }
template <int N>
__device__ __forceinline__ void wg_wait() {
  asm volatile("wgmma.wait_group.sync.aligned %0;" ::"n"(N) : "memory");
}
template <int N>
__device__ __forceinline__ void fence_regs(float (&d)[N]) {
#pragma unroll
  for (int i = 0; i < N; i++) asm volatile("" : "+f"(d[i])::"memory");
}
__device__ __forceinline__ void bar_sync(int id, int n) { asm volatile("bar.sync %0, %1;" ::"r"(id), "r"(n) : "memory"); }
__device__ __forceinline__ void bar_arrive(int id, int n) { asm volatile("bar.arrive %0, %1;" ::"r"(id), "r"(n) : "memory"); }

#define R8(a, i) "+f"(a[i]), "+f"(a[i + 1]), "+f"(a[i + 2]), "+f"(a[i + 3]), "+f"(a[i + 4]), "+f"(a[i + 5]), "+f"(a[i + 6]), "+f"(a[i + 7])
#define OP32(d, o) R8(d, o), R8(d, o + 8), R8(d, o + 16), R8(d, o + 24)
#define L32A "%0,%1,%2,%3,%4,%5,%6,%7,%8,%9,%10,%11,%12,%13,%14,%15,%16,%17,%18,%19,%20,%21,%22,%23,%24,%25,%26,%27,%28,%29,%30,%31"
#define L32B "%32,%33,%34,%35,%36,%37,%38,%39,%40,%41,%42,%43,%44,%45,%46,%47,%48,%49,%50,%51,%52,%53,%54,%55,%56,%57,%58,%59,%60,%61,%62,%63"
#define L32C "%64,%65,%66,%67,%68,%69,%70,%71,%72,%73,%74,%75,%76,%77,%78,%79,%80,%81,%82,%83,%84,%85,%86,%87,%88,%89,%90,%91,%92,%93,%94,%95"
#define L32D "%96,%97,%98,%99,%100,%101,%102,%103,%104,%105,%106,%107,%108,%109,%110,%111,%112,%113,%114,%115,%116,%117,%118,%119,%120,%121,%122,%123,%124,%125,%126,%127"
#define WG_PRE(a, b, s, ha, hb) "{\n.reg .pred p;\n.reg .b64 da, db;\nmov.b64 da, {" a ", " ha "};\nmov.b64 db, {" b ", " hb "};\nsetp.ne.b32 p, " s ", 0;\n"

constexpr uint32_t HI128 = 0x40000040;
constexpr uint32_t HI64 = 0x80000080;
template <int TB>
__device__ __forceinline__ void wgmma_n128(float (&d)[64], uint32_t da, uint32_t ha, uint32_t db, uint32_t hb, int scale_d) {
  asm volatile(WG_PRE("%64", "%65", "%66", "%67", "%68") "wgmma.mma_async.sync.aligned.m64n128k16.f32.bf16.bf16 {" L32A "," L32B "}, da, db, p, 1, 1, 0, %69;\n}\n"
               : OP32(d, 0), OP32(d, 32)
               : "r"(da), "r"(db), "r"(scale_d), "r"(ha), "r"(hb), "n"(TB));
}
__device__ __forceinline__ void wgmma_n192_tb(float (&d)[96], uint32_t da, uint32_t db, int scale_d) {
  asm volatile(WG_PRE("%96", "%97", "%98", "%99", "%99") "wgmma.mma_async.sync.aligned.m64n192k16.f32.bf16.bf16 {" L32A "," L32B "," L32C "}, da, db, p, 1, 1, 0, 1;\n}\n"
               : OP32(d, 0), OP32(d, 32), OP32(d, 64)
               : "r"(da), "r"(db), "r"(scale_d), "r"(HI128));
}
__device__ __forceinline__ void wgmma_n64(float (&d)[64], uint32_t da, uint32_t db, int scale_d) {
  asm volatile(WG_PRE("%32", "%33", "%34", "%35", "%35") "wgmma.mma_async.sync.aligned.m64n64k16.f32.bf16.bf16 {" L32A "}, da, db, p, 1, 1, 0, 0;\n}\n"
               : OP32(d, 0)
               : "r"(da), "r"(db), "r"(scale_d), "r"(HI64));
}
__device__ __forceinline__ void wgmma_n128_rs_tb(float (&d)[64], uint32_t a0, uint32_t a1, uint32_t a2, uint32_t a3, uint32_t db, int scale_d) {
  asm volatile("{\n.reg .pred p;\n.reg .b64 db;\nmov.b64 db, {%68, %70};\nsetp.ne.b32 p, %69, 0;\n"
               "wgmma.mma_async.sync.aligned.m64n128k16.f32.bf16.bf16 {" L32A "," L32B "}, {%64,%65,%66,%67}, db, p, 1, 1, 1;\n}\n"
               : OP32(d, 0), OP32(d, 32)
               : "r"(a0), "r"(a1), "r"(a2), "r"(a3), "r"(db), "r"(scale_d), "r"(HI64));
}
__device__ __forceinline__ void mma_16816(float (&c)[4], uint32_t a0, uint32_t a1, uint32_t a2, uint32_t a3, uint32_t b0, uint32_t b1) {
  asm volatile("mma.sync.aligned.m16n8k16.row.col.f32.bf16.bf16.f32 {%0,%1,%2,%3}, {%4,%5,%6,%7}, {%8,%9}, {%0,%1,%2,%3};"
               : "+f"(c[0]), "+f"(c[1]), "+f"(c[2]), "+f"(c[3])
               : "r"(a0), "r"(a1), "r"(a2), "r"(a3), "r"(b0), "r"(b1));
}
__device__ __forceinline__ void mma_1688(float (&c)[4], uint32_t a0, uint32_t a1, uint32_t b0) {
  asm volatile("mma.sync.aligned.m16n8k8.row.col.f32.bf16.bf16.f32 {%0,%1,%2,%3}, {%4,%5}, {%6}, {%0,%1,%2,%3};"
               : "+f"(c[0]), "+f"(c[1]), "+f"(c[2]), "+f"(c[3])
               : "r"(a0), "r"(a1), "r"(b0));
}
__device__ __forceinline__ void quad_sum(float& l0, float& l1) {
  const uint32_t h0 = __float_as_uint(l0) & 0xFFFFE000u, h1 = __float_as_uint(l1) & 0xFFFFE000u;
  const float r0 = l0 - __uint_as_float(h0), r1 = l1 - __uint_as_float(h1);
  asm volatile("{\n.reg .f32 c1, c3;\nmma.sync.aligned.m16n8k8.row.col.f32.tf32.tf32.f32 {%0,c1,%1,c3}, {%2,%3,%4,%5}, {%6,%6}, {%7,%7,%7,%7};\n}"
               : "=f"(l0), "=f"(l1)
               : "r"(h0), "r"(h1), "r"(__float_as_uint(r0)), "r"(__float_as_uint(r1)), "r"(0x3F800000), "f"(0.f));
}
__device__ __forceinline__ uint32_t movm_t(uint32_t x) {
  uint32_t y;
  asm volatile("movmatrix.sync.aligned.m8n8.trans.b16 %0, %1;" : "=r"(y) : "r"(x));
  return y;
}
__device__ __forceinline__ void sts128(uint32_t a, uint32_t x, uint32_t y, uint32_t z, uint32_t w) {
  asm volatile("st.shared.v4.u32 [%0], {%1,%2,%3,%4};" ::"r"(a), "r"(x), "r"(y), "r"(z), "r"(w) : "memory");
}
__device__ __forceinline__ void stg128_if0(uint4* a, uint32_t x, uint32_t y, uint32_t z, uint32_t w, uint32_t sel) {
  asm volatile("{\n.reg .pred p;\nsetp.eq.u32 p, %5, 0;\n@p st.global.v4.u32 [%0], {%1,%2,%3,%4};\n}" ::"l"(a), "r"(x), "r"(y), "r"(z), "r"(w),
               "r"(sel)
               : "memory");
}
__device__ __forceinline__ void lds128(uint32_t a, uint32_t& x, uint32_t& y, uint32_t& z, uint32_t& w) {
  asm volatile("ld.shared.v4.u32 {%0,%1,%2,%3}, [%4];" : "=r"(x), "=r"(y), "=r"(z), "=r"(w) : "r"(a) : "memory");
}

#define KVR 16
constexpr int PLANE = 2048 * 16;
constexpr int PL_Q = 0, PL_KV = 32, PL_OA = PL_KV + 4 * KVR, NPLANES = PL_OA + 8;
__device__ __align__(1024) uint4 g_scr[NPLANES * PLANE];
__device__ uint4 g_carry[16 * 128];
constexpr int F_Q = 0, F_CTX = 256, F_KV = 768, F_TD = 1280, F_L = 1296, F_CAR = 1312, F_EPOCH = 1328, F_END = 1328 + 132;
__device__ uint32_t g_flags[F_END];

#define NTURN 256

enum { K_Q = 0, K_KV = 1, K_L = 2, K_T = 3, K_OA = 4, K_OB = 5, K_END = 7 };
constexpr int NCLUSTERS = 66, MAXITEMS = 16;
constexpr int A_STAGE = 16384, B_SLOT = 32768;
constexpr int SM_B = 6 * A_STAGE, SM_CARRY = SM_B + 4 * B_SLOT, SM_BAR = SM_CARRY + 2048, SM_TOTAL = SM_BAR + 512;

struct Params {
  CUtensorMap mapA[3];
  CUtensorMap mapB[6];
  CUtensorMap mapO[2];
  uint4* scr;
  uint4* carry;
  uint32_t* flags;
  uint32_t zero;
  uint16_t sched[NCLUSTERS * MAXITEMS];
};

__device__ __forceinline__ bool item_narrow(uint32_t item) { return (item & 0x204) == 0x204; }
__device__ __forceinline__ int item_nk(uint32_t item) {
  const uint32_t kind = item & 7;
  return (kind == K_KV ? 8 : kind == K_OB ? 64 : 16) >> item_narrow(item);
}
__device__ __forceinline__ int item_row(uint32_t kind, int g, int pos) {
  if (kind == K_L || kind == K_OA) return g == 0 ? (pos - 1) * 1024 : 64 * (3 * g - 2 + pos + (g > 5));
  return 64 * (3 * g - 1 + pos);
}

__device__ __forceinline__ void wait_flag(const uint32_t* f, uint32_t target) {
  uint32_t it = 0;
#pragma unroll 1
  while (true) {
    uint32_t v;
    asm volatile("ld.acquire.gpu.global.u32 %0, [%1];" : "=r"(v) : "l"(f) : "memory");
    if ((int)(v - target) >= 0) break;
    __nanosleep(40);
    if (++it > (1u << 18)) break;
  }
  asm volatile("fence.proxy.async.global;" ::: "memory");
}
__device__ __forceinline__ uint32_t wait_bits(const uint32_t* f, uint32_t inv, uint32_t mask) {
  uint32_t it = 0, v;
#pragma unroll 1
  while (true) {
    asm volatile("ld.acquire.gpu.global.u32 %0, [%1];" : "=r"(v) : "l"(f) : "memory");
    v ^= inv;
    if (!(~v & mask)) break;
    __nanosleep(40);
    if (++it > (1u << 18)) break;
  }
  asm volatile("fence.proxy.async.global;" ::: "memory");
  return v;
}
__device__ __forceinline__ void red_add(uint32_t* f) { asm volatile("red.relaxed.gpu.global.add.u32 [%0], 1;" ::"l"(f) : "memory"); }
__device__ __forceinline__ void red_xor(uint32_t* f, uint32_t v) {
  asm volatile("red.relaxed.gpu.global.xor.b32 [%0], %1;" ::"l"(f), "r"(v) : "memory");
}

__device__ __noinline__ void attn_fallback(uint4* q, const uint4* __restrict__ k, int row0, int lane) {
  const int g = lane >> 2, tq = lane & 3;
  q += row0 * 16;
  k += lane ^ (lane >> 3);
  const uint4* v = k + 2 * PLANE;
  float o[16][4];
#pragma unroll
  for (int i = 0; i < 16; i++) o[i][0] = o[i][1] = o[i][2] = o[i][3] = 0.f;
  float m0 = -INFINITY, m1 = -INFINITY, l0 = 0.f, l1 = 0.f;
#pragma unroll 1
  for (int k0 = 0; k0 < row0 + 16; k0 += 16) {
    float sc[2][4] = {{0.f, 0.f, 0.f, 0.f}, {0.f, 0.f, 0.f, 0.f}};
#pragma unroll 1
    for (int cg = 0; cg < 4; cg++) {
      const uint4 qa = __ldcg(q + cg * 32 + (lane ^ (lane >> 3)));
      const uint4 qb = __ldcg(q + 128 + cg * 32 + (lane ^ (lane >> 3)));
#pragma unroll
      for (int t = 0; t < 2; t++) {
        const uint4 kk = __ldcg(k + (k0 + 8 * t) * 16 + cg * 32);
        mma_16816(sc[t], qa.x, qb.x, qa.y, qb.y, kk.x, kk.y);
        mma_16816(sc[t], qa.z, qb.z, qa.w, qb.w, kk.z, kk.w);
      }
    }
    float x0 = -INFINITY, x1 = -INFINITY;
#pragma unroll
    for (int t = 0; t < 2; t++) {
#pragma unroll
      for (int e = 0; e < 2; e++) {
        const int key = k0 + 8 * t + 2 * tq + e;
        if (key > row0 + g) sc[t][e] = -INFINITY;
        if (key > row0 + g + 8) sc[t][2 + e] = -INFINITY;
        x0 = fmaxf(x0, sc[t][e]);
        x1 = fmaxf(x1, sc[t][2 + e]);
      }
    }
    x0 = fmaxf(x0, __shfl_xor_sync(0xffffffffu, x0, 1));
    x1 = fmaxf(x1, __shfl_xor_sync(0xffffffffu, x1, 1));
    x0 = fmaxf(x0, __shfl_xor_sync(0xffffffffu, x0, 2));
    x1 = fmaxf(x1, __shfl_xor_sync(0xffffffffu, x1, 2));
    const float n0 = fmaxf(m0, x0), n1 = fmaxf(m1, x1);
    const float a0 = ex2(m0 - n0), a1 = ex2(m1 - n1);
    m0 = n0;
    m1 = n1;
    l0 *= a0;
    l1 *= a1;
    uint32_t pa[4];
#pragma unroll
    for (int t = 0; t < 2; t++) {
      const float e0 = ex2(sc[t][0] - m0), e1 = ex2(sc[t][1] - m0);
      const float e2 = ex2(sc[t][2] - m1), e3 = ex2(sc[t][3] - m1);
      l0 += e0 + e1;
      l1 += e2 + e3;
      pa[2 * t] = pack_bf16(e0, e1);
      pa[2 * t + 1] = pack_bf16(e2, e3);
    }
#pragma unroll
    for (int cg = 0; cg < 4; cg++) {
      const uint4 va = __ldcg(v + k0 * 16 + cg * 32);
      const uint4 vb = __ldcg(v + k0 * 16 + 128 + cg * 32);
#pragma unroll
      for (int r = 0; r < 4; r++) {
        const uint32_t w0 = r == 0 ? va.x : r == 1 ? va.y : r == 2 ? va.z : va.w;
        const uint32_t w1 = r == 0 ? vb.x : r == 1 ? vb.y : r == 2 ? vb.z : vb.w;
        float(&oo)[4] = o[4 * cg + r];
        oo[0] *= a0;
        oo[1] *= a0;
        oo[2] *= a1;
        oo[3] *= a1;
        mma_16816(oo, pa[0], pa[1], pa[2], pa[3], movm_t(w0), movm_t(w1));
      }
    }
  }
  l0 += __shfl_xor_sync(0xffffffffu, l0, 1);
  l1 += __shfl_xor_sync(0xffffffffu, l1, 1);
  l0 += __shfl_xor_sync(0xffffffffu, l0, 2);
  l1 += __shfl_xor_sync(0xffffffffu, l1, 2);
  const float i0 = 1.f / l0, i1 = 1.f / l1;
  __syncwarp();
  uint32_t* o0 = reinterpret_cast<uint32_t*>(q + g * 4) + tq;
#pragma unroll
  for (int i = 0; i < 16; i++) {
    uint32_t* d = o0 + (i >> 2) * 128 + ((i & 3) ^ (g >> 1)) * 4;
    d[0] = pack_bf16(o[i][0] * i0, o[i][1] * i0);
    d[512] = pack_bf16(o[i][2] * i1, o[i][3] * i1);
  }
}

#define KB_LIMIT 1.2089258e24f
#define KB_LOW 9.094947e-13f

__device__ __forceinline__ void local_attn(const uint32_t (&lo)[24], const uint32_t (&hi)[24], const uint32_t (&hk)[8], const uint32_t (&hv)[8],
                                           uint4* __restrict__ dst, bool first, int lane) {
  const int g = lane >> 2, tq = lane & 3;
  float s[2][3][4];
#pragma unroll
  for (int h = 0; h < 2; h++)
#pragma unroll
    for (int jj = 0; jj < 3; jj++) {
      s[h][jj][0] = s[h][jj][1] = s[h][jj][2] = s[h][jj][3] = 0.f;
#pragma unroll
      for (int st = 0; st < 2; st++) {
        const int c = 4 * h + 2 * st;
        mma_16816(s[h][jj], lo[c], hi[c], lo[c + 1], hi[c + 1], jj == 0 ? hk[c] : jj == 1 ? lo[8 + c] : hi[8 + c],
                  jj == 0 ? hk[c + 1] : jj == 1 ? lo[9 + c] : hi[9 + c]);
      }
    }
  const bool h0 = 2 * tq > g, h1 = 2 * tq + 1 > g;
  const uint32_t m = (h0 ? 0xFFFFu : 0u) | (h1 ? 0xFFFF0000u : 0u);
  float u0[2], u1[2], w0[2], w1[2], mu[2], mw[2];
#pragma unroll
  for (int h = 0; h < 2; h++) {
    u0[h] = h0 ? s[h][0][0] : s[h][1][0];
    u1[h] = h1 ? s[h][0][1] : s[h][1][1];
    w0[h] = h0 ? s[h][1][2] : s[h][2][2];
    w1[h] = h1 ? s[h][1][3] : s[h][2][3];
    if (first) {
      if (h0) u0[h] = -INFINITY;
      if (h1) u1[h] = -INFINITY;
    }
    mu[h] = fmaxf(u0[h], u1[h]);
    mw[h] = fmaxf(w0[h], w1[h]);
  }
#pragma unroll
  for (int o = 1; o <= 2; o++)
#pragma unroll
    for (int h = 0; h < 2; h++) {
      mu[h] = fmaxf(mu[h], __shfl_xor_sync(0xffffffffu, mu[h], o));
      mw[h] = fmaxf(mw[h], __shfl_xor_sync(0xffffffffu, mw[h], o));
    }
  const float c = 0.17677669529663687f * 1.4426950408889634f;
  float lu[2], lw[2];
#pragma unroll
  for (int h = 0; h < 2; h++) {
    u0[h] = ex2((u0[h] - mu[h]) * c);
    u1[h] = ex2((u1[h] - mu[h]) * c);
    w0[h] = ex2((w0[h] - mw[h]) * c);
    w1[h] = ex2((w1[h] - mw[h]) * c);
    lu[h] = u0[h] + u1[h];
    lw[h] = w0[h] + w1[h];
  }
#pragma unroll
  for (int o = 1; o <= 2; o++)
#pragma unroll
    for (int h = 0; h < 2; h++) {
      lu[h] += __shfl_xor_sync(0xffffffffu, lu[h], o);
      lw[h] += __shfl_xor_sync(0xffffffffu, lw[h], o);
    }
#pragma unroll
  for (int h = 0; h < 2; h++) {
    const float iu = rcp(lu[h]), iw = rcp(lw[h]);
    const uint32_t pu = pack_bf16(u0[h] * iu, u1[h] * iu), pw = pack_bf16(w0[h] * iw, w1[h] * iw);
    float o[4][4];
#pragma unroll
    for (int cc = 0; cc < 4; cc++) {
      o[cc][0] = o[cc][1] = o[cc][2] = o[cc][3] = 0.f;
      mma_16816(o[cc], pu & m, 0u, pu & ~m, pw & m, hv[4 * h + cc], lo[16 + 4 * h + cc]);
      mma_1688(o[cc], 0u, pw & ~m, hi[16 + 4 * h + cc]);
    }
    dst[h * 32] = make_uint4(pack_bf16(o[0][0], o[0][1]), pack_bf16(o[1][0], o[1][1]), pack_bf16(o[2][0], o[2][1]), pack_bf16(o[3][0], o[3][1]));
    dst[h * 32 + 128] =
        make_uint4(pack_bf16(o[0][2], o[0][3]), pack_bf16(o[1][2], o[1][3]), pack_bf16(o[2][2], o[2][3]), pack_bf16(o[3][2], o[3][3]));
  }
}

__global__ __cluster_dims__(2, 1, 1) __launch_bounds__(512, 1) void fused_kernel(const __grid_constant__ Params p) {
  extern __shared__ __align__(1024) uint8_t smem_dyn[];
  DECLARE_READY();
  const uint32_t sbase = smem_u32(smem_dyn);
  const uint32_t afull0 = sbase + SM_BAR, aempty0 = afull0 + 48, bfull0 = afull0 + 96, bempty0 = afull0 + 128, carbar = afull0 + 160,
                 pub0 = afull0 + 168;
  const uint32_t bbase = sbase + SM_B;
  const int wg = __reduce_min_sync(0xffffffffu, (int)(threadIdx.x >> 7));
  const uint32_t rank = blockIdx.x & 1;
  const uint16_t* sched = p.sched + (blockIdx.x >> 1) * MAXITEMS;

  auto fill_b = [&](uint32_t item, int t, uint32_t pb) {
    const uint32_t kind = item & 7, j = (item >> 7) & 15, sl = pb & 3;
    if (((item >> 3) & 15) == 0) mbar_arrive_n(bempty0 + 8 * sl, 1);
    mbar_expect_tx(bfull0 + 8 * sl, kind == K_L ? 24576 : 32768);
    const uint32_t nt = kind == K_KV ? j : 2 * j + rank, dst = bbase + sl * B_SLOT;
    const uint32_t cb = item_narrow(item) ? nt - 8 : nt * 2 + (t & 1), ks = item_narrow(item) ? t : t >> 1;
    if (kind == K_OA) {
      tma_load_5d(dst, &p.mapB[K_OA], bfull0 + 8 * sl, cb * 128, ks * 4);
      tma_load_5d(dst + 16384, &p.mapB[K_OA], bfull0 + 8 * sl, cb * 128 + 64, ks * 4);
    } else if (kind == K_L) {
      tma_load_3d(dst, &p.mapB[K_L], bfull0 + 8 * sl, nt * 64, t * 64, 0);
    } else {
      tma_load_3d(dst, &p.mapB[kind == K_KV ? 1 + 2 * rank : kind], bfull0 + 8 * sl, 0, ks * 128, cb * 2);
    }
  };
  auto fill_a = [&](uint32_t item, int d, int pos, uint32_t u, bool mc) {
    const uint32_t kind = item & 7;
    const int row = item_row(kind, (item >> 3) & 15, pos);
    const uint32_t dst = sbase + u * A_STAGE, bar = afull0 + 8 * u;
    mbar_expect_tx(bar, A_STAGE);
    if (kind >= K_OA) {
      bulk_load_mc(dst + rank * 8192, p.scr + ((kind == K_OA ? PL_OA : PL_Q) + d) * PLANE + row * 16 + rank * 512, 8192, bar, (uint16_t)3);
    } else {
      const int blk = 2 * d + (kind == K_L ? (row >> 10) * 16 : 0), r = kind == K_L ? row & 1023 : row;
      if (mc) {
        tma_load_3d_mc(dst + rank * 8192, &p.mapA[kind], bar, 0, r, blk + rank, (uint16_t)3);
      } else {
        tma_load_3d(dst, &p.mapA[kind], bar, 0, r, blk);
        tma_load_3d(dst + 8192, &p.mapA[kind], bar, 0, r, blk + 1);
      }
    }
  };
  if (threadIdx.x == 0) {
    for (int i = 0; i < 4; i++) {
      mbar_init(bfull0 + 8 * i, 1);
      mbar_init(bempty0 + 8 * i, 3);
    }
    asm volatile("fence.proxy.async.shared::cta;" ::: "memory");
    for (int t = 0; t < 4; t++) fill_b(sched[0], t, t);
  } else if (threadIdx.x == 32) {
    for (int i = 0; i < 6; i++) {
      mbar_init(afull0 + 8 * i, 1);
      mbar_init(aempty0 + 8 * i, 2);
    }
    asm volatile("fence.proxy.async.shared::cta;" ::: "memory");
    const int g0 = ((sched[0] >> 3) & 15) == 0;
    for (int w = 0; w + g0 < 3; w++) fill_a(sched[0], 0, w + g0, 2 * w, false);
    asm volatile("fence.mbarrier_init.release.cluster;" ::: "memory");
  } else if (threadIdx.x == 64) {
    mbar_init(carbar, 1);
    for (int i = 0; i < MAXITEMS; i++) mbar_init(pub0 + 8 * i, 12);
  }
  __syncthreads();
  cluster_sync_relaxed();

  if (wg == 0) {
    asm volatile("setmaxnreg.dec.sync.aligned.u32 32;");
    if (threadIdx.x == 0) {
      const uint32_t e = __ldcg(p.flags + F_EPOCH + blockIdx.x) + 1;
      uint32_t pb = 4;
      for (int it = 0; it < MAXITEMS; it++) {
        const uint32_t item = sched[it];
        const uint32_t kind = item & 7;
        if (kind == K_END) break;
        if (kind != K_T) {
          const int nk = item_nk(item);
          const uint32_t g = (item >> 3) & 15, nb = g ? 3 : 2;
          uint32_t old = item_narrow(item) && kind == K_OB ? wait_bits(p.flags + F_CTX + g * 32, (e & 1) - 1, 0) : 0;
          for (int t = it == 0 ? 4 : 0; t < nk; t++, pb++) {
            mbar_wait(bempty0 + 8 * (pb & 3), ((pb >> 2) & 1) ^ 1);
            fill_b(item, t, pb);
            if ((old >>= 1) & 1) prefetch_l2(p.scr + (PL_Q + t + 1) * PLANE + (3 * g + 2 - nb) * 1024 + rank * nb * 512, nb * 8192);
          }
        } else {
          const int g = (item >> 3) & 15, j = (item >> 7) & 15;
          const uint4* src = p.scr + (PL_KV + (j % KVR) * 4 + rank) * PLANE;
          const int n = ((3 * g + 1) >> 1) + 1;
          uint32_t groups = 0;
          for (int t = 0; t < n; t++, src += 2048) {
            const uint32_t need = (4u << 2 * min((2 * t + 2) / 3, g)) - 1;
            if (~groups & need) groups = wait_bits(p.flags + F_KV + j * 32, (e & 1) - 1, need);
            const uint32_t nskip = t == n - 1 ? 1 + (g & 1) : 0;
            uint32_t sl = pb & 3;
            mbar_wait(bempty0 + 8 * sl, ((pb >> 2) & 1) ^ 1);
            if (nskip) mbar_arrive_n(bempty0 + 8 * sl, nskip);
            mbar_expect_tx(bfull0 + 8 * sl, 32768);
            pb++;
            if (nskip == 2) {
              bulk_load(bbase + sl * B_SLOT, src, 16384, bfull0 + 8 * sl);
              bulk_load(bbase + sl * B_SLOT + 16384, src + 2 * PLANE, 16384, bfull0 + 8 * sl);
              continue;
            }
            bulk_load(bbase + sl * B_SLOT, src, 32768, bfull0 + 8 * sl);
            sl = pb & 3;
            mbar_wait(bempty0 + 8 * sl, ((pb >> 2) & 1) ^ 1);
            if (nskip) mbar_arrive_n(bempty0 + 8 * sl, nskip);
            mbar_expect_tx(bfull0 + 8 * sl, 32768);
            bulk_load(bbase + sl * B_SLOT, src + 2 * PLANE, 32768, bfull0 + 8 * sl);
            pb++;
          }
        }
      }
    } else if (threadIdx.x == 32) {
      const uint32_t e = __ldcg(p.flags + F_EPOCH + blockIdx.x) + 1;
      uint32_t pk = ((sched[0] >> 3) & 15) == 0 ? 0x0101 : 0x010101;
      auto next_stage = [&](uint32_t w) {
        const uint32_t n = pk >> (8 * w), u = 2 * w + (n & 1);
        mbar_wait(aempty0 + 8 * u, ((n >> 1) & 1) ^ 1);
        pk += 1u << (8 * w);
        return u;
      };
      for (int it = 0; it < MAXITEMS; it++) {
        const uint32_t item = sched[it];
        const uint32_t kind = item & 7;
        if (kind == K_END) break;
        const int g = (item >> 3) & 15, j = (item >> 7) & 15;
        const int nd = kind == K_T ? 1 : item_nk(kind) >> 1;
        if (kind == K_KV && j >= KVR) wait_flag(p.flags + F_TD + j - KVR, 22 * e);
        if (kind == K_OA) wait_flag(p.flags + F_L + g, 16 * e);
        if (kind == K_T) wait_flag(p.flags + F_Q + j * 16 + g, e);
        uint32_t heads = 0;
        for (int d = it == 0; d < nd; d++) {
          if (kind == K_OB && !(heads >> d & 1)) heads = wait_bits(p.flags + F_CTX + g * 32, (e & 1) - 1, 1u << d);
          for (int rho = 0; rho < 3 - (g == 0); rho++) {
            uint32_t w = rho + 3 - (item >> 11);
            if (w >= 3) w -= 3;
            const uint32_t u = next_stage(w);
            if (kind == K_T) {
              mbar_expect_tx(afull0 + 8 * u, A_STAGE);
              bulk_load(sbase + u * A_STAGE, p.scr + (PL_Q + 2 * j + rank) * PLANE + (3 * g + 1 - rho) * 1024, A_STAGE, afull0 + 8 * u);
            } else {
              fill_a(item, d, rho + (g == 0), u, true);
            }
          }
        }
      }
      for (int i = 0; i < 6; i++) next_stage(i >> 1);
    } else if (threadIdx.x == 64) {
      for (int it = 0; it < MAXITEMS; it++) {
        const uint32_t item = sched[it];
        const uint32_t kind = item & 7;
        const int g = (item >> 3) & 15, j = (item >> 7) & 15;
        mbar_wait(pub0 + 8 * (kind == K_END ? MAXITEMS - 1 : it), 0);
        if (kind == K_END) break;
        if (kind >= K_OA) continue;
        asm volatile("fence.acq_rel.gpu;" ::: "memory");
        if (kind == K_Q) red_add(p.flags + F_Q + (2 * j + rank) * 16 + g);
        if (kind == K_KV) red_xor(p.flags + F_KV + j * 32, 1u << (2 * g + rank));
        if (kind == K_L) {
          red_add(p.flags + F_L + g);
          if (g == 0) red_add(p.flags + F_CAR + 2 * j + rank);
        }
        if (kind == K_T) {
          red_xor(p.flags + F_CTX + g * 32, 1u << (2 * j + rank));
          red_add(p.flags + F_TD + j);
        }
      }
      red_add(p.flags + F_EPOCH + blockIdx.x);
    } else if (threadIdx.x == 96) {
      for (int i = 0; i < 3; i++) prefetch_tmap(&p.mapA[i]);
      for (int i = 0; i < 6; i++) prefetch_tmap(&p.mapB[i]);
      prefetch_tmap(&p.mapO[0]);
      prefetch_tmap(&p.mapO[1]);
    }
  } else {
    asm volatile("setmaxnreg.inc.sync.aligned.u32 160;");
    const int cw = wg - 1;
    const int wq = __reduce_min_sync(0xffffffffu, (int)((threadIdx.x >> 5) & 3));
    auto turn = [&](uint32_t dep = 0) {
      bar_sync((1 + cw) | dep, NTURN);
    };
    auto pass = [&]() { bar_arrive(cw == 0 ? 3 : cw, NTURN); };
    auto rank_of = [&](uint32_t item) {
      const int r = cw + (item >> 11);
      return r >= 3 ? r - 3 : r;
    };
    if (cw == 1) pass();
    if (cw == 2) { turn(); pass(); }
    const uint32_t abase = sbase + cw * (2 * A_STAGE), afull = afull0 + 16 * cw, aempty = aempty0 + 16 * cw;
    const uint32_t adesc = ((abase & 0x3FFFF) >> 4) | (1u << 16), bdesc = (bbase & 0x3FFFF) >> 4;
    uint32_t pa = 0, pb = 0;
    int it = 0;
    uint32_t item = sched[0];
    auto publish = [&](int i, uint32_t skip = 0) {
      __syncwarp();
      mbar_arrive_if0(pub0 + 8 * i, (threadIdx.x & 31) | skip);
    };
    auto test_ab = [&](uint32_t a, uint32_t b) {
      test_a(afull + 8 * (a & 1), (a >> 1) & 1);
      test_b(bfull0 + 8 * (b & 3), (b >> 2) & 1);
    };
    auto wait_ab = [&]() {
      if (!ready_ab()) {
        mbar_wait_u(afull + 8 * (pa & 1), (pa >> 1) & 1);
        mbar_wait_u(bfull0 + 8 * (pb & 3), (pb >> 2) & 1);
      }
    };
    test_ab(0, 0);
    auto gturn = [&](auto second_c, bool hold, auto mma, auto meanwhile, uint32_t dep = 0) {
      constexpr bool SECOND = decltype(second_c)::value != 0;
      const uint32_t da = adesc + (pa & 1) * (A_STAGE >> 4), db = bdesc + (pb & 3) * (B_SLOT >> 4);
      if (decltype(second_c)::value != 1) wait_ab();
      else if (!ready_b()) mbar_wait_u(bfull0 + 8 * (pb & 3), (pb >> 2) & 1);
      turn(dep);
      wg_fence();
      mma(da, db);
      wg_commit();
      pass();
      if (SECOND) test_ab(pa + 1, pb + 1);
      else test_b(bfull0 + 8 * ((pb + 1) & 3), ((pb + 1) >> 2) & 1);
      meanwhile();
      wg_wait<0>();
      if (SECOND) {
        mbar_arrive_cta_if0(wq < 2 ? aempty + 8 * (pa & 1) : bempty0 + 8 * (pb & 3), wq < 2 ? wq : rank,
                            (threadIdx.x & 31) | (wq == 3) | (hold && wq < 2));
        pa++;
      } else {
        mbar_arrive_if0(bempty0 + 8 * (pb & 3), threadIdx.x & 127);
      }
      __syncwarp();
      pb++;
    };
    constexpr std::true_type YES{};
    constexpr std::false_type NO{};
    constexpr std::integral_constant<int, 2> ONCE{};
    auto nothing = []() {};
    auto idle = [&]() { return ((item >> 3) & 15) == 0 && rank_of(item) == 2; };
    auto skip_item = [&]() {
      const int n = (item & 7) == K_T ? 2 : item_nk(item);
      publish(it);
#pragma unroll 1
      for (int i = 2; i < n; i++) {
        turn();
        pass();
      }
      pb += n;
      test_ab(pa, pb);
      item = sched[++it];
    };

    if ((item & 7) == K_L && idle()) skip_item();
    while ((item & 7) == K_L) {
      const int g = (item >> 3) & 15, j = (item >> 7) & 15;
      const int rho = rank_of(item);
      float acc[96];
      auto mma = [&](int kb, bool first) {
        return [&acc, kb, first](uint32_t da, uint32_t db) {
#pragma unroll
          for (int k = 0; k < 4; k++) wgmma_n192_tb(acc, da + kb * 512 + k * 2, (db | (512u << 16)) + k * 128, !(first && k == 0));
        };
      };
      gturn(NO, false, mma(0, true), nothing);
#pragma unroll 1
      for (int d = 7; d > 0; d--) {
        gturn(YES, false, mma(1, false), nothing);
        gturn(NO, false, mma(0, false), nothing);
      }
      gturn(YES, true, mma(1, false), nothing);
      fence_regs(acc);
      const int lane = threadIdx.x & 31;
      uint32_t lo[24], hi[24], hk[8], hv[8];
#pragma unroll
      for (int i = 0; i < 24; i++) {
        lo[i] = pack_bf16(acc[4 * i], acc[4 * i + 1]);
        hi[i] = pack_bf16(acc[4 * i + 2], acc[4 * i + 3]);
      }
#pragma unroll
      for (int i = 16; i < 24; i++) {
        hi[i] = movm_t(hi[i]);
        lo[i] = movm_t(lo[i]);
      }
      const int row = item_row(K_L, g, rho + (g == 0));
      const int b = (row >> 6) & 15;
      const uint32_t xb = abase + ((pa - 1) & 1) * A_STAGE + lane * 16;
      const uint32_t cb = sbase + SM_CARRY + lane * 16;
      if (wq < 3) {
#pragma unroll
        for (int i = 0; i < 4; i++) sts128(xb + wq * 2048 + i * 512, hi[8 + 4 * i], hi[9 + 4 * i], hi[10 + 4 * i], hi[11 + 4 * i]);
      }
#pragma unroll
      for (int i = 0; i < 8; i++) hk[i] = hv[i] = 0;
      if (wq == 0 && b != 0) {
        if (row == 1024 + 64) {
          const uint32_t e = __ldcg(p.flags + F_EPOCH + blockIdx.x) + 1;
          wait_flag(p.flags + F_CAR + 2 * j + rank, e);
          __syncwarp();
          const uint4* c = p.carry + (2 * j + rank) * 128 + lane;
          const uint4 c0 = __ldcg(c), c1 = __ldcg(c + 32), c2 = __ldcg(c + 64), c3 = __ldcg(c + 96);
          hk[0] = c0.x; hk[1] = c0.y; hk[2] = c0.z; hk[3] = c0.w; hk[4] = c1.x; hk[5] = c1.y; hk[6] = c1.z; hk[7] = c1.w;
          hv[0] = c2.x; hv[1] = c2.y; hv[2] = c2.z; hv[3] = c2.w; hv[4] = c3.x; hv[5] = c3.y; hv[6] = c3.z; hv[7] = c3.w;
        } else {
          mbar_wait_u(carbar, (b - 1 - (row >> 10)) & 1);
          lds128(cb, hk[0], hk[1], hk[2], hk[3]);
          lds128(cb + 512, hk[4], hk[5], hk[6], hk[7]);
          lds128(cb + 1024, hv[0], hv[1], hv[2], hv[3]);
          lds128(cb + 1536, hv[4], hv[5], hv[6], hv[7]);
        }
      }
      bar_sync(4 + cw, 128);
      if (wq > 0) {
        const uint32_t a = xb + (wq - 1) * 2048;
        lds128(a, hk[0], hk[1], hk[2], hk[3]);
        lds128(a + 512, hk[4], hk[5], hk[6], hk[7]);
        lds128(a + 1024, hv[0], hv[1], hv[2], hv[3]);
        lds128(a + 1536, hv[4], hv[5], hv[6], hv[7]);
      }
      if (wq == 3) {
        if (row == 1024) {
          uint4* c = p.carry + (2 * j + rank) * 128 + lane;
#pragma unroll
          for (int i = 0; i < 4; i++) c[32 * i] = make_uint4(hi[8 + 4 * i], hi[9 + 4 * i], hi[10 + 4 * i], hi[11 + 4 * i]);
        } else {
#pragma unroll
          for (int i = 0; i < 4; i++) sts128(cb + i * 512, hi[8 + 4 * i], hi[9 + 4 * i], hi[10 + 4 * i], hi[11 + 4 * i]);
          __syncwarp();
          mbar_arrive_if0(carbar, lane);
        }
      }
      bar_sync(4 + cw, 128);
      mbar_arrive_cta_if0(aempty + 8 * ((pa - 1) & 1), wq & 1, lane | (wq >> 1));
      local_attn(lo, hi, hk, hv, p.scr + (PL_OA + j) * PLANE + (row + wq * 16) * 16 + rank * 64 + (lane ^ (lane >> 3)), b == 0 && wq == 0,
                 lane);
      publish(it);
      item = sched[++it];
    }

    float Y[64];
    uint32_t done;
    uint4* pdst;
    auto stores = [&](uint4* dst, const uint32_t (&r)[32], uint32_t skip) {
#pragma unroll
      for (int i = 0; i < 8; i++) stg128_if0(dst + (i >> 1) * 32 + (i & 1) * 128, r[4 * i], r[4 * i + 1], r[4 * i + 2], r[4 * i + 3], skip);
    };
    auto pack = [&](uint32_t (&r)[32], const float (&acc)[64]) {
#pragma unroll
      for (int i = 0; i < 16; i++) {
        r[8 * (i >> 2) + (i & 3)] = pack_bf16(acc[4 * i], acc[4 * i + 1]);
        r[8 * (i >> 2) + (i & 3) + 4] = pack_bf16(acc[4 * i + 2], acc[4 * i + 3]);
      }
    };
    auto scale = [&](float (&acc)[64], float s0, float s1) {
#pragma unroll
      for (int i = 0; i < 64; i++) acc[i] *= i & 2 ? s1 : s0;
    };
    auto late = [&](float& x, float& y) {
      uint32_t t;
      asm volatile("mov.u32 %0, %%clock;" : "=r"(t)::"memory");
      x = __uint_as_float(__float_as_uint(x) | (t & p.zero));
      y = __uint_as_float(__float_as_uint(y) | (t & p.zero));
    };
    auto flush = [&]() {
      uint32_t r[32];
      pack(r, Y);
      stores(pdst, r, done);
      publish(it - 1, done);
    };
    auto no_pending = [&]() {
      done = 1;
      pdst = p.scr;
#pragma unroll
      for (int i = 0; i < 64; i++) Y[i] = 0.f;
    };
    no_pending();
    auto mma128 = [&](auto scr_c, float (&acc)[64], bool keep) {
      return [&acc, keep](uint32_t da, uint32_t db) {
        constexpr bool SCR = decltype(scr_c)::value;
#pragma unroll
        for (int k = 0; k < 8; k++)
          wgmma_n128<1>(acc, da + (k & 1) * 2 + ((k >> 1) & 1) * (SCR ? 32 : 4) + (k >> 2) * (SCR ? 64 : 512), SCR ? HI64 : HI128,
                        (db | (1024u << 16)) + k * 128, HI128, k != 0 || keep);
      };
    };
    auto all_but_last = [&](auto scr_c, float (&X)[64]) {
      int n = item_nk(item);
      gturn(NO, false, mma128(scr_c, X, false), flush);
      gturn(YES, false, mma128(scr_c, Y, false), nothing);
#pragma unroll 1
      while (true) {
        gturn(NO, false, mma128(scr_c, X, true), nothing);
        if ((n -= 2) == 2) break;
        gturn(YES, false, mma128(scr_c, Y, true), nothing);
      }
      fence_regs(X);
    };
    while ((item & 7) < K_OA) {
      if (idle()) {
        flush();
        done = 1;
        skip_item();
        continue;
      }
      const uint32_t kind = item & 7;
      const int g = (item >> 3) & 15, j = (item >> 7) & 15;
      const int rho = rank_of(item);
      if (kind != K_T) {
        float X[64];
        all_but_last(NO, X);
        const int lane = threadIdx.x & 31;
        const int row = item_row(K_Q, g, rho + (g == 0)) + wq * 16;
        constexpr float QS = 0.08838834764831845f * 1.4426950408889634f;
        if (kind == K_Q) scale(X, QS, QS);
        pdst = p.scr + ((kind == K_Q ? PL_Q + j * 4 : PL_KV + (j % KVR) * 4) + rank * 2 + 1) * PLANE + row * 16 + (lane ^ (lane >> 3));
        uint32_t rx[32];
        pack(rx, X);
        stores(pdst - PLANE, rx, 0);
        item = sched[++it];
        gturn(YES, false, mma128(NO, Y, true), nothing);
        fence_regs(Y);
        test_ab(pa, pb);
        if (kind == K_Q) scale(Y, QS, QS);
        if (p.zero) stores(pdst - PLANE, rx, 0);
        done = 0;
      } else {
        float(&O)[64] = Y;
        float S[64];
        float l0 = 0.f, l1 = 0.f;
        float sc0, sc1;
        const uint32_t sel = threadIdx.x & 127;
        const int b = 3 * g + 1 - rho;
        enum { FIRST, MID, LAST, HALF };
        auto round = [&](auto mode_c) {
          constexpr int MODE = decltype(mode_c)::value;
          constexpr int NI = MODE == HALF ? 8 : 16;
          const uint32_t shared = MODE == HALF ? rho == 0 : 0;
          const uint32_t tv = pb + 1 - shared;
          {
            const uint32_t dq = adesc + (pa & 1) * (A_STAGE >> 4);
            const uint32_t dk = (bdesc + (pb & 3) * 2048) | (1u << 16);
            wait_ab();
            turn();
            wg_fence();
#pragma unroll
            for (int k = 0; k < 8; k++) {
              if (MODE == HALF) wgmma_n64(S, dq + (k >> 1) * 32 + (k & 1) * 2, dk + (k >> 1) * 32 + (k & 1) * 2, k != 0);
              else wgmma_n128<0>(S, dq + (k >> 1) * 32 + (k & 1) * 2, HI64, dk + (k >> 1) * 32 + (k & 1) * 2, HI64, k != 0);
            }
            wg_commit();
            pass();
          }
          test_b(bfull0 + 8 * (tv & 3), (tv >> 2) & 1);
          if (!ready_b()) mbar_wait_u(bfull0 + 8 * (tv & 3), (tv >> 2) & 1);
          if (MODE == FIRST) flush();
          wg_wait<0>();
#pragma unroll
          for (int i = 0; i < 4 * NI; i++) asm volatile("" : "+f"(S[i])::"memory");
          mbar_arrive_if0(bempty0 + 8 * (pb & 3), sel | shared);
          if (MODE >= LAST) mbar_arrive_cta_if0(aempty + 8 * (pa & 1), wq & 1, (sel & 31) | (wq >> 1));
          uint32_t P[2 * NI];
          if (MODE >= LAST) {
            const int lane = threadIdx.x & 31;
            const int row = wq * 16 + (lane >> 2) - 2 * (lane & 3);
#pragma unroll
            for (int i = 0; i < 8; i++) {
#pragma unroll
              for (int e = 0; e < 2; e++) {
                if (8 * i + e > row) S[4 * (NI - 8 + i) + e] = -INFINITY;
                if (8 * i + e > row + 8) S[4 * (NI - 8 + i) + 2 + e] = -INFINITY;
              }
            }
          }
          float s0 = 0.f, s1 = 0.f, t0 = 0.f, t1 = 0.f;
#pragma unroll
          for (int i = 0; i < NI; i++) {
            const float e0 = ex2(S[4 * i + 0]);
            const float e1 = ex2(S[4 * i + 1]);
            const float e2 = ex2(S[4 * i + 2]);
            const float e3 = ex2(S[4 * i + 3]);
            s0 += e0;
            t0 += e1;
            s1 += e2;
            t1 += e3;
            P[2 * i] = pack_bf16(e0, e1);
            P[2 * i + 1] = pack_bf16(e2, e3);
          }
          l0 += s0 + t0;
          l1 += s1 + t1;
          uint32_t dep = (__float_as_uint(l0) ^ __float_as_uint(l1)) ^ P[2 * NI - 1];
          if (MODE != FIRST) fence_regs(O);
#pragma unroll
          for (int i = 0; i < 2 * NI; i++) asm volatile("" : "+r"(P[i])::"memory");
          turn(dep & p.zero);
          wg_fence();
          const uint32_t dv = (bdesc + (tv & 3) * 2048 + shared * 1024) | (32u << 16);
#pragma unroll
          for (int k = 0; k < NI / 2; k++)
            wgmma_n128_rs_tb(O, P[4 * k], P[4 * k + 1], P[4 * k + 2], P[4 * k + 3], dv + k * 256, k != 0 || MODE != FIRST);
          wg_commit();
          pass();
          pb = tv + 1;
          if (MODE >= LAST) {
            const int nskip = 1 + (g & 1);
            if (rho + nskip >= 3) pb += 3 - nskip;
            pa++;
          } else {
            test_ab(pa, pb);
          }
          if (MODE >= LAST) {
            l0 += __shfl_xor_sync(0xffffffffu, l0, 1);
            l1 += __shfl_xor_sync(0xffffffffu, l1, 1);
            l0 += __shfl_xor_sync(0xffffffffu, l0, 2);
            l1 += __shfl_xor_sync(0xffffffffu, l1, 2);
            sc0 = rcp(l0);
            sc1 = rcp(l1);
          }
          wg_wait<0>();
          fence_regs(O);
          mbar_arrive_if0(bempty0 + 8 * (tv & 3), sel);
        };
        if (b < 2) {
          flush();
#pragma unroll
          for (int i = 0; i < 64; i++) O[i] = 0.f;
        } else {
          round(std::integral_constant<int, FIRST>{});
#pragma unroll 1
          for (int n = b >> 1; --n;) round(std::integral_constant<int, MID>{});
        }
        item = sched[++it];
        if (b & 1) round(std::integral_constant<int, LAST>{});
        else round(std::integral_constant<int, HALF>{});
        test_ab(pa, pb);
        float z[4] = {0.f, 0.f, 0.f, 0.f};
#pragma unroll
        for (int i = 0; i < 32; i++) z[i & 3] = fmaf(O[2 * i], O[2 * i + 1], z[i & 3]);
        const bool bad = !(l0 <= KB_LIMIT && l0 >= KB_LOW) || !(l1 <= KB_LIMIT && l1 >= KB_LOW) ||
                         !(fabsf(z[0]) + fabsf(z[1]) + fabsf(z[2]) + fabsf(z[3]) <= 3e38f);
        scale(O, sc0, sc1);
        const int lane = threadIdx.x & 31;
        pdst = p.scr + (PL_Q + 2 * j + rank) * PLANE + (b * 64 + wq * 16) * 16 + (lane ^ (lane >> 3));
        done = 0;
        if (__any_sync(0xffffffffu, bad)) {
          attn_fallback(p.scr + (PL_Q + 2 * j + rank) * PLANE, p.scr + (PL_KV + (j % KVR) * 4 + rank) * PLANE, b * 64 + wq * 16,
                        threadIdx.x & 31);
          publish(it - 1);
          no_pending();
          test_ab(pa, pb);
        }
      }
    }

    if ((item & 7) == K_END) {
      flush();
    } else if (idle()) {
      flush();
      skip_item();
    } else {
      const uint32_t kind = item & 7;
      const int g = (item >> 3) & 15, j = (item >> 7) & 15;
      const int row = item_row(kind, g, rank_of(item) + (g == 0)) + wq * 16;
      auto epilogue = [&](float (&acc)[64], int cb) {
        const int lane = threadIdx.x & 31;
        const uint32_t stg = abase + ((pa - 1) & 1) * A_STAGE + wq * 4096;
        const int srow = lane & 15;
#pragma unroll
        for (int jj = 0; jj < 8; jj++) {
          const uint32_t r0 = pack_bf16(acc[8 * jj + 0], acc[8 * jj + 1]);
          const uint32_t r1 = pack_bf16(acc[8 * jj + 2], acc[8 * jj + 3]);
          const uint32_t r2 = pack_bf16(acc[8 * jj + 4], acc[8 * jj + 5]);
          const uint32_t r3 = pack_bf16(acc[8 * jj + 6], acc[8 * jj + 7]);
          const int chunk = (2 * jj + (lane >> 4)) & 7;
          const uint32_t addr = stg + (jj >> 2) * 2048 + srow * 128 + ((chunk ^ (srow & 7)) << 4);
          asm volatile("stmatrix.sync.aligned.m8n8.x4.shared.b16 [%0], {%1,%2,%3,%4};" ::"r"(addr), "r"(r0), "r"(r1), "r"(r2), "r"(r3)
                       : "memory");
        }
        asm volatile("fence.proxy.async.shared::cta;" ::: "memory");
        __syncwarp();
        if (lane == 0) {
          const int col = cb * 128 + (kind == K_OA ? (row >> 10) * 2048 : 1024);
          const int r = kind == K_OA ? row & 1023 : row;
          tma_store_2d(&p.mapO[kind - K_OA], stg, col, r);
          tma_store_2d(&p.mapO[kind - K_OA], stg + 2048, col + 64, r);
          asm volatile("cp.async.bulk.commit_group;" ::: "memory");
        }
      };
      float X[64];
      if (item_narrow(item)) {
        int n = item_nk(item);
        gturn(ONCE, false, mma128(YES, X, false), flush);
#pragma unroll 1
        while (--n) gturn(ONCE, false, mma128(YES, X, true), nothing);
        fence_regs(X);
        epilogue(X, 2 * j + rank - 8);
      } else {
        all_but_last(YES, X);
        epilogue(X, 4 * j + 2 * rank);
        gturn(YES, false, mma128(YES, Y, true), nothing);
        fence_regs(Y);
        epilogue(Y, 4 * j + 2 * rank + 1);
      }
      publish(it);
      item = sched[++it];
    }
    const int rho = rank_of(item);
    if (rho == 0) {
      turn();
      pass();
    }
    if (rho == 1) turn();
    publish(MAXITEMS - 1);
    asm volatile("cp.async.bulk.wait_group.read 0;" ::: "memory");
  }
}

typedef CUresult (*EncodeFn)(CUtensorMap*, CUtensorMapDataType, cuuint32_t, void*, const cuuint64_t*, const cuuint64_t*,
                             const cuuint32_t*, const cuuint32_t*, CUtensorMapInterleave, CUtensorMapSwizzle, CUtensorMapL2promotion,
                             CUtensorMapFloatOOBfill);

void make_map(EncodeFn enc, CUtensorMap* m, const void* ptr, uint64_t d0, uint64_t d1, uint64_t d2, uint64_t s1, uint64_t s2, uint32_t b0,
              uint32_t b1, uint32_t b2) {
  cuuint64_t gd[3] = {d0, d1, d2}, gs[2] = {s1, s2};
  cuuint32_t bd[3] = {b0, b1, b2}, es[3] = {1, 1, 1};
  enc(m, CU_TENSOR_MAP_DATA_TYPE_BFLOAT16, d2 ? 3 : 2, const_cast<void*>(ptr), gd, gs, bd, es, CU_TENSOR_MAP_INTERLEAVE_NONE,
      CU_TENSOR_MAP_SWIZZLE_128B, CU_TENSOR_MAP_L2_PROMOTION_L2_128B, CU_TENSOR_MAP_FLOAT_OOB_FILL_NONE);
}

struct HostState {
  Params p;
  const void* in[9];
  void* out;
  bool valid;
};
HostState g_hs;

const uint16_t h_sched[NCLUSTERS * MAXITEMS] = {
    80, 256, 409, 459, 593, 953, 939, 709, 7, 7, 7, 7, 7, 7, 7, 7,
    848, 129, 401, 177, 827, 1027, 1313, 1219, 909, 7, 7, 7, 7, 7, 7, 7,
    960, 168, 73, 323, 1673, 1561, 1203, 1555, 1675, 172, 7, 7, 7, 7, 7, 7,
    24, 456, 155, 843, 963, 717, 7, 7, 7, 7, 7, 7, 7, 7, 7, 7,
    640, 208, 417, 457, 825, 555, 1681, 1209, 1723, 517, 7, 7, 7, 7, 7, 7,
    840, 440, 147, 275, 553, 1281, 1169, 1433, 969, 1867, 148, 7, 7, 7, 7, 7,
    576, 145, 83, 571, 1331, 917, 7, 7, 7, 7, 7, 7, 7, 7, 7, 7,
    696, 568, 449, 419, 691, 1235, 1411, 901, 7, 7, 7, 7, 7, 7, 7, 7,
    0, 17, 265, 785, 657, 435, 1987, 1859, 68, 7, 7, 7, 7, 7, 7, 7,
    976, 304, 387, 81, 835, 1995, 669, 7, 7, 7, 7, 7, 7, 7, 7, 7,
    792, 432, 521, 201, 673, 569, 1107, 1283, 597, 7, 7, 7, 7, 7, 7, 7,
    64, 176, 139, 291, 1929, 1065, 1321, 1347, 1699, 20, 7, 7, 7, 7, 7, 7,
    672, 536, 179, 539, 1961, 1193, 977, 1179, 725, 7, 7, 7, 7, 7, 7, 7,
    928, 384, 289, 809, 665, 849, 1083, 1225, 1427, 813, 7, 7, 7, 7, 7, 7,
    784, 400, 395, 403, 819, 1947, 1817, 1587, 1691, 60, 7, 7, 7, 7, 7, 7,
    816, 3, 33, 49, 433, 515, 523, 667, 1305, 721, 1825, 1729, 1163, 957, 7, 7,
    912, 320, 649, 817, 1033, 689, 1969, 1091, 829, 7, 7, 7, 7, 7, 7, 7,
    584, 520, 163, 833, 897, 1161, 945, 1491, 1547, 1539, 28, 7, 7, 7, 7, 7,
    896, 184, 19, 339, 979, 589, 7, 7, 7, 7, 7, 7, 7, 7, 7, 7,
    648, 192, 67, 1153, 1409, 1977, 1457, 1849, 1291, 533, 7, 7, 7, 7, 7, 7,
    920, 128, 43, 329, 1921, 707, 1473, 1595, 196, 7, 7, 7, 7, 7, 7, 7,
    664, 544, 297, 451, 1665, 1985, 1577, 1481, 565, 7, 7, 7, 7, 7, 7, 7,
    680, 160, 259, 441, 811, 1043, 1185, 1211, 845, 7, 7, 7, 7, 7, 7, 7,
    944, 25, 41, 315, 905, 2003, 1843, 76, 7, 7, 7, 7, 7, 7, 7, 7,
    56, 385, 161, 75, 577, 1363, 973, 7, 7, 7, 7, 7, 7, 7, 7, 7,
    40, 416, 131, 305, 545, 595, 1585, 1617, 581, 7, 7, 7, 7, 7, 7, 7,
    9, 136, 35, 427, 587, 1611, 1667, 12, 7, 7, 7, 7, 7, 7, 7, 7,
    832, 312, 185, 307, 1051, 1441, 1217, 1435, 693, 7, 7, 7, 7, 7, 7, 7,
    2, 10, 18, 26, 34, 42, 2001, 1443, 573, 7, 7, 7, 7, 7, 7, 7,
    824, 273, 51, 651, 841, 1297, 1425, 1201, 1875, 212, 7, 7, 7, 7, 7, 7,
    800, 296, 59, 1057, 705, 1809, 923, 1873, 925, 7, 7, 7, 7, 7, 7, 7,
    130, 138, 146, 154, 162, 170, 931, 1865, 837, 7, 7, 7, 7, 7, 7, 7,
    768, 552, 195, 683, 1801, 1739, 1683, 52, 7, 7, 7, 7, 7, 7, 7, 7,
    952, 336, 203, 921, 1329, 1353, 1233, 1419, 805, 7, 7, 7, 7, 7, 7, 7,
    258, 266, 274, 282, 290, 298, 1705, 1571, 653, 7, 7, 7, 7, 7, 7, 7,
    688, 144, 267, 787, 659, 1049, 697, 1793, 1345, 1747, 188, 7, 7, 7, 7, 7,
    656, 272, 771, 443, 699, 1713, 1601, 1155, 821, 7, 7, 7, 7, 7, 7, 7,
    386, 394, 402, 410, 418, 426, 1569, 1315, 549, 7, 7, 7, 7, 7, 7, 7,
    936, 424, 211, 1963, 1361, 1603, 44, 7, 7, 7, 7, 7, 7, 7, 7, 7,
    592, 528, 641, 313, 547, 1059, 1067, 1745, 789, 7, 7, 7, 7, 7, 7, 7,
    514, 522, 530, 538, 546, 554, 899, 1459, 797, 7, 7, 7, 7, 7, 7, 7,
    720, 393, 777, 467, 1417, 1689, 1619, 1803, 1795, 132, 7, 7, 7, 7, 7, 7,
    8, 769, 280, 779, 643, 209, 681, 1073, 1099, 701, 7, 7, 7, 7, 7, 7,
    770, 778, 786, 794, 802, 810, 1097, 1187, 557, 7, 7, 7, 7, 7, 7, 7,
    776, 464, 65, 321, 1025, 1937, 585, 1089, 1227, 1811, 164, 7, 7, 7, 7, 7,
    904, 137, 11, 57, 851, 971, 541, 7, 7, 7, 7, 7, 7, 7, 7, 7,
    898, 906, 914, 922, 930, 938, 915, 907, 1857, 781, 7, 7, 7, 7, 7, 7,
    1, 560, 27, 529, 803, 1289, 929, 1355, 1827, 84, 7, 7, 7, 7, 7, 7,
    72, 408, 425, 465, 337, 675, 1075, 1737, 965, 7, 7, 7, 7, 7, 7, 7,
    50, 58, 66, 74, 82, 1955, 1451, 685, 7, 7, 7, 7, 7, 7, 7, 7,
    16, 392, 801, 299, 1945, 1081, 961, 1465, 1489, 1707, 180, 7, 7, 7, 7, 7,
    712, 257, 264, 283, 563, 1923, 1553, 1483, 645, 7, 7, 7, 7, 7, 7, 7,
    306, 314, 322, 330, 338, 955, 1171, 981, 7, 7, 7, 7, 7, 7, 7, 7,
    32, 153, 281, 187, 723, 1579, 1819, 140, 7, 7, 7, 7, 7, 7, 7, 7,
    808, 152, 793, 411, 561, 1953, 713, 1467, 949, 7, 7, 7, 7, 7, 7, 7,
    562, 570, 578, 586, 594, 1939, 1339, 941, 7, 7, 7, 7, 7, 7, 7, 7,
    48, 288, 513, 537, 795, 715, 1593, 1715, 204, 7, 7, 7, 7, 7, 7, 7,
    968, 448, 331, 1035, 937, 1697, 1841, 1609, 677, 7, 7, 7, 7, 7, 7, 7,
    690, 698, 706, 714, 722, 1979, 1299, 525, 7, 7, 7, 7, 7, 7, 7, 7,
    642, 650, 658, 666, 674, 682, 1475, 1835, 4, 7, 7, 7, 7, 7, 7, 7,
    512, 200, 169, 193, 531, 579, 947, 1563, 773, 7, 7, 7, 7, 7, 7, 7,
    818, 826, 834, 842, 850, 1537, 1993, 1323, 661, 7, 7, 7, 7, 7, 7, 7,
    178, 186, 194, 202, 210, 1545, 1449, 1721, 1851, 36, 7, 7, 7, 7, 7, 7,
    704, 328, 171, 1041, 913, 1177, 1105, 1195, 853, 7, 7, 7, 7, 7, 7, 7,
    946, 954, 962, 970, 978, 1971, 1307, 933, 7, 7, 7, 7, 7, 7, 7, 7,
    434, 442, 450, 458, 466, 1931, 1337, 1833, 1731, 156, 7, 7, 7, 7, 7, 7,
};

void setup(void* const* d_in, void* d_out) {
  void* fn = nullptr;
  cudaDriverEntryPointQueryResult qr;
  cudaGetDriverEntryPoint("cuTensorMapEncodeTiled", &fn, cudaEnableDefault, &qr);
  EncodeFn enc = (EncodeFn)fn;
  void *scr, *carry, *flags;
  cudaGetSymbolAddress(&scr, g_scr);
  cudaGetSymbolAddress(&carry, g_carry);
  cudaGetSymbolAddress(&flags, g_flags);
  Params& p = g_hs.p;
  make_map(enc, &p.mapA[0], d_in[3], 64, 2048, 16, 2048, 128, 64, 64, 1);
  make_map(enc, &p.mapA[1], d_in[4], 64, 2048, 8, 1024, 128, 64, 64, 1);
  make_map(enc, &p.mapA[2], d_in[0], 64, 1024, 32, 4096, 128, 64, 64, 1);
  make_map(enc, &p.mapB[0], d_in[5], 64, 1024, 64, 8192, 128, 64, 128, 2);
  make_map(enc, &p.mapB[1], d_in[6], 64, 512, 64, 8192, 128, 64, 128, 2);
  make_map(enc, &p.mapB[2], d_in[1], 1024, 1024, 3, 6144, 2048, 64, 64, 3);
  make_map(enc, &p.mapB[3], d_in[7], 64, 512, 64, 8192, 128, 64, 128, 2);
  make_map(enc, &p.mapB[5], d_in[8], 64, 4096, 16, 2048, 128, 64, 128, 2);
  {
    cuuint64_t gd[5] = {1024, 2, 4, 4, 32}, gs[4] = {2048, 8 * 2048, 2 * 2048, 32 * 2048};
    cuuint32_t bd[5] = {64, 2, 4, 4, 4}, es[5] = {1, 1, 1, 1, 1};
    enc(&p.mapB[4], CU_TENSOR_MAP_DATA_TYPE_BFLOAT16, 5, d_in[2], gd, gs, bd, es, CU_TENSOR_MAP_INTERLEAVE_NONE, CU_TENSOR_MAP_SWIZZLE_128B,
        CU_TENSOR_MAP_L2_PROMOTION_L2_128B, CU_TENSOR_MAP_FLOAT_OOB_FILL_NONE);
  }
  make_map(enc, &p.mapO[0], d_out, 4096, 1024, 0, 8192, 0, 64, 16, 1);
  make_map(enc, &p.mapO[1], d_out, 2048, 2048, 0, 4096, 0, 64, 16, 1);
  p.scr = (uint4*)scr;
  p.carry = (uint4*)carry;
  p.flags = (uint32_t*)flags;
  p.zero = 0;
  for (int c = 0; c < NCLUSTERS; c++) {
    int rot = 0;
    for (int i = c * MAXITEMS; i < (c + 1) * MAXITEMS; i++) {
      const int kind = h_sched[i] & 7, g = (h_sched[i] >> 3) & 15;
      p.sched[i] = (uint16_t)(h_sched[i] | rot << 11);
      rot = (rot + (kind == K_T ? 1 + (g & 1) : g == 0)) % 3;
    }
  }
  cudaFuncSetAttribute(fused_kernel, cudaFuncAttributeMaxDynamicSharedMemorySize, SM_TOTAL);
  for (int i = 0; i < 9; i++) g_hs.in[i] = d_in[i];
  g_hs.out = d_out;
  g_hs.valid = true;
}

}

extern "C" void kernel_launch(void* const* d_in, const int* in_sizes, int n_in, void* d_out, int out_size) {
  (void)in_sizes;
  (void)n_in;
  (void)out_size;
  bool ok = g_hs.valid && g_hs.out == d_out;
  for (int i = 0; ok && i < 9; i++) ok = g_hs.in[i] == d_in[i];
  if (!ok) setup(d_in, d_out);
  fused_kernel<<<NCLUSTERS * 2, 512, SM_TOTAL, cudaStreamPerThread>>>(g_hs.p);
}
```

```cpp
#include <cuda_runtime.h>
#include <cuda_bf16.h>
#include <cuda.h>
#include <stdint.h>
#include <type_traits>

namespace {

typedef __nv_bfloat16 bf16;

__device__ __forceinline__ uint32_t smem_u32(const void* p) { return (uint32_t)__cvta_generic_to_shared(p); }
__device__ __forceinline__ void mbar_init(uint32_t bar, uint32_t cnt) {
  asm volatile("mbarrier.init.shared::cta.b64 [%0], %1;" ::"r"(bar), "r"(cnt) : "memory");
}
__device__ __forceinline__ void mbar_expect_tx(uint32_t bar, uint32_t bytes) {
  asm volatile("mbarrier.arrive.expect_tx.shared::cta.b64 _, [%0], %1;" ::"r"(bar), "r"(bytes) : "memory");
}
__device__ __forceinline__ void mbar_arrive_n(uint32_t bar, uint32_t n) {
  asm volatile("mbarrier.arrive.shared::cta.b64 _, [%0], %1;" ::"r"(bar), "r"(n) : "memory");
}
__device__ __forceinline__ void mbar_arrive_if0(uint32_t bar, uint32_t sel) {
  asm volatile("{\n.reg .pred p;\nsetp.eq.u32 p, %1, 0;\n@p mbarrier.arrive.shared::cta.b64 _, [%0];\n}" ::"r"(bar), "r"(sel) : "memory");
}
__device__ __forceinline__ void mbar_arrive_cta_if0(uint32_t bar, uint32_t cta, uint32_t sel) {
  asm volatile("{\n.reg .pred p;\n.reg .b32 ra;\nsetp.eq.u32 p, %2, 0;\nmapa.shared::cluster.u32 ra, %0, %1;\n"
               "@p mbarrier.arrive.shared::cluster.b64 _, [ra];\n}" ::"r"(bar),
               "r"(cta), "r"(sel)
               : "memory");
}
__device__ __forceinline__ void mbar_wait(uint32_t bar, uint32_t parity) {
  uint32_t done;
  uint32_t it = 0;
#pragma unroll 1
  while (true) {
    asm volatile("{\n.reg .pred p;\nmbarrier.try_wait.parity.shared::cta.b64 p, [%1], %2, 1000;\nselp.u32 %0, 1, 0, p;\n}"
                 : "=r"(done)
                 : "r"(bar), "r"(parity)
                 : "memory");
    if (done) break;
    if (++it > (1u << 20)) __trap();
  }
}
__device__ __forceinline__ void mbar_wait_u(uint32_t bar, uint32_t parity) {
  uint32_t it = 0;
#pragma unroll 1
  while (true) {
    uint32_t done;
    asm volatile("{\n.reg .pred p, q;\nmbarrier.try_wait.parity.shared::cta.b64 p, [%1], %2;\nvote.sync.all.pred q, p, 0xffffffff;\nselp.u32 %0, 1, 0, q;\n}"
                 : "=r"(done)
                 : "r"(bar), "r"(parity)
                 : "memory");
    if (done) break;
    if (++it > (1u << 20)) break;
  }
}
#define DECLARE_READY() asm volatile(".reg .pred RDYA, RDYB;")
__device__ __forceinline__ void test_a(uint32_t bar, uint32_t parity) {
  asm volatile("mbarrier.test_wait.parity.shared::cta.b64 RDYA, [%0], %1;" ::"r"(bar), "r"(parity) : "memory");
}
__device__ __forceinline__ void test_b(uint32_t bar, uint32_t parity) {
  asm volatile("mbarrier.test_wait.parity.shared::cta.b64 RDYB, [%0], %1;" ::"r"(bar), "r"(parity) : "memory");
}
__device__ __forceinline__ uint32_t ready_b(uint32_t dep = 0) {
  uint32_t r;
  asm volatile("{\n.reg .pred q;\nsetp.eq.and.u32 q, %1, 0, RDYB;\nvote.sync.all.pred q, q, 0xffffffff;\nselp.u32 %0, 1, 0, q;\n}" : "=r"(r) : "r"(dep) : "memory");
  return r;
}
__device__ __forceinline__ uint32_t ready_ab() {
  uint32_t r;
  asm volatile("{\n.reg .pred q;\nand.pred q, RDYA, RDYB;\nvote.sync.all.pred q, q, 0xffffffff;\nselp.u32 %0, 1, 0, q;\n}" : "=r"(r)::"memory");
  return r;
}
__device__ __forceinline__ void tma_load_3d(uint32_t dst, const CUtensorMap* m, uint32_t bar, int c0, int c1, int c2) {
  asm volatile("cp.async.bulk.tensor.3d.shared::cluster.global.mbarrier::complete_tx::bytes [%0], [%1, {%3, %4, %5}], [%2];" ::"r"(dst),
               "l"(m), "r"(bar), "r"(c0), "r"(c1), "r"(c2)
               : "memory");
}
__device__ __forceinline__ void tma_load_3d_mc(uint32_t dst, const CUtensorMap* m, uint32_t bar, int c0, int c1, int c2, uint16_t mask) {
  asm volatile(
      "cp.async.bulk.tensor.3d.shared::cluster.global.mbarrier::complete_tx::bytes.multicast::cluster [%0], [%1, {%3, %4, %5}], [%2], %6;" ::"r"(dst),
      "l"(m), "r"(bar), "r"(c0), "r"(c1), "r"(c2), "h"(mask)
      : "memory");
}
__device__ __forceinline__ void tma_load_5d(uint32_t dst, const CUtensorMap* m, uint32_t bar, int c0, int c4) {
  asm volatile("cp.async.bulk.tensor.5d.shared::cluster.global.mbarrier::complete_tx::bytes [%0], [%1, {%3, 0, 0, 0, %4}], [%2];" ::"r"(dst),
               "l"(m), "r"(bar), "r"(c0), "r"(c4)
               : "memory");
}
__device__ __forceinline__ void bulk_load(uint32_t dst, const void* src, uint32_t bytes, uint32_t bar) {
  asm volatile("cp.async.bulk.shared::cluster.global.mbarrier::complete_tx::bytes [%0], [%1], %2, [%3];" ::"r"(dst), "l"(src), "r"(bytes), "r"(bar)
               : "memory");
}
__device__ __forceinline__ void bulk_load_mc(uint32_t dst, const void* src, uint32_t bytes, uint32_t bar, uint16_t mask) {
  asm volatile("cp.async.bulk.shared::cluster.global.mbarrier::complete_tx::bytes.multicast::cluster [%0], [%1], %2, [%3], %4;" ::"r"(dst),
               "l"(src), "r"(bytes), "r"(bar), "h"(mask)
               : "memory");
}
__device__ __forceinline__ void prefetch_l2(const void* src, uint32_t bytes) {
  asm volatile("cp.async.bulk.prefetch.L2.global [%0], %1;" ::"l"(src), "r"(bytes) : "memory");
}
__device__ __forceinline__ void tma_store_2d(const CUtensorMap* m, uint32_t src, int c0, int c1) {
  asm volatile("cp.async.bulk.tensor.2d.global.shared::cta.bulk_group [%0, {%2, %3}], [%1];" ::"l"(m), "r"(src), "r"(c0), "r"(c1)
               : "memory");
}
__device__ __forceinline__ void prefetch_tmap(const CUtensorMap* m) { asm volatile("prefetch.tensormap [%0];" ::"l"(m) : "memory"); }
__device__ __forceinline__ void cluster_sync_relaxed() {
  asm volatile("barrier.cluster.arrive.relaxed.aligned;\nbarrier.cluster.wait.aligned;" ::: "memory");
}
__device__ __forceinline__ uint32_t pack_bf16(float lo, float hi) {
  uint32_t r;
  asm("cvt.rn.bf16x2.f32 %0, %1, %2;" : "=r"(r) : "f"(hi), "f"(lo));
  return r;
}
__device__ __forceinline__ float ex2(float x) {
  float y;
  asm("ex2.approx.ftz.f32 %0, %1;" : "=f"(y) : "f"(x));
  return y;
}
__device__ __forceinline__ float rcp(float x) {
  float y;
  asm("rcp.approx.ftz.f32 %0, %1;" : "=f"(y) : "f"(x));
  return y;
}
__device__ __forceinline__ void wg_fence() { asm volatile("wgmma.fence.sync.aligned;" ::: "memory"); }
__device__ __forceinline__ void wg_commit() { asm volatile("wgmma.commit_group.sync.aligned;" ::: "memory"); }
template <int N>
__device__ __forceinline__ void wg_wait() {
  asm volatile("wgmma.wait_group.sync.aligned %0;" ::"n"(N) : "memory");
}
template <int N>
__device__ __forceinline__ void fence_regs(float (&d)[N]) {
#pragma unroll
  for (int i = 0; i < N; i++) asm volatile("" : "+f"(d[i])::"memory");
}
__device__ __forceinline__ uint32_t sched_fence() {
  uint32_t t;
  asm volatile("mov.u32 %0, %%clock;" : "=r"(t)::"memory");
  return t;
}
__device__ __forceinline__ void bar_sync(int id, int n) { asm volatile("bar.sync %0, %1;" ::"r"(id), "r"(n) : "memory"); }
__device__ __forceinline__ void bar_arrive_if(bool c, int id, int n) {
  asm volatile("{\n.reg .pred p;\nsetp.ne.u32 p, %2, 0;\n@p bar.arrive %0, %1;\n}" ::"r"(id), "r"(n), "r"((uint32_t)c) : "memory");
}
__device__ __forceinline__ void bar_arrive(int id, int n) { asm volatile("bar.arrive %0, %1;" ::"r"(id), "r"(n) : "memory"); }

#define R8(a, i) "+f"(a[i]), "+f"(a[i + 1]), "+f"(a[i + 2]), "+f"(a[i + 3]), "+f"(a[i + 4]), "+f"(a[i + 5]), "+f"(a[i + 6]), "+f"(a[i + 7])
#define OP32(d, o) R8(d, o), R8(d, o + 8), R8(d, o + 16), R8(d, o + 24)
#define L32A "%0,%1,%2,%3,%4,%5,%6,%7,%8,%9,%10,%11,%12,%13,%14,%15,%16,%17,%18,%19,%20,%21,%22,%23,%24,%25,%26,%27,%28,%29,%30,%31"
#define L32B "%32,%33,%34,%35,%36,%37,%38,%39,%40,%41,%42,%43,%44,%45,%46,%47,%48,%49,%50,%51,%52,%53,%54,%55,%56,%57,%58,%59,%60,%61,%62,%63"
#define L32C "%64,%65,%66,%67,%68,%69,%70,%71,%72,%73,%74,%75,%76,%77,%78,%79,%80,%81,%82,%83,%84,%85,%86,%87,%88,%89,%90,%91,%92,%93,%94,%95"
#define WG_PRE(a, b, s, ha, hb) "{\n.reg .pred p;\n.reg .b64 da, db;\nmov.b64 da, {" a ", " ha "};\nmov.b64 db, {" b ", " hb "};\nsetp.ne.b32 p, " s ", 0;\n"

constexpr uint32_t HI128 = 0x40000040;
constexpr uint32_t HI64 = 0x80000080;
template <int TB>
__device__ __forceinline__ void wgmma_n128(float (&d)[64], uint32_t da, uint32_t ha, uint32_t db, uint32_t hb, int scale_d) {
  asm volatile(WG_PRE("%64", "%65", "%66", "%67", "%68") "wgmma.mma_async.sync.aligned.m64n128k16.f32.bf16.bf16 {" L32A "," L32B "}, da, db, p, 1, 1, 0, %69;\n}\n"
               : OP32(d, 0), OP32(d, 32)
               : "r"(da), "r"(db), "r"(scale_d), "r"(ha), "r"(hb), "n"(TB));
}
__device__ __forceinline__ void wgmma_n192_tb(float (&d)[96], uint32_t da, uint32_t db, int scale_d) {
  asm volatile(WG_PRE("%96", "%97", "%98", "%99", "%99") "wgmma.mma_async.sync.aligned.m64n192k16.f32.bf16.bf16 {" L32A "," L32B "," L32C "}, da, db, p, 1, 1, 0, 1;\n}\n"
               : OP32(d, 0), OP32(d, 32), OP32(d, 64)
               : "r"(da), "r"(db), "r"(scale_d), "r"(HI128));
}
__device__ __forceinline__ void wgmma_n64(float (&d)[64], uint32_t da, uint32_t db, int scale_d) {
  asm volatile(WG_PRE("%32", "%33", "%34", "%35", "%35") "wgmma.mma_async.sync.aligned.m64n64k16.f32.bf16.bf16 {" L32A "}, da, db, p, 1, 1, 0, 0;\n}\n"
               : OP32(d, 0)
               : "r"(da), "r"(db), "r"(scale_d), "r"(HI64));
}
__device__ __forceinline__ void wgmma_n128_rs_tb(float (&d)[64], uint32_t a0, uint32_t a1, uint32_t a2, uint32_t a3, uint32_t db, int scale_d) {
  asm volatile("{\n.reg .pred p;\n.reg .b64 db;\nmov.b64 db, {%68, %70};\nsetp.ne.b32 p, %69, 0;\n"
               "wgmma.mma_async.sync.aligned.m64n128k16.f32.bf16.bf16 {" L32A "," L32B "}, {%64,%65,%66,%67}, db, p, 1, 1, 1;\n}\n"
               : OP32(d, 0), OP32(d, 32)
               : "r"(a0), "r"(a1), "r"(a2), "r"(a3), "r"(db), "r"(scale_d), "r"(HI64));
}
__device__ __forceinline__ void mma_16816(float (&c)[4], uint32_t a0, uint32_t a1, uint32_t a2, uint32_t a3, uint32_t b0, uint32_t b1) {
  asm volatile("mma.sync.aligned.m16n8k16.row.col.f32.bf16.bf16.f32 {%0,%1,%2,%3}, {%4,%5,%6,%7}, {%8,%9}, {%0,%1,%2,%3};"
               : "+f"(c[0]), "+f"(c[1]), "+f"(c[2]), "+f"(c[3])
               : "r"(a0), "r"(a1), "r"(a2), "r"(a3), "r"(b0), "r"(b1));
}
__device__ __forceinline__ uint32_t movm_t(uint32_t x) {
  uint32_t y;
  asm volatile("movmatrix.sync.aligned.m8n8.trans.b16 %0, %1;" : "=r"(y) : "r"(x));
  return y;
}
__device__ __forceinline__ void sts128(uint32_t a, uint32_t x, uint32_t y, uint32_t z, uint32_t w) {
  asm volatile("st.shared.v4.u32 [%0], {%1,%2,%3,%4};" ::"r"(a), "r"(x), "r"(y), "r"(z), "r"(w) : "memory");
}
__device__ __forceinline__ void stsm4(uint32_t a, uint32_t x, uint32_t y, uint32_t z, uint32_t w) {
  asm volatile("stmatrix.sync.aligned.m8n8.x4.shared.b16 [%0], {%1,%2,%3,%4};" ::"r"(a), "r"(x), "r"(y), "r"(z), "r"(w) : "memory");
}
__device__ __forceinline__ void ldsm4_t(uint32_t a, uint32_t (&r)[4]) {
  asm volatile("ldmatrix.sync.aligned.m8n8.x4.trans.shared.b16 {%0,%1,%2,%3}, [%4];"
               : "=r"(r[0]), "=r"(r[1]), "=r"(r[2]), "=r"(r[3])
               : "r"(a)
               : "memory");
}
__device__ __forceinline__ void stg128_if0(uint4* a, uint32_t x, uint32_t y, uint32_t z, uint32_t w, uint32_t sel) {
  asm volatile("{\n.reg .pred p;\nsetp.eq.u32 p, %5, 0;\n@p st.global.v4.u32 [%0], {%1,%2,%3,%4};\n}" ::"l"(a), "r"(x), "r"(y), "r"(z), "r"(w),
               "r"(sel)
               : "memory");
}
__device__ __forceinline__ void lds128(uint32_t a, uint32_t& x, uint32_t& y, uint32_t& z, uint32_t& w) {
  asm volatile("ld.shared.v4.u32 {%0,%1,%2,%3}, [%4];" : "=r"(x), "=r"(y), "=r"(z), "=r"(w) : "r"(a) : "memory");
}

#define KVR 16
constexpr int PLANE = 2048 * 16;
constexpr int PL_Q = 0, PL_KV = 32, PL_OA = PL_KV + 4 * KVR, NPLANES = PL_OA + 8;
__device__ __align__(1024) uint4 g_scr[NPLANES * PLANE];
__device__ uint4 g_carry[16 * 128];
constexpr int F_Q = 0, F_CTX = 256, F_KV = 768, F_TD = 1280, F_L = 1296, F_CAR = 1312, F_EPOCH = 1328, F_END = 1328 + 132;
__device__ uint32_t g_flags[F_END];

#define NTURN 256

enum { K_Q = 0, K_KV = 1, K_L = 2, K_T = 3, K_OA = 4, K_OB = 5, K_END = 7 };
constexpr int NCLUSTERS = 66, MAXITEMS = 16;
constexpr int A_STAGE = 16384, B_SLOT = 32768;
constexpr int SM_B = 6 * A_STAGE, SM_CARRY = SM_B + 4 * B_SLOT, SM_BAR = SM_CARRY + 2048, SM_TOTAL = SM_BAR + 512;

struct Params {
  CUtensorMap mapA[3];
  CUtensorMap mapB[6];
  CUtensorMap mapO[2];
  uint4* scr;
  uint4* carry;
  uint32_t* flags;
  uint32_t zero;
  uint16_t sched[NCLUSTERS * MAXITEMS];
};

__device__ __forceinline__ bool item_narrow(uint32_t item) { return (item & 0x204) == 0x204; }
__device__ __forceinline__ int item_nk(uint32_t item) {
  const uint32_t kind = item & 7;
  return (kind == K_KV ? 8 : kind == K_OB ? 64 : 16) >> item_narrow(item);
}
__device__ __forceinline__ int item_row(uint32_t kind, int g, int pos) {
  if (kind == K_L || kind == K_OA) return g == 0 ? (pos - 1) * 1024 : 64 * (3 * g - 2 + pos + (g > 5));
  return 64 * (3 * g - 1 + pos);
}

__device__ __forceinline__ void wait_flag(const uint32_t* f, uint32_t target) {
  uint32_t it = 0;
#pragma unroll 1
  while (true) {
    uint32_t v;
    asm volatile("ld.acquire.gpu.global.u32 %0, [%1];" : "=r"(v) : "l"(f) : "memory");
    if ((int)(v - target) >= 0) break;
    __nanosleep(40);
    if (++it > (1u << 18)) break;
  }
  asm volatile("fence.proxy.async.global;" ::: "memory");
}
__device__ __forceinline__ uint32_t wait_bits(const uint32_t* f, uint32_t inv, uint32_t mask) {
  uint32_t it = 0, v;
#pragma unroll 1
  while (true) {
    asm volatile("ld.acquire.gpu.global.u32 %0, [%1];" : "=r"(v) : "l"(f) : "memory");
    v ^= inv;
    if (!(~v & mask)) break;
    __nanosleep(40);
    if (++it > (1u << 18)) break;
  }
  asm volatile("fence.proxy.async.global;" ::: "memory");
  return v;
}
__device__ __forceinline__ void red_add(uint32_t* f) { asm volatile("red.relaxed.gpu.global.add.u32 [%0], 1;" ::"l"(f) : "memory"); }
__device__ __forceinline__ void red_xor(uint32_t* f, uint32_t v) {
  asm volatile("red.relaxed.gpu.global.xor.b32 [%0], %1;" ::"l"(f), "r"(v) : "memory");
}

__device__ __noinline__ void attn_fallback(uint4* q, const uint4* __restrict__ k, int row0, int lane) {
  const int g = lane >> 2, tq = lane & 3;
  q += row0 * 16;
  k += lane ^ (lane >> 3);
  const uint4* v = k + 2 * PLANE;
  float o[16][4];
#pragma unroll
  for (int i = 0; i < 16; i++) o[i][0] = o[i][1] = o[i][2] = o[i][3] = 0.f;
  float m0 = -INFINITY, m1 = -INFINITY, l0 = 0.f, l1 = 0.f;
#pragma unroll 1
  for (int k0 = 0; k0 < row0 + 16; k0 += 16) {
    float sc[2][4] = {{0.f, 0.f, 0.f, 0.f}, {0.f, 0.f, 0.f, 0.f}};
#pragma unroll 1
    for (int cg = 0; cg < 4; cg++) {
      const uint4 qa = __ldcg(q + cg * 32 + (lane ^ (lane >> 3)));
      const uint4 qb = __ldcg(q + 128 + cg * 32 + (lane ^ (lane >> 3)));
#pragma unroll
      for (int t = 0; t < 2; t++) {
        const uint4 kk = __ldcg(k + (k0 + 8 * t) * 16 + cg * 32);
        mma_16816(sc[t], qa.x, qb.x, qa.y, qb.y, kk.x, kk.y);
        mma_16816(sc[t], qa.z, qb.z, qa.w, qb.w, kk.z, kk.w);
      }
    }
    float x0 = -INFINITY, x1 = -INFINITY;
#pragma unroll
    for (int t = 0; t < 2; t++) {
#pragma unroll
      for (int e = 0; e < 2; e++) {
        const int key = k0 + 8 * t + 2 * tq + e;
        if (key > row0 + g) sc[t][e] = -INFINITY;
        if (key > row0 + g + 8) sc[t][2 + e] = -INFINITY;
        x0 = fmaxf(x0, sc[t][e]);
        x1 = fmaxf(x1, sc[t][2 + e]);
      }
    }
    x0 = fmaxf(x0, __shfl_xor_sync(0xffffffffu, x0, 1));
    x1 = fmaxf(x1, __shfl_xor_sync(0xffffffffu, x1, 1));
    x0 = fmaxf(x0, __shfl_xor_sync(0xffffffffu, x0, 2));
    x1 = fmaxf(x1, __shfl_xor_sync(0xffffffffu, x1, 2));
    const float n0 = fmaxf(m0, x0), n1 = fmaxf(m1, x1);
    const float a0 = ex2(m0 - n0), a1 = ex2(m1 - n1);
    m0 = n0;
    m1 = n1;
    l0 *= a0;
    l1 *= a1;
    uint32_t pa[4];
#pragma unroll
    for (int t = 0; t < 2; t++) {
      const float e0 = ex2(sc[t][0] - m0), e1 = ex2(sc[t][1] - m0);
      const float e2 = ex2(sc[t][2] - m1), e3 = ex2(sc[t][3] - m1);
      l0 += e0 + e1;
      l1 += e2 + e3;
      pa[2 * t] = pack_bf16(e0, e1);
      pa[2 * t + 1] = pack_bf16(e2, e3);
    }
#pragma unroll
    for (int cg = 0; cg < 4; cg++) {
      const uint4 va = __ldcg(v + k0 * 16 + cg * 32);
      const uint4 vb = __ldcg(v + k0 * 16 + 128 + cg * 32);
#pragma unroll
      for (int r = 0; r < 4; r++) {
        const uint32_t w0 = r == 0 ? va.x : r == 1 ? va.y : r == 2 ? va.z : va.w;
        const uint32_t w1 = r == 0 ? vb.x : r == 1 ? vb.y : r == 2 ? vb.z : vb.w;
        float(&oo)[4] = o[4 * cg + r];
        oo[0] *= a0;
        oo[1] *= a0;
        oo[2] *= a1;
        oo[3] *= a1;
        mma_16816(oo, pa[0], pa[1], pa[2], pa[3], movm_t(w0), movm_t(w1));
      }
    }
  }
  l0 += __shfl_xor_sync(0xffffffffu, l0, 1);
  l1 += __shfl_xor_sync(0xffffffffu, l1, 1);
  l0 += __shfl_xor_sync(0xffffffffu, l0, 2);
  l1 += __shfl_xor_sync(0xffffffffu, l1, 2);
  const float i0 = 1.f / l0, i1 = 1.f / l1;
  __syncwarp();
  uint32_t* o0 = reinterpret_cast<uint32_t*>(q + g * 4) + tq;
#pragma unroll
  for (int i = 0; i < 16; i++) {
    uint32_t* d = o0 + (i >> 2) * 128 + ((i & 3) ^ (g >> 1)) * 4;
    d[0] = pack_bf16(o[i][0] * i0, o[i][1] * i0);
    d[512] = pack_bf16(o[i][2] * i1, o[i][3] * i1);
  }
}

#define KB_LIMIT 1.2089258e24f
#define KB_LOW 9.094947e-13f

__device__ __forceinline__ void local_scores(float (&s)[2][4], const uint32_t (&lo)[24], const uint32_t (&hi)[24], const uint32_t* k) {
#pragma unroll
  for (int h = 0; h < 2; h++) s[h][0] = s[h][1] = s[h][2] = s[h][3] = 0.f;
#pragma unroll
  for (int c = 0; c < 4; c += 2)
#pragma unroll
    for (int h = 0; h < 8; h += 4) mma_16816(s[h >> 2], lo[h + c], hi[h + c], lo[h + c + 1], hi[h + c + 1], k[h + c], k[h + c + 1]);
}
__device__ __forceinline__ void local_attn(float (&o)[2][4][4], float (&l)[2][4], const float (&s)[3][2][4], const uint32_t (&vt)[2][4][4],
                                           bool first, int lane) {
  const int g = lane >> 2, tq = lane & 3;
  const bool h0 = 2 * tq > g, h1 = 2 * tq + 1 > g;
  const uint32_t m = (h0 ? 0xFFFFu : 0u) | (h1 ? 0xFFFF0000u : 0u);
  float u0[2], u1[2], w0[2], w1[2], mu[2], mw[2];
#pragma unroll
  for (int h = 0; h < 2; h++) {
    u0[h] = h0 ? s[0][h][0] : s[1][h][0];
    u1[h] = h1 ? s[0][h][1] : s[1][h][1];
    w0[h] = h0 ? s[1][h][2] : s[2][h][2];
    w1[h] = h1 ? s[1][h][3] : s[2][h][3];
    if (first) {
      if (h0) u0[h] = -INFINITY;
      if (h1) u1[h] = -INFINITY;
    }
    mu[h] = fmaxf(u0[h], u1[h]);
    mw[h] = fmaxf(w0[h], w1[h]);
  }
#pragma unroll
  for (int o = 1; o <= 2; o++)
#pragma unroll
    for (int h = 0; h < 2; h++) {
      mw[h] = fmaxf(mw[h], __shfl_xor_sync(0xffffffffu, mw[h], o));
      mu[h] = fmaxf(mu[h], __shfl_xor_sync(0xffffffffu, mu[h], o));
    }
  const float c = 0.17677669529663687f * 1.4426950408889634f;
#pragma unroll
  for (int h = 0; h < 2; h++) {
    const uint32_t pu = pack_bf16(ex2((u0[h] - mu[h]) * c), ex2((u1[h] - mu[h]) * c));
    const uint32_t pw = pack_bf16(ex2((w0[h] - mw[h]) * c), ex2((w1[h] - mw[h]) * c));
    l[h][0] = l[h][1] = l[h][2] = l[h][3] = 0.f;
    mma_16816(l[h], 0x3F803F80, 0u, 0u, 0x3F803F80, pu, pw);
#pragma unroll
    for (int i = 0; i < 4; i++) {
      const uint32_t(&v)[4] = vt[i >> 1][2 * h + (i & 1)];
      o[h][i][0] = o[h][i][1] = o[h][i][2] = o[h][i][3] = 0.f;
      mma_16816(o[h][i], v[0], v[1], v[2], v[3], i < 2 ? pu & m : pw & ~m, i < 2 ? pu & ~m : pw & m);
    }
  }
}

__global__ __cluster_dims__(2, 1, 1) __launch_bounds__(512, 1) void fused_kernel(const __grid_constant__ Params p) {
  extern __shared__ __align__(1024) uint8_t smem_dyn[];
  DECLARE_READY();
  const uint32_t sbase = smem_u32(smem_dyn);
  const uint32_t afull0 = sbase + SM_BAR, aempty0 = afull0 + 48, bfull0 = afull0 + 96, bempty0 = afull0 + 128, carbar = afull0 + 160,
                 pub0 = afull0 + 200;
  const uint32_t bbase = sbase + SM_B;
  const int wg = __reduce_min_sync(0xffffffffu, (int)(threadIdx.x >> 7));
  const uint32_t rank = blockIdx.x & 1;
  const uint16_t* sched = p.sched + (blockIdx.x >> 1) * MAXITEMS;

  auto fill_b = [&](uint32_t item, int t, uint32_t pb) {
    const uint32_t kind = item & 7, j = (item >> 7) & 15, sl = pb & 3;
    if (((item >> 3) & 15) == 0) mbar_arrive_n(bempty0 + 8 * sl, 1);
    mbar_expect_tx(bfull0 + 8 * sl, kind == K_L ? 24576 : 32768);
    const uint32_t nt = kind == K_KV ? j : 2 * j + rank, dst = bbase + sl * B_SLOT;
    const uint32_t cb = item_narrow(item) ? nt - 8 : nt * 2 + (t & 1), ks = item_narrow(item) ? t : t >> 1;
    if (kind == K_OA) {
      tma_load_5d(dst, &p.mapB[K_OA], bfull0 + 8 * sl, cb * 128, ks * 4);
      tma_load_5d(dst + 16384, &p.mapB[K_OA], bfull0 + 8 * sl, cb * 128 + 64, ks * 4);
    } else if (kind == K_L) {
      tma_load_3d(dst, &p.mapB[K_L], bfull0 + 8 * sl, nt * 64, t * 64, 0);
    } else {
      tma_load_3d(dst, &p.mapB[kind == K_KV ? 1 + 2 * rank : kind], bfull0 + 8 * sl, 0, ks * 128, cb * 2);
    }
  };
  auto fill_a = [&](uint32_t item, int d, int pos, uint32_t u, bool mc) {
    const uint32_t kind = item & 7;
    const int row = item_row(kind, (item >> 3) & 15, pos);
    const uint32_t dst = sbase + u * A_STAGE, bar = afull0 + 8 * u;
    mbar_expect_tx(bar, A_STAGE);
    if (kind >= K_OA) {
      bulk_load_mc(dst + rank * 8192, p.scr + ((kind == K_OA ? PL_OA : PL_Q) + d) * PLANE + row * 16 + rank * 512, 8192, bar, (uint16_t)3);
    } else {
      const int blk = 2 * d + (kind == K_L ? (row >> 10) * 16 : 0), r = kind == K_L ? row & 1023 : row;
      if (mc) {
        tma_load_3d_mc(dst + rank * 8192, &p.mapA[kind], bar, 0, r, blk + rank, (uint16_t)3);
      } else {
        tma_load_3d(dst, &p.mapA[kind], bar, 0, r, blk);
        tma_load_3d(dst + 8192, &p.mapA[kind], bar, 0, r, blk + 1);
      }
    }
  };
  if (threadIdx.x == 0) {
    for (int i = 0; i < 4; i++) {
      mbar_init(bfull0 + 8 * i, 1);
      mbar_init(bempty0 + 8 * i, 3);
    }
    asm volatile("fence.proxy.async.shared::cta;" ::: "memory");
    for (int t = 0; t < 4; t++) fill_b(sched[0], t, t);
  } else if (threadIdx.x == 32) {
    for (int i = 0; i < 6; i++) {
      mbar_init(afull0 + 8 * i, 1);
      mbar_init(aempty0 + 8 * i, 2);
    }
    asm volatile("fence.proxy.async.shared::cta;" ::: "memory");
    const int g0 = ((sched[0] >> 3) & 15) == 0;
    for (int w = 0; w + g0 < 3; w++) fill_a(sched[0], 0, w + g0, 2 * w, false);
    asm volatile("fence.mbarrier_init.release.cluster;" ::: "memory");
  } else if (threadIdx.x == 64) {
    for (int i = 0; i < 5; i++) mbar_init(carbar + 8 * i, 1);
    for (int i = 0; i < MAXITEMS; i++) mbar_init(pub0 + 8 * i, 12);
  }
  __syncthreads();
  cluster_sync_relaxed();

  if (wg == 0) {
    asm volatile("setmaxnreg.dec.sync.aligned.u32 32;");
    if (threadIdx.x == 0) {
      const uint32_t e = __ldcg(p.flags + F_EPOCH + blockIdx.x) + 1;
      uint32_t pb = 4;
      for (int it = 0; it < MAXITEMS; it++) {
        const uint32_t item = sched[it];
        const uint32_t kind = item & 7;
        if (kind == K_END) break;
        if (kind != K_T) {
          const int nk = item_nk(item);
          uint32_t heads = 0;
          for (int t = it == 0 ? 4 : 0; t < nk; t++, pb++) {
            mbar_wait(bempty0 + 8 * (pb & 3), ((pb >> 2) & 1) ^ 1);
            fill_b(item, t, pb);
            if (item_narrow(item) && kind == K_OB) {
              const uint32_t g = (item >> 3) & 15, nb = g ? 3 : 2;
              if (!(heads >> t & 2)) heads = wait_bits(p.flags + F_CTX + g * 32, (e & 1) - 1, 0);
              if (heads >> t & 2) prefetch_l2(p.scr + (PL_Q + t + 1) * PLANE + (3 * g + 2 - nb) * 1024 + rank * nb * 512, nb * 8192);
            }
          }
        } else {
          const int g = (item >> 3) & 15, j = (item >> 7) & 15;
          const uint4* src = p.scr + (PL_KV + (j % KVR) * 4 + rank) * PLANE;
          const int n = ((3 * g + 1) >> 1) + 1;
          uint32_t groups = 0;
          for (int t = 0; t < n; t++, src += 2048) {
            const uint32_t need = (4u << 2 * min((2 * t + 2) / 3, g)) - 1;
            if (~groups & need) groups = wait_bits(p.flags + F_KV + j * 32, (e & 1) - 1, need);
            const uint32_t nskip = t == n - 1 ? 1 + (g & 1) : 0;
            uint32_t sl = pb & 3;
            mbar_wait(bempty0 + 8 * sl, ((pb >> 2) & 1) ^ 1);
            if (nskip) mbar_arrive_n(bempty0 + 8 * sl, nskip);
            mbar_expect_tx(bfull0 + 8 * sl, 32768);
            pb++;
            if (nskip == 2) {
              bulk_load(bbase + sl * B_SLOT, src, 16384, bfull0 + 8 * sl);
              bulk_load(bbase + sl * B_SLOT + 16384, src + 2 * PLANE, 16384, bfull0 + 8 * sl);
              continue;
            }
            bulk_load(bbase + sl * B_SLOT, src, 32768, bfull0 + 8 * sl);
            sl = pb & 3;
            mbar_wait(bempty0 + 8 * sl, ((pb >> 2) & 1) ^ 1);
            if (nskip) mbar_arrive_n(bempty0 + 8 * sl, nskip);
            mbar_expect_tx(bfull0 + 8 * sl, 32768);
            bulk_load(bbase + sl * B_SLOT, src + 2 * PLANE, 32768, bfull0 + 8 * sl);
            pb++;
          }
        }
      }
    } else if (threadIdx.x == 32) {
      const uint32_t e = __ldcg(p.flags + F_EPOCH + blockIdx.x) + 1;
      uint32_t pk = ((sched[0] >> 3) & 15) == 0 ? 0x0101 : 0x010101;
      auto next_stage = [&](uint32_t w) {
        const uint32_t n = pk >> (8 * w), u = 2 * w + (n & 1);
        mbar_wait(aempty0 + 8 * u, ((n >> 1) & 1) ^ 1);
        pk += 1u << (8 * w);
        return u;
      };
      for (int it = 0; it < MAXITEMS; it++) {
        const uint32_t item = sched[it];
        const uint32_t kind = item & 7;
        if (kind == K_END) break;
        const int g = (item >> 3) & 15, j = (item >> 7) & 15;
        const int nd = kind == K_T ? 1 : item_nk(kind) >> 1;
        if (kind == K_KV && j >= KVR) wait_flag(p.flags + F_TD + j - KVR, 22 * e);
        if (kind == K_OA) wait_flag(p.flags + F_L + g, 16 * e);
        if (kind == K_T) wait_flag(p.flags + F_Q + j * 16 + g, e);
        uint32_t heads = 0;
        for (int d = it == 0; d < nd; d++) {
          if (kind == K_OB && !(heads >> d & 1)) heads = wait_bits(p.flags + F_CTX + g * 32, (e & 1) - 1, 1u << d);
          for (int rho = 0; rho < 3 - (g == 0); rho++) {
            uint32_t w = rho + 3 - (item >> 11);
            if (w >= 3) w -= 3;
            const uint32_t u = next_stage(w);
            if (kind == K_T) {
              mbar_expect_tx(afull0 + 8 * u, A_STAGE);
              bulk_load(sbase + u * A_STAGE, p.scr + (PL_Q + 2 * j + rank) * PLANE + (3 * g + 1 - rho) * 1024, A_STAGE, afull0 + 8 * u);
            } else {
              fill_a(item, d, rho + (g == 0), u, true);
            }
          }
        }
      }
      for (int i = 0; i < 6; i++) next_stage(i >> 1);
    } else if (threadIdx.x == 64) {
      const uint32_t pair = 2 * ((sched[0] >> 7) & 15) + rank;
      if ((sched[0] & 127) == K_L) {
        mbar_wait(carbar + 24, 0);
        asm volatile("fence.proxy.async.shared::cta;\ncp.async.bulk.global.shared::cta.bulk_group [%0], [%1], 2048;\n"
                     "cp.async.bulk.commit_group;\ncp.async.bulk.wait_group 0;\nfence.proxy.async.global;\nfence.acq_rel.gpu;" ::"l"(p.carry + pair * 128),
                     "r"(sbase + SM_CARRY - 2048)
                     : "memory");
        red_add(p.flags + F_CAR + pair);
      }
      if ((sched[0] & 127) == (K_L | 6 << 3)) {
        wait_flag(p.flags + F_CAR + pair, __ldcg(p.flags + F_EPOCH + blockIdx.x) + 1);
        mbar_expect_tx(carbar + 32, 2048);
        bulk_load(sbase + SM_CARRY, p.carry + pair * 128, 2048, carbar + 32);
      }
      for (int it = 0; it < MAXITEMS; it++) {
        const uint32_t item = sched[it];
        const uint32_t kind = item & 7;
        const int g = (item >> 3) & 15, j = (item >> 7) & 15;
        mbar_wait(pub0 + 8 * (kind == K_END ? MAXITEMS - 1 : it), 0);
        if (kind == K_END) break;
        if (kind >= K_OA) continue;
        asm volatile("fence.acq_rel.gpu;" ::: "memory");
        if (kind == K_Q) red_add(p.flags + F_Q + (2 * j + rank) * 16 + g);
        if (kind == K_KV) red_xor(p.flags + F_KV + j * 32, 1u << (2 * g + rank));
        if (kind == K_L) red_add(p.flags + F_L + g);
        if (kind == K_T) {
          red_xor(p.flags + F_CTX + g * 32, 1u << (2 * j + rank));
          red_add(p.flags + F_TD + j);
        }
      }
      red_add(p.flags + F_EPOCH + blockIdx.x);
    } else if (threadIdx.x == 96) {
      for (int i = 0; i < 3; i++) prefetch_tmap(&p.mapA[i]);
      for (int i = 0; i < 6; i++) prefetch_tmap(&p.mapB[i]);
      prefetch_tmap(&p.mapO[0]);
      prefetch_tmap(&p.mapO[1]);
    }
  } else {
    asm volatile("setmaxnreg.inc.sync.aligned.u32 160;");
    const int cw = wg - 1;
    const int wq = __reduce_min_sync(0xffffffffu, (int)((threadIdx.x >> 5) & 3));
    auto turn = [&](uint32_t dep = 0) {
      bar_sync((1 + cw) | dep, NTURN);
    };
    const int fwd = cw == 0 ? 3 : cw, back = cw == 2 ? 1 : cw + 2;
    int next = fwd;
    auto pass = [&]() {
      bar_arrive(next, NTURN);
      next = fwd;
    };
    auto rank_of = [&](uint32_t item) {
      const int r = cw + (item >> 11);
      return r >= 3 ? r - 3 : r;
    };
    if (cw == 1) pass();
    if (cw == 2) { turn(); pass(); }
    const uint32_t abase = sbase + cw * (2 * A_STAGE), afull = afull0 + 16 * cw, aempty = aempty0 + 16 * cw;
    const uint32_t adesc = ((abase & 0x3FFFF) >> 4) | (1u << 16), bdesc = (bbase & 0x3FFFF) >> 4;
    uint32_t pa = 0, pb = 0;
    int it = 0;
    uint32_t item = sched[0];
    auto publish = [&](int i, uint32_t skip = 0) {
      __syncwarp();
      mbar_arrive_if0(pub0 + 8 * i, (threadIdx.x & 31) | skip);
    };
    auto test_ab = [&](uint32_t a, uint32_t b) {
      test_a(afull + 8 * (a & 1), (a >> 1) & 1);
      test_b(bfull0 + 8 * (b & 3), (b >> 2) & 1);
    };
    auto wait_ab = [&]() {
      if (!ready_ab()) {
        mbar_wait_u(afull + 8 * (pa & 1), (pa >> 1) & 1);
        mbar_wait_u(bfull0 + 8 * (pb & 3), (pb >> 2) & 1);
      }
    };
    auto release_ab = [&](uint32_t a, uint32_t b, uint32_t skip) {
      mbar_arrive_cta_if0(wq < 2 ? aempty + 8 * (a & 1) : bempty0 + 8 * (b & 3), wq < 2 ? wq : rank, (threadIdx.x & 31) | (wq == 3) | skip);
    };
    test_ab(0, 0);
    auto gturn = [&](auto second_c, bool hold, auto mma, auto meanwhile, uint32_t dep = 0) {
      constexpr bool SECOND = decltype(second_c)::value != 0;
      const uint32_t da = adesc + (pa & 1) * (A_STAGE >> 4), db = bdesc + (pb & 3) * (B_SLOT >> 4);
      if (decltype(second_c)::value != 1) wait_ab();
      else if (!ready_b()) mbar_wait_u(bfull0 + 8 * (pb & 3), (pb >> 2) & 1);
      turn(dep);
      wg_fence();
      mma(da, db);
      wg_commit();
      if (!hold) pass();
      if (hold) {
      } else if (SECOND) test_ab(pa + 1, pb + 1);
      else test_b(bfull0 + 8 * ((pb + 1) & 3), ((pb + 1) >> 2) & 1);
      meanwhile();
      wg_wait<0>();
      if (SECOND) {
        if (!hold) release_ab(pa, pb, 0);
        pa++;
      } else {
        mbar_arrive_if0(bempty0 + 8 * (pb & 3), threadIdx.x & 127);
      }
      __syncwarp();
      pb++;
    };
    constexpr std::true_type YES{};
    constexpr std::false_type NO{};
    constexpr std::integral_constant<int, 2> ONCE{};
    auto nothing = []() {};
    auto idle = [&]() { return ((item >> 3) & 15) == 0 && rank_of(item) == 2; };
    auto skip_item = [&]() {
      const int n = (item & 7) == K_T ? 2 : item_nk(item);
      publish(it);
#pragma unroll 1
      for (int i = 2; i < n; i++) {
        turn();
        pass();
      }
      pb += n;
      test_ab(pa, pb);
      item = sched[++it];
    };

    if ((item & 7) == K_L && idle()) skip_item();
    float lo_[2][4][4] = {}, ll[2][4] = {};
    uint4* ldst = p.scr;
    uint32_t lnone = 1;
    auto lrelease = [&]() { release_ab(1, 3, lnone); };
    auto lflush = [&]() {
      const uint32_t t = sched_fence() & p.zero;
#pragma unroll
      for (int i = 0; i < 4; i++) {
        const int h = i >> 1, e = i & 1 ? 2 : 0;
        const float f0 = rcp(__uint_as_float(__float_as_uint(ll[h][e]) | t)), f1 = rcp(__uint_as_float(__float_as_uint(ll[h][e + 1]) | t));
        const float(&r0)[4] = lo_[h][e], (&r1)[4] = lo_[h][e + 1];
        stg128_if0(ldst + h * 32 + e * 64, movm_t(pack_bf16(r0[0] * f0, r0[1] * f1)), movm_t(pack_bf16(r0[2] * f0, r0[3] * f1)),
                   movm_t(pack_bf16(r1[0] * f0, r1[1] * f1)), movm_t(pack_bf16(r1[2] * f0, r1[3] * f1)), lnone);
      }
      publish(it - 1, lnone);
    };
    while ((item & 7) == K_L) {
      const int g = (item >> 3) & 15, j = (item >> 7) & 15;
      const int rho = rank_of(item);
      float acc[96];
      auto mma = [&](int kb, bool first) {
        return [&acc, kb, first](uint32_t da, uint32_t db) {
#pragma unroll
          for (int k = 0; k < 4; k++) wgmma_n192_tb(acc, da + kb * 512 + k * 2, (db | (512u << 16)) + k * 128, !(first && k == 0));
        };
      };
      gturn(NO, false, mma(0, true), lrelease);
      gturn(YES, false, mma(1, false), lflush);
#pragma unroll 1
      for (int d = 7;;) {
        gturn(NO, false, mma(0, false), nothing);
        if (--d == 0) break;
        gturn(YES, false, mma(1, false), nothing);
      }
      const int lane = threadIdx.x & 31;
      const int from = rho ? rho : 4 * (~g & 1), to = g == 0 ? 3 * rho : rho == 2 ? 4 * (g & 1) : rho + 1;
      uint32_t own, front, vlo;
      gturn(YES, true, mma(1, false), [&]() {
        bar_arrive_if(rho != 2, g && rho ? back : next, NTURN);
        own = (wq < 3 ? abase + A_STAGE + wq * 2048 : sbase + SM_CARRY - 8192 + to * 2048) + lane * 16;
        front = (wq > 0 ? abase + A_STAGE + wq * 2048 - 2048 : g == 0 ? abase + A_STAGE : sbase + SM_CARRY - 8192 + from * 2048) + lane * 16;
        vlo = abase + A_STAGE + 8192 + wq * 1024 + lane * 16;
        ldst = p.scr + (PL_OA + j) * PLANE + (item_row(K_L, g, rho + (g == 0)) + wq * 16) * 16 + rank * 64 + (lane ^ (lane >> 3));
        asm volatile("" : "+r"(own), "+r"(front), "+r"(vlo), "+l"(ldst));
        lnone = 0;
        item = sched[++it];
        if (wq == 0 && g != 0) mbar_wait_u(carbar + 8 * from, ((g - (g <= 5 ? 1 : 6)) >> (rho == 0)) & 1);
      });
      if (g && rho == 0) next = back;
      fence_regs(acc);
      uint32_t lo[24], hi[24], hk[8], vt[2][4][4];
#pragma unroll
      for (int i = 0; i < 24; i++) {
        lo[i] = pack_bf16(acc[4 * i], acc[4 * i + 1]);
        hi[i] = pack_bf16(acc[4 * i + 2], acc[4 * i + 3]);
      }
      sts128(own, hi[8], hi[9], hi[10], hi[11]);
      sts128(own + 512, hi[12], hi[13], hi[14], hi[15]);
      stsm4(own + 1024, hi[16], hi[17], hi[18], hi[19]);
      stsm4(own + 1536, hi[20], hi[21], hi[22], hi[23]);
      __syncwarp();
      mbar_arrive_if0(carbar + 8 * to, lane | (wq ^ 3));
      stsm4(vlo, lo[16], lo[17], lo[18], lo[19]);
      stsm4(vlo + 512, lo[20], lo[21], lo[22], lo[23]);
      bar_sync(4 + cw, 128);
      lds128(front, hk[0], hk[1], hk[2], hk[3]);
      lds128(front + 512, hk[4], hk[5], hk[6], hk[7]);
#pragma unroll
      for (int i = 0; i < 8; i++) ldsm4_t((lane < 16 ? (i < 4 ? front : own) + 1024 : vlo - 256) + (i & 3) * 256, vt[i >> 2][i & 3]);
      float sc[3][2][4];
      local_scores(sc[2], lo, hi, hi + 8);
      local_scores(sc[1], lo, hi, lo + 8);
      local_scores(sc[0], lo, hi, hk);
      test_ab(pa, pb);
      local_attn(lo_, ll, sc, vt, g == 0 && wq == 0, lane);
      bar_arrive_if(rho == 2, back, NTURN);
    }
    if (!lnone) {
      bar_sync(4 + cw, 128);
      lrelease();
      lflush();
    }

    float Y[64];
    uint32_t done;
    uint4* pdst;
    auto stores = [&](uint4* dst, const uint32_t (&r)[32], uint32_t skip) {
#pragma unroll
      for (int i = 0; i < 8; i++) stg128_if0(dst + (i >> 1) * 32 + (i & 1) * 128, r[4 * i], r[4 * i + 1], r[4 * i + 2], r[4 * i + 3], skip);
    };
    auto pack = [&](uint32_t (&r)[32], const float (&acc)[64]) {
#pragma unroll
      for (int i = 0; i < 16; i++) {
        r[8 * (i >> 2) + (i & 3)] = pack_bf16(acc[4 * i], acc[4 * i + 1]);
        r[8 * (i >> 2) + (i & 3) + 4] = pack_bf16(acc[4 * i + 2], acc[4 * i + 3]);
      }
    };
    auto scale = [&](float (&acc)[64], float s0, float s1) {
#pragma unroll
      for (int i = 0; i < 64; i++) acc[i] *= i & 2 ? s1 : s0;
    };
    auto flush = [&]() {
      uint32_t r[32];
      pack(r, Y);
      stores(pdst, r, done);
      publish(it - 1, done);
    };
    auto no_pending = [&]() {
      done = 1;
      pdst = p.scr;
#pragma unroll
      for (int i = 0; i < 64; i++) Y[i] = 0.f;
    };
    no_pending();
    auto mma128 = [&](auto scr_c, float (&acc)[64], bool keep) {
      return [&acc, keep](uint32_t da, uint32_t db) {
        constexpr bool SCR = decltype(scr_c)::value;
#pragma unroll
        for (int k = 0; k < 8; k++)
          wgmma_n128<1>(acc, da + (k & 1) * 2 + ((k >> 1) & 1) * (SCR ? 32 : 4) + (k >> 2) * (SCR ? 64 : 512), SCR ? HI64 : HI128,
                        (db | (1024u << 16)) + k * 128, HI128, k != 0 || keep);
      };
    };
    auto all_but_last = [&](auto scr_c, float (&X)[64]) {
      int n = item_nk(item);
      gturn(NO, false, mma128(scr_c, X, false), flush);
      gturn(YES, false, mma128(scr_c, Y, false), nothing);
#pragma unroll 1
      while (true) {
        gturn(NO, false, mma128(scr_c, X, true), nothing);
        if ((n -= 2) == 2) break;
        gturn(YES, false, mma128(scr_c, Y, true), nothing);
      }
      fence_regs(X);
    };
    while ((item & 7) < K_OA) {
      if (idle()) {
        flush();
        done = 1;
        skip_item();
        continue;
      }
      const uint32_t kind = item & 7;
      const int g = (item >> 3) & 15, j = (item >> 7) & 15;
      const int rho = rank_of(item);
      if (kind != K_T) {
        float X[64];
        all_but_last(NO, X);
        const int lane = threadIdx.x & 31;
        const int row = item_row(K_Q, g, rho + (g == 0)) + wq * 16;
        constexpr float QS = 0.08838834764831845f * 1.4426950408889634f;
        if (kind == K_Q) scale(X, QS, QS);
        pdst = p.scr + ((kind == K_Q ? PL_Q + j * 4 : PL_KV + (j % KVR) * 4) + rank * 2 + 1) * PLANE + row * 16 + (lane ^ (lane >> 3));
        uint32_t rx[32];
        pack(rx, X);
        stores(pdst - PLANE, rx, 0);
        item = sched[++it];
        gturn(YES, false, mma128(NO, Y, true), nothing);
        fence_regs(Y);
        test_ab(pa, pb);
        if (kind == K_Q) scale(Y, QS, QS);
        if (p.zero) stores(pdst - PLANE, rx, 0);
        done = 0;
      } else {
        float(&O)[64] = Y;
        float S[64];
        float l0 = 0.f, l1 = 0.f;
        float sc0, sc1, zlim;
        const uint32_t sel = threadIdx.x & 127;
        const int b = 3 * g + 1 - rho;
        enum { FIRST, MID, LAST, HALF };
        auto round = [&](auto mode_c) {
          constexpr int MODE = decltype(mode_c)::value;
          constexpr bool INIT = MODE == LAST;
          constexpr int NI = MODE == HALF ? 8 : 16;
          const uint32_t shared = MODE == HALF ? rho == 0 : 0;
          const uint32_t tv = pb + 1 - shared;
          {
            const uint32_t dq = adesc + (pa & 1) * (A_STAGE >> 4);
            const uint32_t dk = (bdesc + (pb & 3) * 2048) | (1u << 16);
            if (INIT) {
              const int lane = threadIdx.x & 31;
              const int row = (wq * 16 + (lane >> 2) - 2 * (lane & 3) + 11) << 23;
              const int r0 = row ^ (__float_as_uint(l0) & p.zero & (MODE + 16)), r1 = row ^ (__float_as_uint(l1) & p.zero & (MODE + 16));
#pragma unroll
              for (int i = 0; i < 4 * NI; i++) {
                const int c = i - 4 * (NI - 8);
                S[i] = c < 0 ? 0.f : __int_as_float((c & 2 ? r1 : r0) + ((4 * (c & 2) - 2 * (c & ~3) - (c & 1) - 11) << 23));
                asm volatile("" : "+f"(S[i])::"memory");
              }
            }
            wait_ab();
            turn();
            wg_fence();
#pragma unroll
            for (int k = 0; k < 8; k++) {
              if (MODE == HALF) wgmma_n64(S, dq + (k >> 1) * 32 + (k & 1) * 2, dk + (k >> 1) * 32 + (k & 1) * 2, k != 0 || INIT);
              else wgmma_n128<0>(S, dq + (k >> 1) * 32 + (k & 1) * 2, HI64, dk + (k >> 1) * 32 + (k & 1) * 2, HI64, k != 0 || INIT);
            }
            wg_commit();
            pass();
          }
          test_b(bfull0 + 8 * (tv & 3), (tv >> 2) & 1);
          if (!ready_b()) mbar_wait_u(bfull0 + 8 * (tv & 3), (tv >> 2) & 1);
          uint32_t r[32];
          if (MODE == FIRST) {
            pack(r, Y);
#pragma unroll
            for (int i = 0; i < 32; i++) asm volatile("" : "+r"(r[i])::"memory");
            done |= sched_fence() & p.zero;
          }
          wg_wait<0>();
#pragma unroll
          for (int i = 0; i < 4 * NI; i++) asm volatile("" : "+f"(S[i])::"memory");
          mbar_arrive_if0(bempty0 + 8 * (pb & 3), sel | shared);
          if (MODE >= LAST) mbar_arrive_cta_if0(aempty + 8 * (pa & 1), wq & 1, (sel & 31) | (wq >> 1));
          uint32_t P[2 * NI];
          if (MODE >= LAST && !INIT) {
            const int lane = threadIdx.x & 31;
            const int row = wq * 16 + (lane >> 2) - 2 * (lane & 3);
#pragma unroll
            for (int i = 0; i < 8; i++) {
#pragma unroll
              for (int e = 0; e < 2; e++) {
                if (8 * i + e > row) S[4 * (NI - 8 + i) + e] = -INFINITY;
                if (8 * i + e > row + 8) S[4 * (NI - 8 + i) + 2 + e] = -INFINITY;
              }
            }
          }
          float s0 = 0.f, s1 = 0.f, t0 = 0.f, t1 = 0.f;
#pragma unroll
          for (int i = 0; i < NI; i++) {
#pragma unroll
            for (int e = 0; e < 4; e++) S[4 * i + e] = ex2(S[4 * i + e]);
            s0 += S[4 * i];
            t0 += S[4 * i + 1];
            s1 += S[4 * i + 2];
            t1 += S[4 * i + 3];
            P[2 * i] = pack_bf16(S[4 * i], S[4 * i + 1]);
            P[2 * i + 1] = pack_bf16(S[4 * i + 2], S[4 * i + 3]);
            if (MODE == FIRST) {
#pragma unroll
              for (int k = 0; k < 8; k++)
                if (k * 7 / 4 == i)
                  stg128_if0(pdst + (k >> 1) * 32 + (k & 1) * 128, r[4 * k], r[4 * k + 1], r[4 * k + 2], r[4 * k + 3], done | (P[2 * i] & p.zero));
              if (i == 12) publish(it - 1, done);
            }
          }
          l0 += s0 + t0;
          l1 += s1 + t1;
          uint32_t dep = (__float_as_uint(l0) ^ __float_as_uint(l1)) ^ P[2 * NI - 1];
          if (MODE != FIRST) fence_regs(O);
#pragma unroll
          for (int i = 0; i < 2 * NI; i++) asm volatile("" : "+r"(P[i])::"memory");
          turn(dep & p.zero);
          wg_fence();
          const uint32_t dv = (bdesc + (tv & 3) * 2048 + shared * 1024) | (32u << 16);
#pragma unroll
          for (int k = 0; k < NI / 2; k++)
            wgmma_n128_rs_tb(O, P[4 * k], P[4 * k + 1], P[4 * k + 2], P[4 * k + 3], dv + k * 256, k != 0 || MODE != FIRST);
          wg_commit();
          pass();
          pb = tv + 1;
          if (MODE >= LAST) {
            const int nskip = 1 + (g & 1);
            if (rho + nskip >= 3) pb += 3 - nskip;
            pa++;
          } else {
            test_ab(pa, pb);
          }
          if (MODE >= LAST) {
            l0 += __shfl_xor_sync(0xffffffffu, l0, 1);
            l1 += __shfl_xor_sync(0xffffffffu, l1, 1);
            l0 += __shfl_xor_sync(0xffffffffu, l0, 2);
            l1 += __shfl_xor_sync(0xffffffffu, l1, 2);
            sc0 = rcp(l0);
            sc1 = rcp(l1);
            zlim = l0 <= KB_LIMIT && l0 >= KB_LOW && l1 <= KB_LIMIT && l1 >= KB_LOW ? 3e38f : -1.f;
          }
          wg_wait<0>();
          fence_regs(O);
          mbar_arrive_if0(bempty0 + 8 * (tv & 3), sel);
        };
        if (b < 2) {
          flush();
#pragma unroll
          for (int i = 0; i < 64; i++) O[i] = 0.f;
        } else {
          round(std::integral_constant<int, FIRST>{});
#pragma unroll 1
          for (int n = b >> 1; --n;) round(std::integral_constant<int, MID>{});
        }
        item = sched[++it];
        if (b & 1) round(std::integral_constant<int, LAST>{});
        else round(std::integral_constant<int, HALF>{});
        test_ab(pa, pb);
        float z[4] = {0.f, 0.f, 0.f, 0.f};
#pragma unroll
        for (int i = 0; i < 32; i++) z[i & 3] = fmaf(O[2 * i], O[2 * i + 1], z[i & 3]);
        const bool bad = !(fabsf(z[0]) + fabsf(z[1]) + fabsf(z[2]) + fabsf(z[3]) <= zlim);
        scale(O, sc0, sc1);
        const int lane = threadIdx.x & 31;
        pdst = p.scr + (PL_Q + 2 * j + rank) * PLANE + (b * 64 + wq * 16) * 16 + (lane ^ (lane >> 3));
        done = 0;
        if (__any_sync(0xffffffffu, bad)) {
          attn_fallback(p.scr + (PL_Q + 2 * j + rank) * PLANE, p.scr + (PL_KV + (j % KVR) * 4 + rank) * PLANE, b * 64 + wq * 16,
                        threadIdx.x & 31);
          publish(it - 1);
          no_pending();
          test_ab(pa, pb);
        }
      }
    }

    if ((item & 7) == K_END) {
      flush();
    } else if (idle()) {
      flush();
      skip_item();
    } else {
      const uint32_t kind = item & 7;
      const int g = (item >> 3) & 15, j = (item >> 7) & 15;
      const int row = item_row(kind, g, rank_of(item) + (g == 0)) + wq * 16;
      auto epilogue = [&](float (&acc)[64], int cb) {
        const int lane = threadIdx.x & 31;
        const uint32_t stg = abase + ((pa - 1) & 1) * A_STAGE + wq * 4096;
        const int srow = lane & 15;
#pragma unroll
        for (int jj = 0; jj < 8; jj++) {
          const uint32_t r0 = pack_bf16(acc[8 * jj + 0], acc[8 * jj + 1]);
          const uint32_t r1 = pack_bf16(acc[8 * jj + 2], acc[8 * jj + 3]);
          const uint32_t r2 = pack_bf16(acc[8 * jj + 4], acc[8 * jj + 5]);
          const uint32_t r3 = pack_bf16(acc[8 * jj + 6], acc[8 * jj + 7]);
          const int chunk = (2 * jj + (lane >> 4)) & 7;
          const uint32_t addr = stg + (jj >> 2) * 2048 + srow * 128 + ((chunk ^ (srow & 7)) << 4);
          asm volatile("stmatrix.sync.aligned.m8n8.x4.shared.b16 [%0], {%1,%2,%3,%4};" ::"r"(addr), "r"(r0), "r"(r1), "r"(r2), "r"(r3)
                       : "memory");
        }
        asm volatile("fence.proxy.async.shared::cta;" ::: "memory");
        __syncwarp();
        if (lane == 0) {
          const int col = cb * 128 + (kind == K_OA ? (row >> 10) * 2048 : 1024);
          const int r = kind == K_OA ? row & 1023 : row;
          tma_store_2d(&p.mapO[kind - K_OA], stg, col, r);
          tma_store_2d(&p.mapO[kind - K_OA], stg + 2048, col + 64, r);
          asm volatile("cp.async.bulk.commit_group;" ::: "memory");
        }
      };
      float X[64];
      if (item_narrow(item)) {
        int n = item_nk(item);
        gturn(ONCE, false, mma128(YES, X, false), flush);
#pragma unroll 1
        while (--n) gturn(ONCE, false, mma128(YES, X, true), nothing);
        fence_regs(X);
        epilogue(X, 2 * j + rank - 8);
      } else {
        all_but_last(YES, X);
        epilogue(X, 4 * j + 2 * rank);
        gturn(YES, false, mma128(YES, Y, true), nothing);
        fence_regs(Y);
        epilogue(Y, 4 * j + 2 * rank + 1);
      }
      publish(it);
      item = sched[++it];
    }
    const int rho = rank_of(item);
    if (rho == 0) {
      turn();
      pass();
    }
    if (rho == 1) turn();
    publish(MAXITEMS - 1);
    asm volatile("cp.async.bulk.wait_group.read 0;" ::: "memory");
  }
}

typedef CUresult (*EncodeFn)(CUtensorMap*, CUtensorMapDataType, cuuint32_t, void*, const cuuint64_t*, const cuuint64_t*,
                             const cuuint32_t*, const cuuint32_t*, CUtensorMapInterleave, CUtensorMapSwizzle, CUtensorMapL2promotion,
                             CUtensorMapFloatOOBfill);

void make_map(EncodeFn enc, CUtensorMap* m, const void* ptr, uint64_t d0, uint64_t d1, uint64_t d2, uint64_t s1, uint64_t s2, uint32_t b0,
              uint32_t b1, uint32_t b2) {
  cuuint64_t gd[3] = {d0, d1, d2}, gs[2] = {s1, s2};
  cuuint32_t bd[3] = {b0, b1, b2}, es[3] = {1, 1, 1};
  enc(m, CU_TENSOR_MAP_DATA_TYPE_BFLOAT16, d2 ? 3 : 2, const_cast<void*>(ptr), gd, gs, bd, es, CU_TENSOR_MAP_INTERLEAVE_NONE,
      CU_TENSOR_MAP_SWIZZLE_128B, CU_TENSOR_MAP_L2_PROMOTION_L2_128B, CU_TENSOR_MAP_FLOAT_OOB_FILL_NONE);
}

struct HostState {
  Params p;
  const void* in[9];
  void* out;
  bool valid;
};
HostState g_hs;

const uint16_t h_sched[NCLUSTERS * MAXITEMS] = {
    512, 424, 1155, 1107, 427, 1577, 1587, 517, 7, 7, 7, 7, 7, 7, 7, 7,
    288, 273, 145, 305, 19, 1939, 1963, 713, 1337, 1729, 717, 7, 7, 7, 7, 7,
    768, 688, 275, 1921, 945, 1953, 529, 441, 577, 1875, 1803, 132, 7, 7, 7, 7,
    640, 400, 1059, 1097, 49, 1969, 553, 1681, 1539, 1315, 925, 7, 7, 7, 7, 7,
    280, 912, 1209, 33, 393, 417, 643, 779, 579, 821, 7, 7, 7, 7, 7, 7,
    320, 704, 267, 203, 1297, 1491, 1683, 156, 7, 7, 7, 7, 7, 7, 7, 7,
    136, 257, 1049, 323, 1987, 1481, 1555, 965, 7, 7, 7, 7, 7, 7, 7, 7,
    528, 448, 1083, 521, 1425, 707, 541, 7, 7, 7, 7, 7, 7, 7, 7, 7,
    848, 80, 17, 1225, 1931, 513, 467, 1851, 44, 7, 7, 7, 7, 7, 7, 7,
    160, 40, 291, 193, 1961, 545, 1801, 1825, 1435, 941, 7, 7, 7, 7, 7, 7,
    560, 440, 915, 971, 561, 563, 573, 7, 7, 7, 7, 7, 7, 7, 7, 7,
    544, 944, 899, 1081, 35, 1995, 1739, 188, 7, 7, 7, 7, 7, 7, 7, 7,
    536, 1169, 297, 939, 961, 785, 595, 933, 7, 7, 7, 7, 7, 7, 7, 7,
    184, 0, 9, 1217, 979, 833, 547, 549, 7, 7, 7, 7, 7, 7, 7, 7,
    824, 56, 1091, 73, 1433, 683, 1723, 140, 7, 7, 7, 7, 7, 7, 7, 7,
    176, 976, 1027, 3, 931, 43, 819, 1849, 515, 829, 7, 7, 7, 7, 7, 7,
    648, 960, 321, 963, 851, 701, 7, 7, 7, 7, 7, 7, 7, 7, 7, 7,
    672, 384, 1043, 131, 313, 171, 723, 1843, 212, 7, 7, 7, 7, 7, 7, 7,
    200, 656, 331, 1409, 419, 1579, 589, 7, 7, 7, 7, 7, 7, 7, 7, 7,
    264, 913, 1, 1201, 1089, 83, 1331, 981, 7, 7, 7, 7, 7, 7, 7, 7,
    312, 8, 161, 1937, 385, 2003, 1361, 1571, 1811, 1795, 4, 7, 7, 7, 7, 7,
    168, 16, 1179, 1233, 641, 977, 1993, 667, 1841, 1547, 949, 7, 7, 7, 7, 7,
    792, 936, 283, 195, 1441, 1483, 901, 7, 7, 7, 7, 7, 7, 7, 7, 7,
    816, 265, 921, 259, 177, 185, 401, 425, 1545, 675, 1721, 1835, 36, 7, 7, 7,
    784, 720, 1073, 211, 1665, 1355, 645, 7, 7, 7, 7, 7, 7, 7, 7, 7,
    568, 24, 307, 209, 537, 449, 721, 1353, 1419, 669, 7, 7, 7, 7, 7, 7,
    192, 48, 315, 65, 1985, 705, 1697, 1603, 68, 7, 7, 7, 7, 7, 7, 7,
    808, 1153, 905, 153, 169, 187, 1553, 1459, 909, 7, 7, 7, 7, 7, 7, 7,
    272, 696, 923, 179, 651, 715, 973, 7, 7, 7, 7, 7, 7, 7, 7, 7,
    152, 1041, 1057, 937, 337, 51, 697, 585, 1867, 172, 7, 7, 7, 7, 7, 7,
    840, 64, 1051, 329, 1955, 689, 465, 1705, 1857, 725, 7, 7, 7, 7, 7, 7,
    2, 10, 18, 26, 34, 42, 771, 1339, 709, 7, 7, 7, 7, 7, 7, 7,
    144, 432, 1171, 139, 27, 769, 459, 1595, 164, 7, 7, 7, 7, 7, 7, 7,
    208, 968, 1203, 649, 673, 2001, 1689, 1713, 1291, 653, 7, 7, 7, 7, 7, 7,
    130, 138, 146, 154, 162, 170, 1449, 849, 1617, 557, 7, 7, 7, 7, 7, 7,
    664, 72, 907, 147, 1923, 41, 777, 801, 1673, 593, 1859, 196, 7, 7, 7, 7,
    800, 464, 339, 403, 1475, 957, 7, 7, 7, 7, 7, 7, 7, 7, 7, 7,
    258, 266, 274, 282, 290, 298, 1809, 1585, 531, 797, 7, 7, 7, 7, 7, 7,
    552, 32, 1163, 155, 67, 1457, 1747, 84, 7, 7, 7, 7, 7, 7, 7, 7,
    712, 1161, 1185, 1227, 1417, 817, 1465, 539, 789, 7, 7, 7, 7, 7, 7, 7,
    386, 394, 402, 410, 418, 426, 1561, 1451, 533, 7, 7, 7, 7, 7, 7, 7,
    256, 392, 1219, 969, 81, 1305, 1347, 1691, 28, 7, 7, 7, 7, 7, 7, 7,
    576, 1025, 289, 929, 1929, 953, 657, 681, 457, 841, 1563, 781, 7, 7, 7, 7,
    514, 522, 530, 538, 546, 554, 825, 1473, 1609, 693, 7, 7, 7, 7, 7, 7,
    584, 952, 1035, 11, 163, 1971, 1817, 1489, 1873, 1827, 60, 7, 7, 7, 7, 7,
    680, 904, 1187, 1945, 409, 433, 795, 1833, 1745, 813, 7, 7, 7, 7, 7, 7,
    642, 650, 658, 666, 674, 682, 811, 1427, 597, 7, 7, 7, 7, 7, 7, 7,
    304, 456, 1075, 59, 1569, 1611, 1667, 180, 7, 7, 7, 7, 7, 7, 7, 7,
    832, 897, 1177, 1065, 947, 1979, 1323, 525, 7, 7, 7, 7, 7, 7, 7, 7,
    770, 778, 786, 794, 802, 810, 803, 1307, 661, 7, 7, 7, 7, 7, 7, 7,
    328, 928, 1067, 201, 665, 699, 1731, 52, 7, 7, 7, 7, 7, 7, 7, 7,
    296, 416, 1099, 793, 1793, 1363, 773, 7, 7, 7, 7, 7, 7, 7, 7, 7,
    898, 906, 914, 922, 930, 938, 827, 1411, 677, 7, 7, 7, 7, 7, 7, 7,
    592, 920, 1195, 75, 1329, 1601, 1715, 20, 7, 7, 7, 7, 7, 7, 7, 7,
    520, 1033, 137, 1211, 1947, 809, 571, 565, 7, 7, 7, 7, 7, 7, 7, 7,
    306, 314, 322, 330, 338, 451, 1299, 845, 7, 7, 7, 7, 7, 7, 7, 7,
    50, 58, 66, 74, 82, 1281, 787, 1619, 1675, 148, 7, 7, 7, 7, 7, 7,
    128, 408, 299, 1105, 57, 1977, 587, 581, 7, 7, 7, 7, 7, 7, 7, 7,
    434, 442, 450, 458, 466, 443, 1737, 1283, 917, 7, 7, 7, 7, 7, 7, 7,
    178, 186, 194, 202, 210, 435, 1593, 523, 1707, 76, 7, 7, 7, 7, 7, 7,
    336, 896, 1193, 25, 955, 1537, 1313, 555, 685, 7, 7, 7, 7, 7, 7, 7,
    690, 698, 706, 714, 722, 411, 1321, 1443, 837, 7, 7, 7, 7, 7, 7, 7,
    562, 570, 578, 586, 594, 1289, 569, 1467, 1819, 12, 7, 7, 7, 7, 7, 7,
    776, 281, 129, 1235, 387, 395, 843, 853, 7, 7, 7, 7, 7, 7, 7, 7,
    946, 954, 962, 970, 978, 659, 835, 805, 7, 7, 7, 7, 7, 7, 7, 7,
    818, 826, 834, 842, 850, 691, 1345, 1865, 1699, 204, 7, 7, 7, 7, 7, 7,
};

void setup(void* const* d_in, void* d_out) {
  void* fn = nullptr;
  cudaDriverEntryPointQueryResult qr;
  cudaGetDriverEntryPoint("cuTensorMapEncodeTiled", &fn, cudaEnableDefault, &qr);
  EncodeFn enc = (EncodeFn)fn;
  void *scr, *carry, *flags;
  cudaGetSymbolAddress(&scr, g_scr);
  cudaGetSymbolAddress(&carry, g_carry);
  cudaGetSymbolAddress(&flags, g_flags);
  Params& p = g_hs.p;
  make_map(enc, &p.mapA[0], d_in[3], 64, 2048, 16, 2048, 128, 64, 64, 1);
  make_map(enc, &p.mapA[1], d_in[4], 64, 2048, 8, 1024, 128, 64, 64, 1);
  make_map(enc, &p.mapA[2], d_in[0], 64, 1024, 32, 4096, 128, 64, 64, 1);
  make_map(enc, &p.mapB[0], d_in[5], 64, 1024, 64, 8192, 128, 64, 128, 2);
  make_map(enc, &p.mapB[1], d_in[6], 64, 512, 64, 8192, 128, 64, 128, 2);
  make_map(enc, &p.mapB[2], d_in[1], 1024, 1024, 3, 6144, 2048, 64, 64, 3);
  make_map(enc, &p.mapB[3], d_in[7], 64, 512, 64, 8192, 128, 64, 128, 2);
  make_map(enc, &p.mapB[5], d_in[8], 64, 4096, 16, 2048, 128, 64, 128, 2);
  {
    cuuint64_t gd[5] = {1024, 2, 4, 4, 32}, gs[4] = {2048, 8 * 2048, 2 * 2048, 32 * 2048};
    cuuint32_t bd[5] = {64, 2, 4, 4, 4}, es[5] = {1, 1, 1, 1, 1};
    enc(&p.mapB[4], CU_TENSOR_MAP_DATA_TYPE_BFLOAT16, 5, d_in[2], gd, gs, bd, es, CU_TENSOR_MAP_INTERLEAVE_NONE, CU_TENSOR_MAP_SWIZZLE_128B,
        CU_TENSOR_MAP_L2_PROMOTION_L2_128B, CU_TENSOR_MAP_FLOAT_OOB_FILL_NONE);
  }
  make_map(enc, &p.mapO[0], d_out, 4096, 1024, 0, 8192, 0, 64, 16, 1);
  make_map(enc, &p.mapO[1], d_out, 2048, 2048, 0, 4096, 0, 64, 16, 1);
  p.scr = (uint4*)scr;
  p.carry = (uint4*)carry;
  p.flags = (uint32_t*)flags;
  p.zero = 0;
  for (int c = 0; c < NCLUSTERS; c++) {
    int rot = 0;
    for (int i = c * MAXITEMS; i < (c + 1) * MAXITEMS; i++) {
      const int kind = h_sched[i] & 7, g = (h_sched[i] >> 3) & 15;
      p.sched[i] = (uint16_t)(h_sched[i] | rot << 11);
      rot = (rot + (kind == K_T ? 1 + (g & 1) : g == 0)) % 3;
    }
  }
  cudaFuncSetAttribute(fused_kernel, cudaFuncAttributeMaxDynamicSharedMemorySize, SM_TOTAL);
  for (int i = 0; i < 9; i++) g_hs.in[i] = d_in[i];
  g_hs.out = d_out;
  g_hs.valid = true;
}

}

extern "C" void kernel_launch(void* const* d_in, const int* in_sizes, int n_in, void* d_out, int out_size) {
  (void)in_sizes;
  (void)n_in;
  (void)out_size;
  bool ok = g_hs.valid && g_hs.out == d_out;
  for (int i = 0; ok && i < 9; i++) ok = g_hs.in[i] == d_in[i];
  if (!ok) setup(d_in, d_out);
  fused_kernel<<<NCLUSTERS * 2, 512, SM_TOTAL, cudaStreamPerThread>>>(g_hs.p);
}
```

```cpp
#include <cuda_runtime.h>
#include <cuda_bf16.h>
#include <cuda.h>
#include <stdint.h>
#include <type_traits>

namespace {

typedef __nv_bfloat16 bf16;

__device__ __forceinline__ uint32_t smem_u32(const void* p) { return (uint32_t)__cvta_generic_to_shared(p); }
__device__ __forceinline__ void mbar_init(uint32_t bar, uint32_t cnt) {
  asm volatile("mbarrier.init.shared::cta.b64 [%0], %1;" ::"r"(bar), "r"(cnt) : "memory");
}
__device__ __forceinline__ void mbar_expect_tx(uint32_t bar, uint32_t bytes) {
  asm volatile("mbarrier.arrive.expect_tx.shared::cta.b64 _, [%0], %1;" ::"r"(bar), "r"(bytes) : "memory");
}
__device__ __forceinline__ void mbar_arrive_n(uint32_t bar, uint32_t n) {
  asm volatile("mbarrier.arrive.shared::cta.b64 _, [%0], %1;" ::"r"(bar), "r"(n) : "memory");
}
__device__ __forceinline__ void mbar_arrive_if0(uint32_t bar, uint32_t sel) {
  asm volatile("{\n.reg .pred p;\nsetp.eq.u32 p, %1, 0;\n@p mbarrier.arrive.shared::cta.b64 _, [%0];\n}" ::"r"(bar), "r"(sel) : "memory");
}
__device__ __forceinline__ void mbar_arrive_cta_if0(uint32_t bar, uint32_t cta, uint32_t sel) {
  asm volatile("{\n.reg .pred p;\n.reg .b32 ra;\nsetp.eq.u32 p, %2, 0;\nmapa.shared::cluster.u32 ra, %0, %1;\n"
               "@p mbarrier.arrive.shared::cluster.b64 _, [ra];\n}" ::"r"(bar),
               "r"(cta), "r"(sel)
               : "memory");
}
__device__ __forceinline__ void mbar_wait(uint32_t bar, uint32_t parity) {
  uint32_t done;
  uint32_t it = 0;
#pragma unroll 1
  while (true) {
    asm volatile("{\n.reg .pred p;\nmbarrier.try_wait.parity.shared::cta.b64 p, [%1], %2, 1000;\nselp.u32 %0, 1, 0, p;\n}"
                 : "=r"(done)
                 : "r"(bar), "r"(parity)
                 : "memory");
    if (done) break;
    if (++it > (1u << 24)) __trap();
  }
}
__device__ __forceinline__ void mbar_wait_u(uint32_t bar, uint32_t parity) {
  uint32_t it = 0;
#pragma unroll 1
  while (true) {
    uint32_t done;
    asm volatile("{\n.reg .pred p, q;\nmbarrier.try_wait.parity.shared::cta.b64 p, [%1], %2;\nvote.sync.all.pred q, p, 0xffffffff;\nselp.u32 %0, 1, 0, q;\n}"
                 : "=r"(done)
                 : "r"(bar), "r"(parity)
                 : "memory");
    if (done) break;
    if (++it > (1u << 20)) break;
  }
}
#define DECLARE_READY() asm volatile(".reg .pred RDYA, RDYB;")
__device__ __forceinline__ void test_a(uint32_t bar, uint32_t parity) {
  asm volatile("mbarrier.test_wait.parity.shared::cta.b64 RDYA, [%0], %1;" ::"r"(bar), "r"(parity) : "memory");
}
__device__ __forceinline__ void test_b(uint32_t bar, uint32_t parity) {
  asm volatile("mbarrier.test_wait.parity.shared::cta.b64 RDYB, [%0], %1;" ::"r"(bar), "r"(parity) : "memory");
}
__device__ __forceinline__ uint32_t ready_b(uint32_t dep = 0) {
  uint32_t r;
  asm volatile("{\n.reg .pred q;\nsetp.eq.and.u32 q, %1, 0, RDYB;\nvote.sync.all.pred q, q, 0xffffffff;\nselp.u32 %0, 1, 0, q;\n}" : "=r"(r) : "r"(dep) : "memory");
  return r;
}
__device__ __forceinline__ uint32_t ready_ab() {
  uint32_t r;
  asm volatile("{\n.reg .pred q;\nand.pred q, RDYA, RDYB;\nvote.sync.all.pred q, q, 0xffffffff;\nselp.u32 %0, 1, 0, q;\n}" : "=r"(r)::"memory");
  return r;
}
__device__ __forceinline__ void tma_load_3d(uint32_t dst, const CUtensorMap* m, uint32_t bar, int c0, int c1, int c2) {
  asm volatile("cp.async.bulk.tensor.3d.shared::cluster.global.mbarrier::complete_tx::bytes [%0], [%1, {%3, %4, %5}], [%2];" ::"r"(dst),
               "l"(m), "r"(bar), "r"(c0), "r"(c1), "r"(c2)
               : "memory");
}
__device__ __forceinline__ void tma_load_3d_mc(uint32_t dst, const CUtensorMap* m, uint32_t bar, int c0, int c1, int c2, uint16_t mask) {
  asm volatile(
      "cp.async.bulk.tensor.3d.shared::cluster.global.mbarrier::complete_tx::bytes.multicast::cluster [%0], [%1, {%3, %4, %5}], [%2], %6;" ::"r"(dst),
      "l"(m), "r"(bar), "r"(c0), "r"(c1), "r"(c2), "h"(mask)
      : "memory");
}
__device__ __forceinline__ void tma_load_5d(uint32_t dst, const CUtensorMap* m, uint32_t bar, int c0, int c4) {
  asm volatile("cp.async.bulk.tensor.5d.shared::cluster.global.mbarrier::complete_tx::bytes [%0], [%1, {%3, 0, 0, 0, %4}], [%2];" ::"r"(dst),
               "l"(m), "r"(bar), "r"(c0), "r"(c4)
               : "memory");
}
__device__ __forceinline__ void bulk_load(uint32_t dst, const void* src, uint32_t bytes, uint32_t bar) {
  asm volatile("cp.async.bulk.shared::cluster.global.mbarrier::complete_tx::bytes [%0], [%1], %2, [%3];" ::"r"(dst), "l"(src), "r"(bytes), "r"(bar)
               : "memory");
}
__device__ __forceinline__ void bulk_load_mc(uint32_t dst, const void* src, uint32_t bytes, uint32_t bar, uint16_t mask) {
  asm volatile("cp.async.bulk.shared::cluster.global.mbarrier::complete_tx::bytes.multicast::cluster [%0], [%1], %2, [%3], %4;" ::"r"(dst),
               "l"(src), "r"(bytes), "r"(bar), "h"(mask)
               : "memory");
}
__device__ __forceinline__ void prefetch_l2(const void* src, uint32_t bytes) {
  asm volatile("cp.async.bulk.prefetch.L2.global [%0], %1;" ::"l"(src), "r"(bytes) : "memory");
}
__device__ __forceinline__ void tma_store_2d(const CUtensorMap* m, uint32_t src, int c0, int c1) {
  asm volatile("cp.async.bulk.tensor.2d.global.shared::cta.bulk_group [%0, {%2, %3}], [%1];" ::"l"(m), "r"(src), "r"(c0), "r"(c1)
               : "memory");
}
__device__ __forceinline__ void prefetch_tmap(const CUtensorMap* m) { asm volatile("prefetch.tensormap [%0];" ::"l"(m) : "memory"); }
__device__ __forceinline__ uint32_t pack_bf16(float lo, float hi) {
  uint32_t r;
  asm("cvt.rn.bf16x2.f32 %0, %1, %2;" : "=r"(r) : "f"(hi), "f"(lo));
  return r;
}
__device__ __forceinline__ float ex2(float x) {
  float y;
  asm("ex2.approx.ftz.f32 %0, %1;" : "=f"(y) : "f"(x));
  return y;
}
__device__ __forceinline__ float rcp(float x) {
  float y;
  asm("rcp.approx.ftz.f32 %0, %1;" : "=f"(y) : "f"(x));
  return y;
}
__device__ __forceinline__ void wg_fence() { asm volatile("wgmma.fence.sync.aligned;" ::: "memory"); }
__device__ __forceinline__ void wg_commit() { asm volatile("wgmma.commit_group.sync.aligned;" ::: "memory"); }
template <int N>
__device__ __forceinline__ void wg_wait() {
  asm volatile("wgmma.wait_group.sync.aligned %0;" ::"n"(N) : "memory");
}
template <int N>
__device__ __forceinline__ void fence_regs(float (&d)[N]) {
#pragma unroll
  for (int i = 0; i < N; i++) asm volatile("" : "+f"(d[i])::"memory");
}
__device__ __forceinline__ uint32_t sched_fence() {
  uint32_t t;
  asm volatile("mov.u32 %0, %%clock;" : "=r"(t)::"memory");
  return t;
}
__device__ __forceinline__ void bar_sync(int id, int n) { asm volatile("bar.sync %0, %1;" ::"r"(id), "r"(n) : "memory"); }
__device__ __forceinline__ void bar_arrive_if(bool c, int id, int n) {
  asm volatile("{\n.reg .pred p;\nsetp.ne.u32 p, %2, 0;\n@p bar.arrive %0, %1;\n}" ::"r"(id), "r"(n), "r"((uint32_t)c) : "memory");
}
__device__ __forceinline__ void bar_arrive(int id, int n) { asm volatile("bar.arrive %0, %1;" ::"r"(id), "r"(n) : "memory"); }

#define R8(a, i) "+f"(a[i]), "+f"(a[i + 1]), "+f"(a[i + 2]), "+f"(a[i + 3]), "+f"(a[i + 4]), "+f"(a[i + 5]), "+f"(a[i + 6]), "+f"(a[i + 7])
#define OP32(d, o) R8(d, o), R8(d, o + 8), R8(d, o + 16), R8(d, o + 24)
#define L32A "%0,%1,%2,%3,%4,%5,%6,%7,%8,%9,%10,%11,%12,%13,%14,%15,%16,%17,%18,%19,%20,%21,%22,%23,%24,%25,%26,%27,%28,%29,%30,%31"
#define L32B "%32,%33,%34,%35,%36,%37,%38,%39,%40,%41,%42,%43,%44,%45,%46,%47,%48,%49,%50,%51,%52,%53,%54,%55,%56,%57,%58,%59,%60,%61,%62,%63"
#define L32C "%64,%65,%66,%67,%68,%69,%70,%71,%72,%73,%74,%75,%76,%77,%78,%79,%80,%81,%82,%83,%84,%85,%86,%87,%88,%89,%90,%91,%92,%93,%94,%95"
#define WG_PRE(a, b, s, ha, hb) "{\n.reg .pred p;\n.reg .b64 da, db;\nmov.b64 da, {" a ", " ha "};\nmov.b64 db, {" b ", " hb "};\nsetp.ne.b32 p, " s ", 0;\n"

constexpr uint32_t HI128 = 0x40000040;
constexpr uint32_t HI64 = 0x80000080;
constexpr uint32_t HIQ = 0x80000040;
template <int TB>
__device__ __forceinline__ void wgmma_n128(float (&d)[64], uint32_t da, uint32_t ha, uint32_t db, uint32_t hb, int scale_d) {
  asm volatile(WG_PRE("%64", "%65", "%66", "%67", "%68") "wgmma.mma_async.sync.aligned.m64n128k16.f32.bf16.bf16 {" L32A "," L32B "}, da, db, p, 1, 1, 0, %69;\n}\n"
               : OP32(d, 0), OP32(d, 32)
               : "r"(da), "r"(db), "r"(scale_d), "r"(ha), "r"(hb), "n"(TB));
}
__device__ __forceinline__ void wgmma_n192_tb(float (&d)[96], uint32_t da, uint32_t db, int scale_d) {
  asm volatile(WG_PRE("%96", "%97", "%98", "%99", "%99") "wgmma.mma_async.sync.aligned.m64n192k16.f32.bf16.bf16 {" L32A "," L32B "," L32C "}, da, db, p, 1, 1, 0, 1;\n}\n"
               : OP32(d, 0), OP32(d, 32), OP32(d, 64)
               : "r"(da), "r"(db), "r"(scale_d), "r"(HI128));
}
__device__ __forceinline__ void wgmma_n64(float (&d)[64], uint32_t da, uint32_t db, int scale_d) {
  asm volatile(WG_PRE("%32", "%33", "%34", "%35", "%36") "wgmma.mma_async.sync.aligned.m64n64k16.f32.bf16.bf16 {" L32A "}, da, db, p, 1, 1, 0, 0;\n}\n"
               : OP32(d, 0)
               : "r"(da), "r"(db), "r"(scale_d), "r"(HIQ), "r"(HI64));
}
__device__ __forceinline__ void wgmma_n128_rs_tb(float (&d)[64], uint32_t a0, uint32_t a1, uint32_t a2, uint32_t a3, uint32_t db, int scale_d) {
  asm volatile("{\n.reg .pred p;\n.reg .b64 db;\nmov.b64 db, {%68, %70};\nsetp.ne.b32 p, %69, 0;\n"
               "wgmma.mma_async.sync.aligned.m64n128k16.f32.bf16.bf16 {" L32A "," L32B "}, {%64,%65,%66,%67}, db, p, 1, 1, 1;\n}\n"
               : OP32(d, 0), OP32(d, 32)
               : "r"(a0), "r"(a1), "r"(a2), "r"(a3), "r"(db), "r"(scale_d), "r"(HI64));
}
__device__ __forceinline__ void mma_16816(float (&c)[4], uint32_t a0, uint32_t a1, uint32_t a2, uint32_t a3, uint32_t b0, uint32_t b1) {
  asm volatile("mma.sync.aligned.m16n8k16.row.col.f32.bf16.bf16.f32 {%0,%1,%2,%3}, {%4,%5,%6,%7}, {%8,%9}, {%0,%1,%2,%3};"
               : "+f"(c[0]), "+f"(c[1]), "+f"(c[2]), "+f"(c[3])
               : "r"(a0), "r"(a1), "r"(a2), "r"(a3), "r"(b0), "r"(b1));
}
__device__ __forceinline__ uint32_t movm_t(uint32_t x) {
  uint32_t y;
  asm volatile("movmatrix.sync.aligned.m8n8.trans.b16 %0, %1;" : "=r"(y) : "r"(x));
  return y;
}
__device__ __forceinline__ void sts128(uint32_t a, uint32_t x, uint32_t y, uint32_t z, uint32_t w) {
  asm volatile("st.shared.v4.u32 [%0], {%1,%2,%3,%4};" ::"r"(a), "r"(x), "r"(y), "r"(z), "r"(w) : "memory");
}
__device__ __forceinline__ void stsm4(uint32_t a, uint32_t x, uint32_t y, uint32_t z, uint32_t w) {
  asm volatile("stmatrix.sync.aligned.m8n8.x4.shared.b16 [%0], {%1,%2,%3,%4};" ::"r"(a), "r"(x), "r"(y), "r"(z), "r"(w) : "memory");
}
__device__ __forceinline__ void ldsm4_t(uint32_t a, uint32_t (&r)[4]) {
  asm volatile("ldmatrix.sync.aligned.m8n8.x4.trans.shared.b16 {%0,%1,%2,%3}, [%4];"
               : "=r"(r[0]), "=r"(r[1]), "=r"(r[2]), "=r"(r[3])
               : "r"(a)
               : "memory");
}
__device__ __forceinline__ void stg128_if0(uint4* a, uint32_t x, uint32_t y, uint32_t z, uint32_t w, uint32_t sel) {
  asm volatile("{\n.reg .pred p;\nsetp.eq.u32 p, %5, 0;\n@p st.global.v4.u32 [%0], {%1,%2,%3,%4};\n}" ::"l"(a), "r"(x), "r"(y), "r"(z), "r"(w),
               "r"(sel)
               : "memory");
}
__device__ __forceinline__ void lds128(uint32_t a, uint32_t& x, uint32_t& y, uint32_t& z, uint32_t& w) {
  asm volatile("ld.shared.v4.u32 {%0,%1,%2,%3}, [%4];" : "=r"(x), "=r"(y), "=r"(z), "=r"(w) : "r"(a) : "memory");
}

constexpr int PLANE = 2048 * 16;
constexpr int PL_CTX = 0, PL_KV = 32, PL_OA = PL_KV + 64, NPLANES = PL_OA + 8;
__device__ __align__(1024) uint4 g_scr[NPLANES * PLANE];
__device__ uint4 g_carry[16 * 128];
constexpr int F_CTX = 0, F_KV = 512, F_L = 1040, F_CAR = 1056, F_EPOCH = 1072, F_END = 1072 + 132;
__device__ uint32_t g_flags[F_END];

#define NTURN 256

enum { K_KV = 1, K_L = 2, K_T = 3, K_OA = 4, K_OB = 5, K_END = 7 };
constexpr int NCLUSTERS = 66, MAXITEMS = 16;
constexpr int A_STAGE = 16384, B_SLOT = 32768;
constexpr int SM_B = 6 * A_STAGE, SM_CARRY = SM_B + 4 * B_SLOT, SM_BAR = SM_CARRY + 2048, SM_TOTAL = SM_BAR + 512;

struct Params {
  CUtensorMap mapA[3];
  CUtensorMap mapB[6];
  CUtensorMap mapO[2];
  uint4* scr;
  uint4* carry;
  uint32_t* flags;
  const uint32_t* x;
  const uint16_t* wq;
  uint32_t zero;
  uint16_t sched[NCLUSTERS * MAXITEMS];
};

__device__ __forceinline__ bool item_narrow(uint32_t item) { return (item & 0x204) == 0x204 || (item & 7) == K_T; }
__device__ __forceinline__ int item_nk(uint32_t item) {
  const uint32_t kind = item & 7;
  return (kind == K_KV ? 8 : kind == K_OB ? 64 : 16) >> item_narrow(item);
}
__device__ __forceinline__ int item_row(uint32_t kind, int g, int pos) {
  if (kind == K_L || kind == K_OA) return g == 0 ? (pos - 1) * 1024 : 64 * (3 * g - 2 + pos + (g > 5));
  return 64 * (3 * g - 1 + pos);
}

__device__ __forceinline__ void wait_flag(const uint32_t* f, uint32_t target) {
  uint32_t it = 0;
#pragma unroll 1
  while (true) {
    uint32_t v;
    asm volatile("ld.acquire.gpu.global.u32 %0, [%1];" : "=r"(v) : "l"(f) : "memory");
    if ((int)(v - target) >= 0) break;
    __nanosleep(40);
    if (++it > (1u << 18)) break;
  }
  asm volatile("fence.proxy.async.global;" ::: "memory");
}
__device__ __forceinline__ uint32_t wait_bits(const uint32_t* f, uint32_t inv, uint32_t mask) {
  uint32_t it = 0, v;
#pragma unroll 1
  while (true) {
    asm volatile("ld.acquire.gpu.global.u32 %0, [%1];" : "=r"(v) : "l"(f) : "memory");
    v ^= inv;
    if (!(~v & mask)) break;
    __nanosleep(40);
    if (++it > (1u << 18)) break;
  }
  asm volatile("fence.proxy.async.global;" ::: "memory");
  return v;
}
__device__ __forceinline__ void red_add(uint32_t* f) { asm volatile("red.relaxed.gpu.global.add.u32 [%0], 1;" ::"l"(f) : "memory"); }
__device__ __forceinline__ void red_xor(uint32_t* f, uint32_t v) {
  asm volatile("red.relaxed.gpu.global.xor.b32 [%0], %1;" ::"l"(f), "r"(v) : "memory");
}

constexpr float QS = 0.08838834764831845f * 1.4426950408889634f;
__device__ __noinline__ void attn_fallback(uint4* q, const uint4* __restrict__ k, const uint32_t* __restrict__ x,
                                           const uint16_t* __restrict__ w, int row0, int lane) {
  const int g = lane >> 2, tq = lane & 3;
  q += row0 * 16;
  k += lane ^ (lane >> 3);
  const uint4* v = k + 2 * PLANE;
  float o[16][4];
#pragma unroll
  for (int i = 0; i < 16; i++) o[i][0] = o[i][1] = o[i][2] = o[i][3] = 0.f;
  x += (row0 + g) * 512 + tq;
  w += 2 * tq * 4096 + g;
#pragma unroll 1
  for (int k0 = 0; k0 < 64; k0++, x += 8, w += 16 * 4096) {
#pragma unroll
    for (int i = 0; i < 16; i++)
      mma_16816(o[i], x[0], x[4096], x[4], x[4100], w[8 * i] | w[4096 + 8 * i] << 16, w[8 * 4096 + 8 * i] | w[9 * 4096 + 8 * i] << 16);
  }
#pragma unroll
  for (int i = 0; i < 8; i++) {
    const int c = 4 * (i >> 1), e = 2 * (i & 1);
    __stcg(q + (i >> 1) * 32 + (i & 1) * 128 + (lane ^ (lane >> 3)),
           make_uint4(pack_bf16(o[c][e], o[c][e + 1]), pack_bf16(o[c + 1][e], o[c + 1][e + 1]),
                      pack_bf16(o[c + 2][e], o[c + 2][e + 1]), pack_bf16(o[c + 3][e], o[c + 3][e + 1])));
  }
  __syncwarp();
#pragma unroll
  for (int i = 0; i < 16; i++) o[i][0] = o[i][1] = o[i][2] = o[i][3] = 0.f;
  float m0 = -INFINITY, m1 = -INFINITY, l0 = 0.f, l1 = 0.f;
#pragma unroll 1
  for (int k0 = 0; k0 < row0 + 16; k0 += 16) {
    float sc[2][4] = {{0.f, 0.f, 0.f, 0.f}, {0.f, 0.f, 0.f, 0.f}};
#pragma unroll 1
    for (int cg = 0; cg < 4; cg++) {
      const uint4 qa = __ldcg(q + cg * 32 + (lane ^ (lane >> 3)));
      const uint4 qb = __ldcg(q + 128 + cg * 32 + (lane ^ (lane >> 3)));
#pragma unroll
      for (int t = 0; t < 2; t++) {
        const uint4 kk = __ldcg(k + (k0 + 8 * t) * 16 + cg * 32);
        mma_16816(sc[t], qa.x, qb.x, qa.y, qb.y, kk.x, kk.y);
        mma_16816(sc[t], qa.z, qb.z, qa.w, qb.w, kk.z, kk.w);
      }
    }
    float x0 = -INFINITY, x1 = -INFINITY;
#pragma unroll
    for (int t = 0; t < 2; t++) {
#pragma unroll
      for (int e = 0; e < 2; e++) {
        const int key = k0 + 8 * t + 2 * tq + e;
        if (key > row0 + g) sc[t][e] = -INFINITY;
        if (key > row0 + g + 8) sc[t][2 + e] = -INFINITY;
        x0 = fmaxf(x0, sc[t][e]);
        x1 = fmaxf(x1, sc[t][2 + e]);
      }
    }
    x0 = fmaxf(x0, __shfl_xor_sync(0xffffffffu, x0, 1));
    x1 = fmaxf(x1, __shfl_xor_sync(0xffffffffu, x1, 1));
    x0 = fmaxf(x0, __shfl_xor_sync(0xffffffffu, x0, 2));
    x1 = fmaxf(x1, __shfl_xor_sync(0xffffffffu, x1, 2));
    const float n0 = fmaxf(m0, x0), n1 = fmaxf(m1, x1);
    const float a0 = ex2(m0 - n0), a1 = ex2(m1 - n1);
    m0 = n0;
    m1 = n1;
    l0 *= a0;
    l1 *= a1;
    uint32_t pa[4];
#pragma unroll
    for (int t = 0; t < 2; t++) {
      const float e0 = ex2(sc[t][0] - m0), e1 = ex2(sc[t][1] - m0);
      const float e2 = ex2(sc[t][2] - m1), e3 = ex2(sc[t][3] - m1);
      l0 += e0 + e1;
      l1 += e2 + e3;
      pa[2 * t] = pack_bf16(e0, e1);
      pa[2 * t + 1] = pack_bf16(e2, e3);
    }
#pragma unroll
    for (int cg = 0; cg < 4; cg++) {
      const uint4 va = __ldcg(v + k0 * 16 + cg * 32);
      const uint4 vb = __ldcg(v + k0 * 16 + 128 + cg * 32);
#pragma unroll
      for (int r = 0; r < 4; r++) {
        const uint32_t w0 = r == 0 ? va.x : r == 1 ? va.y : r == 2 ? va.z : va.w;
        const uint32_t w1 = r == 0 ? vb.x : r == 1 ? vb.y : r == 2 ? vb.z : vb.w;
        float(&oo)[4] = o[4 * cg + r];
        oo[0] *= a0;
        oo[1] *= a0;
        oo[2] *= a1;
        oo[3] *= a1;
        mma_16816(oo, pa[0], pa[1], pa[2], pa[3], movm_t(w0), movm_t(w1));
      }
    }
  }
  l0 += __shfl_xor_sync(0xffffffffu, l0, 1);
  l1 += __shfl_xor_sync(0xffffffffu, l1, 1);
  l0 += __shfl_xor_sync(0xffffffffu, l0, 2);
  l1 += __shfl_xor_sync(0xffffffffu, l1, 2);
  const float i0 = 1.f / l0, i1 = 1.f / l1;
  __syncwarp();
  uint32_t* o0 = reinterpret_cast<uint32_t*>(q + g * 4) + tq;
#pragma unroll
  for (int i = 0; i < 16; i++) {
    uint32_t* d = o0 + (i >> 2) * 128 + ((i & 3) ^ (g >> 1)) * 4;
    d[0] = pack_bf16(o[i][0] * i0, o[i][1] * i0);
    d[512] = pack_bf16(o[i][2] * i1, o[i][3] * i1);
  }
}

#define KB_LIMIT 1.2089258e24f
#define KB_LOW 9.094947e-13f

__device__ __forceinline__ void local_scores(float (&s)[2][4], const uint32_t (&lo)[24], const uint32_t (&hi)[24], const uint32_t* k) {
#pragma unroll
  for (int h = 0; h < 2; h++) s[h][0] = s[h][1] = s[h][2] = s[h][3] = 0.f;
#pragma unroll
  for (int c = 0; c < 4; c += 2)
#pragma unroll
    for (int h = 0; h < 8; h += 4) mma_16816(s[h >> 2], lo[h + c], hi[h + c], lo[h + c + 1], hi[h + c + 1], k[h + c], k[h + c + 1]);
}
__device__ __forceinline__ void local_attn(float (&o)[2][4][4], float (&l)[2][4], const float (&s)[3][2][4], const uint32_t (&vt)[2][4][4],
                                           bool first, int lane) {
  const int g = lane >> 2, tq = lane & 3;
  const bool h0 = 2 * tq > g, h1 = 2 * tq + 1 > g;
  const uint32_t m = (h0 ? 0xFFFFu : 0u) | (h1 ? 0xFFFF0000u : 0u);
  float u0[2], u1[2], w0[2], w1[2], mu[2], mw[2];
#pragma unroll
  for (int h = 0; h < 2; h++) {
    u0[h] = h0 ? s[0][h][0] : s[1][h][0];
    u1[h] = h1 ? s[0][h][1] : s[1][h][1];
    w0[h] = h0 ? s[1][h][2] : s[2][h][2];
    w1[h] = h1 ? s[1][h][3] : s[2][h][3];
    if (first) {
      if (h0) u0[h] = -INFINITY;
      if (h1) u1[h] = -INFINITY;
    }
    mu[h] = fmaxf(u0[h], u1[h]);
    mw[h] = fmaxf(w0[h], w1[h]);
  }
#pragma unroll
  for (int o = 1; o <= 2; o++)
#pragma unroll
    for (int h = 0; h < 2; h++) {
      mw[h] = fmaxf(mw[h], __shfl_xor_sync(0xffffffffu, mw[h], o));
      mu[h] = fmaxf(mu[h], __shfl_xor_sync(0xffffffffu, mu[h], o));
    }
  const float c = 0.17677669529663687f * 1.4426950408889634f;
#pragma unroll
  for (int h = 0; h < 2; h++) {
    const uint32_t pu = pack_bf16(ex2((u0[h] - mu[h]) * c), ex2((u1[h] - mu[h]) * c));
    const uint32_t pw = pack_bf16(ex2((w0[h] - mw[h]) * c), ex2((w1[h] - mw[h]) * c));
    l[h][0] = l[h][1] = l[h][2] = l[h][3] = 0.f;
    mma_16816(l[h], 0x3F803F80, 0u, 0u, 0x3F803F80, pu, pw);
#pragma unroll
    for (int i = 0; i < 4; i++) {
      const uint32_t(&v)[4] = vt[i >> 1][2 * h + (i & 1)];
      o[h][i][0] = o[h][i][1] = o[h][i][2] = o[h][i][3] = 0.f;
      mma_16816(o[h][i], v[0], v[1], v[2], v[3], i < 2 ? pu & m : pw & ~m, i < 2 ? pu & ~m : pw & m);
    }
  }
}

__global__ __cluster_dims__(2, 1, 1) __launch_bounds__(512, 1) void fused_kernel(const __grid_constant__ Params p) {
  extern __shared__ __align__(1024) uint8_t smem_dyn[];
  DECLARE_READY();
  const uint32_t sbase = smem_u32(smem_dyn);
  const uint32_t afull0 = sbase + SM_BAR, aempty0 = afull0 + 48, bfull0 = afull0 + 96, bempty0 = afull0 + 128, carbar = afull0 + 160,
                 pub0 = afull0 + 200;
  const uint32_t bbase = sbase + SM_B;
  const int wg = __reduce_min_sync(0xffffffffu, (int)(threadIdx.x >> 7));
  const uint32_t rank = blockIdx.x & 1;
  const uint16_t* sched = p.sched + (blockIdx.x >> 1) * MAXITEMS;
  const uint32_t item0 = sched[0];

  auto fill_b = [&](uint32_t item, int t, uint32_t pb) {
    const uint32_t kind = item & 7, j = (item >> 7) & 15, sl = pb & 3;
    if (((item >> 3) & 15) == 0) mbar_arrive_n(bempty0 + 8 * sl, 1);
    mbar_expect_tx(bfull0 + 8 * sl, kind == K_L ? 24576 : 32768);
    const uint32_t nt = kind == K_KV ? j : 2 * j + rank, dst = bbase + sl * B_SLOT;
    const uint32_t cb = kind == K_T ? nt : item_narrow(item) ? nt - 8 : nt * 2 + (t >> 1 & 1);
    const uint32_t ks = item_narrow(item) ? t : (t >> 1 & ~1) + (t & 1);
    if (kind == K_OA) {
      tma_load_5d(dst, &p.mapB[K_OA], bfull0 + 8 * sl, cb * 128, ks * 4);
      tma_load_5d(dst + 16384, &p.mapB[K_OA], bfull0 + 8 * sl, cb * 128 + 64, ks * 4);
    } else if (kind == K_L) {
      tma_load_3d(dst, &p.mapB[K_L], bfull0 + 8 * sl, nt * 64, t * 64, 0);
    } else {
      tma_load_3d(dst, &p.mapB[kind == K_KV ? 1 - rank : kind], bfull0 + 8 * sl, 0, ks * 128, cb * 2);
    }
  };
  const bool local0 = (item0 & 7) == K_L;
  const int g0 = (item0 >> 3) & 15;
  auto first_a = [&](uint32_t u, bool mc) {
    const int row = item_row(local0 ? K_L : K_KV, g0, (u >> 1) + (g0 == 0));
    const int r = local0 ? row & 1023 : row, blk = (local0 ? (row >> 10) * 16 : 0) + 2 * (u & 1);
    mbar_expect_tx(afull0 + 8 * u, A_STAGE);
    if (mc) tma_load_3d_mc(sbase + u * A_STAGE + rank * 8192, &p.mapA[local0], afull0 + 8 * u, 0, r, blk + rank, (uint16_t)3);
    else
      for (int h = 0; h < 2; h++) tma_load_3d(sbase + u * A_STAGE + h * 8192, &p.mapA[local0], afull0 + 8 * u, 0, r, blk + h);
  };
  auto first_b = [&](uint32_t t) {
    const int j = (item0 >> 7) & 15;
    mbar_expect_tx(bfull0 + 8 * t, local0 ? 24576 : 32768);
    tma_load_3d(bbase + t * B_SLOT, &p.mapB[local0 ? K_L : 1 - rank], bfull0 + 8 * t, local0 ? (2 * j + rank) * 64 : 0,
                local0 ? t * 64 : (t & 1) * 128, local0 ? 0 : 4 * j + (t & 2));
    if (g0 == 0) mbar_arrive_n(bempty0 + 8 * t, 1);
  };
  if (threadIdx.x == 0) {
    mbar_init(bfull0, 1);
    mbar_init(bempty0, 3);
    asm volatile("fence.proxy.async.shared::cta;" ::: "memory");
    first_b(0);
  } else if (threadIdx.x == 32) {
    mbar_init(afull0, 1);
    asm volatile("fence.proxy.async.shared::cta;" ::: "memory");
    first_a(0, false);
    asm volatile("fence.mbarrier_init.release.cluster;" ::: "memory");
  } else if (threadIdx.x == 64) {
    for (int i = 20; i < 25 + MAXITEMS; i++) mbar_init(afull0 + 8 * i, i < 25 ? 1 : 12);
  } else if (threadIdx.x == 96) {
    for (int i = 1; i < 20; i++)
      if (i != 12 && i != 16) mbar_init(afull0 + 8 * i, i < 6 ? 1 : i < 12 ? 2 : i < 16 ? 1 : 3);
    asm volatile("fence.proxy.async.shared::cta;\nfence.mbarrier_init.release.cluster;" ::: "memory");
  }
  __syncthreads();
  asm volatile("barrier.cluster.arrive.relaxed.aligned;\nbarrier.cluster.wait.aligned;" ::: "memory");

  if (wg == 0) {
    asm volatile("setmaxnreg.dec.sync.aligned.u32 32;");
    if (threadIdx.x == 96) {
#pragma unroll 1
      for (uint32_t x = local0 ? 0x6B42A593u : 0xB6A45239u; x; x >>= 4) {
        if (x & 8) first_b(x & 3);
        else if (g0 != 0 || (x & 7) < 5) first_a((x & 7) - 1, true);
      }
    }
    if (__reduce_min_sync(0xffffffffu, (int)(threadIdx.x >> 5)) == 1) {
      const uint32_t e = __ldcg(p.flags + F_EPOCH + blockIdx.x) + 1;
      const uint32_t w = threadIdx.x - 32;
      uint32_t n = w < 2 || ((sched[0] >> 3) & 15) != 0 ? 2 : 0;
      uint32_t bar0 = afull0 + 16 * w, dst0 = sbase + w * (2 * A_STAGE) + rank * 8192;
      asm volatile("" : "+r"(bar0), "+r"(dst0));
      uint32_t bar, dst, par, prev = 0;
      auto position = [&]() {
        bar = bar0 + 8 * (n & 1), dst = dst0 + (n & 1) * A_STAGE, par = (~n >> 1) & 1;
        asm volatile("" : "+r"(bar), "+r"(dst), "+r"(par));
      };
      position();
      for (int it = 0; it < MAXITEMS; it++) {
        const uint32_t item = sched[it];
        const uint32_t kind = item & 7;
        if (kind == K_END) break;
        const int g = (item >> 3) & 15;
        const int nd = kind == K_T ? 8 : item_nk(kind) >> 1;
        if (kind == K_OA) wait_flag(p.flags + F_L + g, 16 * e);
        int rho = w + (item >> 11);
        if (rho >= 3) rho -= 3;
        const int row = item_row(kind, g, kind == K_T ? 2 - rho : rho + (g == 0));
        const uint32_t on = w > 2 || (g == 0 && rho == 2) ? 0 : ~0u, swap = rho == 1 ? 0 : on, base = (0x924924 >> rho) & on;
        uint32_t m = base ^ (swap & (kind == K_L ? 0xB6DB6D : (item_narrow(item) ? (prev == K_KV ? 1 : 0x6D) : prev == K_KV ? 0x861861 : 0x86186D)));
        prev = kind;
        auto step = [&](auto load) {
          if (m & 1) {
            mbar_wait(bar + 48, par);
            mbar_expect_tx(bar, A_STAGE);
            load();
            n++;
            position();
          }
          m >>= 1;
          __syncwarp();
        };
        if (kind >= K_OA) {
          const uint4* src = p.scr + (kind == K_OA ? PL_OA : PL_CTX) * PLANE + row * 16 + rank * 512;
          uint32_t heads = kind == K_OA ? ~0u : 0, need = 1;
          for (int t = 0; t <= nd; t++, need <<= 1) {
            if (~heads & need) heads = wait_bits(p.flags + F_CTX + g * 32, (e & 1) - 1, need);
            if (item_narrow(item) && t > 2) m = (base >> 2) ^ (t == nd ? swap : 0);
#pragma unroll 1
            for (int x = t == 0; x < (t == nd ? 1 : 3); x++)
              step([&]() {
                bulk_load_mc(dst, src, 8192, bar, (uint16_t)3);
                src += PLANE;
              });
          }
        } else {
          const int r = kind == K_L ? row & 1023 : row;
          int blk = (kind == K_L ? (row >> 10) * 16 : 0) + rank;
          if (kind == K_T) m ^= swap & 0x800000;
          if (it == 0) m &= m - 1, m &= m - 1, blk += 4;
#pragma unroll 1
          for (int x = 3 * nd; x; x--)
            step([&]() {
              tma_load_3d_mc(dst, &p.mapA[kind - 1], bar, 0, r, blk, (uint16_t)3);
              blk += 2;
            });
        }
      }
      if (w < 3) {
        mbar_wait(bar0 + 48, (~(n + 1) >> 1) & 1);
        mbar_wait(bar0 + 56, (~n >> 1) & 1);
      }
    } else if (threadIdx.x == 0) {
      const uint32_t e = __ldcg(p.flags + F_EPOCH + blockIdx.x) + 1;
      uint32_t pb = 4;
      for (int it = 0; it < MAXITEMS; it++) {
        const uint32_t item = sched[it];
        const uint32_t kind = item & 7;
        if (kind == K_END) break;
        const int nk = item_nk(item);
        uint32_t heads = 0;
        for (int t = it == 0 ? 4 : 0; t < nk; t++, pb++) {
          mbar_wait(bempty0 + 8 * (pb & 3), ((pb >> 2) & 1) ^ 1);
          fill_b(item, t, pb);
          if (item_narrow(item) && kind == K_OB) {
            const uint32_t g = (item >> 3) & 15, nb = g ? 3 : 2;
            if (!(heads >> t & 2)) heads = wait_bits(p.flags + F_CTX + g * 32, (e & 1) - 1, 0);
            if (heads >> t & 2) prefetch_l2(p.scr + (PL_CTX + t + 1) * PLANE + (3 * g + 2 - nb) * 1024 + rank * nb * 512, nb * 8192);
          }
        }
        if (kind == K_T) {
          const int g = (item >> 3) & 15, j = (item >> 7) & 15;
          const uint4* src = p.scr + (PL_KV + j * 4 + rank) * PLANE;
          const int n = ((3 * g + 1) >> 1) + 1;
          uint32_t groups = 0;
          for (int t = 0; t < n; t++, src += 2048) {
            const uint32_t need = (4u << 2 * min((2 * t + 2) / 3, g)) - 1;
            if (~groups & need) groups = wait_bits(p.flags + F_KV + j * 32, (e & 1) - 1, need);
            const uint32_t nskip = t == n - 1 ? 1 + (g & 1) : 0;
            uint32_t sl = pb & 3;
            mbar_wait(bempty0 + 8 * sl, ((pb >> 2) & 1) ^ 1);
            if (nskip) mbar_arrive_n(bempty0 + 8 * sl, nskip);
            mbar_expect_tx(bfull0 + 8 * sl, 32768);
            pb++;
            if (nskip == 2) {
              bulk_load(bbase + sl * B_SLOT, src, 16384, bfull0 + 8 * sl);
              bulk_load(bbase + sl * B_SLOT + 16384, src + 2 * PLANE, 16384, bfull0 + 8 * sl);
              continue;
            }
            bulk_load(bbase + sl * B_SLOT, src, 32768, bfull0 + 8 * sl);
            sl = pb & 3;
            mbar_wait(bempty0 + 8 * sl, ((pb >> 2) & 1) ^ 1);
            if (nskip) mbar_arrive_n(bempty0 + 8 * sl, nskip);
            mbar_expect_tx(bfull0 + 8 * sl, 32768);
            bulk_load(bbase + sl * B_SLOT, src + 2 * PLANE, 32768, bfull0 + 8 * sl);
            pb++;
          }
        }
      }
    } else if (threadIdx.x == 64) {
      const uint32_t pair = 2 * ((sched[0] >> 7) & 15) + rank;
      if ((sched[0] & 127) == K_L) {
        mbar_wait(carbar + 24, 0);
        asm volatile("fence.proxy.async.shared::cta;\ncp.async.bulk.global.shared::cta.bulk_group [%0], [%1], 2048;\n"
                     "cp.async.bulk.commit_group;\ncp.async.bulk.wait_group 0;\nfence.proxy.async.global;\nfence.acq_rel.gpu;" ::"l"(p.carry + pair * 128),
                     "r"(sbase + SM_CARRY - 2048)
                     : "memory");
        red_add(p.flags + F_CAR + pair);
      }
      if ((sched[0] & 127) == (K_L | 6 << 3)) {
        wait_flag(p.flags + F_CAR + pair, __ldcg(p.flags + F_EPOCH + blockIdx.x) + 1);
        mbar_expect_tx(carbar + 32, 2048);
        bulk_load(sbase + SM_CARRY, p.carry + pair * 128, 2048, carbar + 32);
      }
      for (int it = 0; it < MAXITEMS; it++) {
        const uint32_t item = sched[it];
        const uint32_t kind = item & 7;
        const int g = (item >> 3) & 15, j = (item >> 7) & 15;
        mbar_wait(pub0 + 8 * (kind == K_END ? MAXITEMS - 1 : it), 0);
        if (kind == K_END) break;
        if (kind >= K_OA) continue;
        asm volatile("fence.acq_rel.gpu;" ::: "memory");
        if (kind == K_KV) red_xor(p.flags + F_KV + j * 32, 1u << (2 * g + rank));
        if (kind == K_L) red_add(p.flags + F_L + g);
        if (kind == K_T) red_xor(p.flags + F_CTX + g * 32, 1u << (2 * j + rank));
      }
      red_add(p.flags + F_EPOCH + blockIdx.x);
    } else if (threadIdx.x == 96) {
      for (int i = 0; i < 3; i++) prefetch_tmap(&p.mapA[i]);
      for (int i = 0; i < 6; i++) prefetch_tmap(&p.mapB[i]);
      prefetch_tmap(&p.mapO[0]);
      prefetch_tmap(&p.mapO[1]);
    }
  } else {
    asm volatile("setmaxnreg.inc.sync.aligned.u32 160;");
    const int cw = wg - 1;
    const int wq = __reduce_min_sync(0xffffffffu, (int)((threadIdx.x >> 5) & 3));
    auto turn = [&](uint32_t dep = 0) {
      bar_sync((1 + cw) | dep, NTURN);
    };
    const int fwd = cw == 0 ? 3 : cw, back = cw == 2 ? 1 : cw + 2;
    int next = fwd;
    auto pass = [&]() {
      bar_arrive(next, NTURN);
      next = fwd;
    };
    auto rank_of = [&](uint32_t item) {
      const int r = cw + (item >> 11);
      return r >= 3 ? r - 3 : r;
    };
    if (cw == 1) pass();
    if (cw == 2) { turn(); pass(); }
    const uint32_t abase = sbase + cw * (2 * A_STAGE), afull = afull0 + 16 * cw, aempty = aempty0 + 16 * cw;
    const uint32_t adesc = ((abase & 0x3FFFF) >> 4) | (1u << 16), bdesc = (bbase & 0x3FFFF) >> 4;
    uint32_t pa = 0, pb = 0;
    int it = 0;
    uint32_t item = sched[0];
    auto publish = [&](int i, uint32_t skip = 0) {
      __syncwarp();
      mbar_arrive_if0(pub0 + 8 * i, (threadIdx.x & 31) | skip);
    };
    auto test_ab = [&](uint32_t a, uint32_t b) {
      test_a(afull + 8 * (a & 1), (a >> 1) & 1);
      test_b(bfull0 + 8 * (b & 3), (b >> 2) & 1);
    };
    auto wait_ab = [&]() {
      if (!ready_ab()) {
        mbar_wait_u(afull + 8 * (pa & 1), (pa >> 1) & 1);
        mbar_wait_u(bfull0 + 8 * (pb & 3), (pb >> 2) & 1);
      }
    };
    auto release_ab = [&](uint32_t a, uint32_t b, uint32_t skip) {
      mbar_arrive_cta_if0(wq < 2 ? aempty + 8 * (a & 1) : bempty0 + 8 * (b & 3), wq < 2 ? wq : rank, (threadIdx.x & 31) | (wq == 3) | skip);
    };
    test_ab(0, 0);
    enum { NEW = 1, REL = 2, FWD = 4, TEST = 8, BACK = 16 };
    auto gturn = [&](auto mode_c, bool hold, auto mma, auto meanwhile) {
      constexpr int MODE = decltype(mode_c)::value;
      const uint32_t da = adesc + (pa & 1) * (A_STAGE >> 4), db = bdesc + (pb & 3) * (B_SLOT >> 4);
      if (MODE & NEW) wait_ab();
      else if (!ready_b()) mbar_wait_u(bfull0 + 8 * (pb & 3), (pb >> 2) & 1);
      turn();
      wg_fence();
      mma(da, db);
      wg_commit();
      if (!hold) pass();
      if (hold) {
      } else if (MODE & TEST) test_ab(pa + 1, pb + 1);
      else test_b(bfull0 + 8 * ((pb + 1) & 3), ((pb + 1) >> 2) & 1);
      meanwhile();
      wg_wait<0>();
      if (MODE & REL) {
        if (!hold) release_ab(pa, pb, 0);
      } else {
        mbar_arrive_if0(bempty0 + 8 * (pb & 3), threadIdx.x & 127);
      }
      if (MODE & FWD) pa++;
      if (MODE & BACK) pa--;
      __syncwarp();
      pb++;
    };
    constexpr std::true_type YES{};
    constexpr std::false_type NO{};
    constexpr std::integral_constant<int, NEW> FIRST{};
    constexpr std::integral_constant<int, REL | FWD | TEST> SECOND{};
    constexpr std::integral_constant<int, NEW | REL | FWD | TEST> ONCE{};
    constexpr std::integral_constant<int, NEW | FWD | TEST> X0{};
    constexpr std::integral_constant<int, NEW | BACK> X1{};
    constexpr std::integral_constant<int, REL | FWD> Y0{};
    auto nothing = []() {};
    auto idle = [&]() { return ((item >> 3) & 15) == 0 && rank_of(item) == 2; };
    auto skip_item = [&](int passed) {
      const int n = (item & 7) == K_T ? 10 : item_nk(item);
      publish(it);
#pragma unroll 1
      for (int i = 2 + passed; i < n; i++) {
        turn();
        pass();
      }
      pb += n;
      test_ab(pa, pb);
      item = sched[++it];
    };

    if ((item & 7) == K_L && idle()) skip_item(0);
    float lo_[2][4][4] = {}, ll[2][4] = {};
    uint4* ldst = p.scr;
    uint32_t lnone = 1;
    auto lrelease = [&]() { release_ab(1, 3, lnone); };
    auto lflush = [&]() {
      const uint32_t t = sched_fence() & p.zero;
#pragma unroll
      for (int i = 0; i < 4; i++) {
        const int h = i >> 1, e = i & 1 ? 2 : 0;
        const float f0 = rcp(__uint_as_float(__float_as_uint(ll[h][e]) | t)), f1 = rcp(__uint_as_float(__float_as_uint(ll[h][e + 1]) | t));
        const float(&r0)[4] = lo_[h][e], (&r1)[4] = lo_[h][e + 1];
        stg128_if0(ldst + h * 32 + e * 64, movm_t(pack_bf16(r0[0] * f0, r0[1] * f1)), movm_t(pack_bf16(r0[2] * f0, r0[3] * f1)),
                   movm_t(pack_bf16(r1[0] * f0, r1[1] * f1)), movm_t(pack_bf16(r1[2] * f0, r1[3] * f1)), lnone);
      }
      publish(it - 1, lnone);
    };
    while ((item & 7) == K_L) {
      const int g = (item >> 3) & 15, j = (item >> 7) & 15;
      const int rho = rank_of(item);
      float acc[96];
      auto mma = [&](int kb, bool first) {
        return [&acc, kb, first](uint32_t da, uint32_t db) {
#pragma unroll
          for (int k = 0; k < 4; k++) wgmma_n192_tb(acc, da + kb * 512 + k * 2, (db | (512u << 16)) + k * 128, !(first && k == 0));
        };
      };
      gturn(FIRST, false, mma(0, true), lrelease);
      gturn(SECOND, false, mma(1, false), lflush);
#pragma unroll 1
      for (int d = 7;;) {
        gturn(FIRST, false, mma(0, false), nothing);
        if (--d == 0) break;
        gturn(SECOND, false, mma(1, false), nothing);
      }
      const int lane = threadIdx.x & 31;
      const int from = rho ? rho : 4 * (~g & 1), to = g == 0 ? 3 * rho : rho == 2 ? 4 * (g & 1) : rho + 1;
      uint32_t own, front, vlo;
      gturn(SECOND, true, mma(1, false), [&]() {
        bar_arrive_if(rho != 2, g && rho ? back : next, NTURN);
        own = (wq < 3 ? abase + A_STAGE + wq * 2048 : sbase + SM_CARRY - 8192 + to * 2048) + lane * 16;
        front = (wq > 0 ? abase + A_STAGE + wq * 2048 - 2048 : g == 0 ? abase + A_STAGE : sbase + SM_CARRY - 8192 + from * 2048) + lane * 16;
        vlo = abase + A_STAGE + 8192 + wq * 1024 + lane * 16;
        ldst = p.scr + (PL_OA + j) * PLANE + (item_row(K_L, g, rho + (g == 0)) + wq * 16) * 16 + rank * 64 + (lane ^ (lane >> 3));
        asm volatile("" : "+r"(own), "+r"(front), "+r"(vlo), "+l"(ldst));
        lnone = 0;
        item = sched[++it];
        if (wq == 0 && g != 0) mbar_wait_u(carbar + 8 * from, ((g - (g <= 5 ? 1 : 6)) >> (rho == 0)) & 1);
      });
      if (g && rho == 0) next = back;
      fence_regs(acc);
      uint32_t lo[24], hi[24], hk[8], vt[2][4][4];
#pragma unroll
      for (int i = 0; i < 24; i++) {
        lo[i] = pack_bf16(acc[4 * i], acc[4 * i + 1]);
        hi[i] = pack_bf16(acc[4 * i + 2], acc[4 * i + 3]);
      }
      sts128(own, hi[8], hi[9], hi[10], hi[11]);
      sts128(own + 512, hi[12], hi[13], hi[14], hi[15]);
      stsm4(own + 1024, hi[16], hi[17], hi[18], hi[19]);
      stsm4(own + 1536, hi[20], hi[21], hi[22], hi[23]);
      __syncwarp();
      mbar_arrive_if0(carbar + 8 * to, lane | (wq ^ 3));
      stsm4(vlo, lo[16], lo[17], lo[18], lo[19]);
      stsm4(vlo + 512, lo[20], lo[21], lo[22], lo[23]);
      bar_sync(4 + cw, 128);
      lds128(front, hk[0], hk[1], hk[2], hk[3]);
      lds128(front + 512, hk[4], hk[5], hk[6], hk[7]);
#pragma unroll
      for (int i = 0; i < 8; i++) ldsm4_t((lane < 16 ? (i < 4 ? front : own) + 1024 : vlo - 256) + (i & 3) * 256, vt[i >> 2][i & 3]);
      float sc[3][2][4];
      local_scores(sc[2], lo, hi, hi + 8);
      local_scores(sc[1], lo, hi, lo + 8);
      local_scores(sc[0], lo, hi, hk);
      test_ab(pa, pb);
      local_attn(lo_, ll, sc, vt, g == 0 && wq == 0, lane);
      bar_arrive_if(rho == 2, back, NTURN);
    }
    if (!lnone) {
      bar_sync(4 + cw, 128);
      lrelease();
      lflush();
    }

    float Y[64];
    float sc0 = 0.f, sc1 = 0.f;
    uint32_t done;
    uint4* pdst;
    auto pack = [&](uint32_t (&r)[16], const float (&acc)[64], int h, float s0, float s1) {
#pragma unroll
      for (int i = 0; i < 8; i++) {
        const int c = 32 * h + 4 * i;
        r[8 * (i >> 2) + (i & 3)] = pack_bf16(acc[c] * s0, acc[c + 1] * s0);
        r[8 * (i >> 2) + (i & 3) + 4] = pack_bf16(acc[c + 2] * s1, acc[c + 3] * s1);
      }
    };
    auto pack_now = [&](uint32_t (&r)[16], const float (&acc)[64], int h) {
      pack(r, acc, h, sc0, sc1);
#pragma unroll
      for (int i = 0; i < 16; i++) asm volatile("" : "+r"(r[i])::"memory");
    };
    auto stores = [&](uint4* dst, const uint32_t (&r)[16], int h, uint32_t skip) {
#pragma unroll
      for (int i = 0; i < 4; i++)
        stg128_if0(dst + h * 64 + (i >> 1) * 32 + (i & 1) * 128, r[4 * i], r[4 * i + 1], r[4 * i + 2], r[4 * i + 3], skip);
    };
    auto flush = [&]() {
      uint32_t r[16];
#pragma unroll
      for (int h = 0; h < 2; h++) {
        turn();
        pass();
        pack(r, Y, h, sc0, sc1);
        stores(pdst, r, h, done);
      }
      publish(it - 1, done);
    };
    auto no_pending = [&]() {
      done = 1;
      pdst = p.scr;
#pragma unroll
      for (int i = 0; i < 64; i++) Y[i] = 0.f;
    };
    no_pending();
    auto mma128 = [&](auto scr_c, float (&acc)[64], int keep) {
      return [&acc, keep](uint32_t da, uint32_t db) {
        constexpr bool SCR = decltype(scr_c)::value;
#pragma unroll
        for (int k = 0; k < 8; k++)
          wgmma_n128<1>(acc, da + (k & 1) * 2 + ((k >> 1) & 1) * (SCR ? 32 : 4) + (k >> 2) * (SCR ? 64 : 512), SCR ? HI64 : HI128,
                        (db | (1024u << 16)) + k * 128, HI128, k != 0 || keep);
      };
    };
    auto first_two = [&](auto mode0, auto mode1, auto scr_c, float (&X)[64]) {
      uint32_t r0[16], r1[16];
      gturn(mode0, false, mma128(scr_c, X, false), [&]() { pack_now(r0, Y, 0); });
      stores(pdst, r0, 0, done);
      gturn(mode1, false, mma128(scr_c, X, true), [&]() { pack_now(r1, Y, 1); });
      stores(pdst, r1, 1, done);
      publish(it - 1, done);
    };
    auto all_but_last_two = [&](auto scr_c, float (&X)[64]) {
      int n = item_nk(item);
      first_two(X0, X1, scr_c, X);
      gturn(Y0, false, mma128(scr_c, Y, false), nothing);
#pragma unroll 1
      while (true) {
        gturn(SECOND, false, mma128(scr_c, Y, true), nothing);
        gturn(X0, false, mma128(scr_c, X, true), nothing);
        gturn(X1, false, mma128(scr_c, X, true), nothing);
        if (!decltype(scr_c)::value || (n -= 4) == 4) break;
        gturn(Y0, false, mma128(scr_c, Y, true), nothing);
      }
      fence_regs(X);
    };
    while ((item & 7) < K_OA) {
      if (idle()) {
        flush();
        done = 1;
        skip_item(2);
        continue;
      }
      const uint32_t kind = item & 7;
      const int g = (item >> 3) & 15, j = (item >> 7) & 15;
      const int rho = rank_of(item);
      if (kind != K_T) {
        float X[64];
        all_but_last_two(NO, X);
        const int lane = threadIdx.x & 31;
        const int row = item_row(K_KV, g, rho + (g == 0)) + wq * 16;
        sc0 = sc1 = rank ? 1.f : QS;
        pdst = p.scr + (PL_KV + j * 4 + rank * 2 + 1) * PLANE + row * 16 + (lane ^ (lane >> 3));
        uint32_t r0[16], r1[16];
        pack(r0, X, 0, sc0, sc1);
        stores(pdst - PLANE, r0, 0, 0);
        gturn(Y0, false, mma128(NO, Y, true), [&]() { pack_now(r1, X, 1); });
        stores(pdst - PLANE, r1, 1, 0);
        item = sched[++it];
        gturn(SECOND, false, mma128(NO, Y, true), nothing);
        test_ab(pa, pb);
        fence_regs(Y);
        done = 0;
      } else {
        float(&O)[64] = Y;
        float S[64];
        float l0 = 0.f, l1 = 0.f;
        float zlim;
        const uint32_t sel = threadIdx.x & 127;
        const int b = 3 * g + 1 - rho;
        first_two(ONCE, ONCE, NO, S);
#pragma unroll 1
        for (int n = 0; n < 5; n++) gturn(ONCE, false, mma128(NO, S, true), nothing);
#pragma unroll
        for (int i = 0; i < 64; i++) O[i] = 0.f;
        fence_regs(O);
        gturn(FIRST, false, mma128(NO, S, true), nothing);
        fence_regs(S);
        {
          const uint32_t lane = threadIdx.x & 31, dst = abase + (pa & 1) * A_STAGE + wq * 2048 + (lane ^ (lane >> 3)) * 16;
#pragma unroll
          for (int h = 0; h < 2; h++) {
            uint32_t r[16];
            pack(r, S, h, 1.f, 1.f);
#pragma unroll
            for (int i = 0; i < 4; i++) {
              sts128(dst + h * 8192 + (i >> 1) * 512 + (i & 1) * 1024, r[4 * i], r[4 * i + 1], r[4 * i + 2], r[4 * i + 3]);
              if (4 * h + i < 7) __nanosleep(30);
            }
          }
          asm volatile("fence.proxy.async.shared::cta;" ::: "memory");
        }
        enum { MID, LAST, HALF };
        auto round = [&](auto mode_c) {
          constexpr int MODE = decltype(mode_c)::value;
          constexpr bool INIT = MODE == LAST;
          constexpr int NI = MODE == HALF ? 8 : 16;
          const uint32_t shared = MODE == HALF ? rho == 0 : 0;
          const uint32_t tv = pb + 1 - shared;
          {
            const uint32_t dq = adesc + (pa & 1) * (A_STAGE >> 4);
            const uint32_t dk = (bdesc + (pb & 3) * 2048) | (1u << 16);
            if (INIT) {
              const int lane = threadIdx.x & 31;
              const int row = (wq * 16 + (lane >> 2) - 2 * (lane & 3) + 11) << 23;
              const int r0 = row ^ (__float_as_uint(l0) & p.zero & (MODE + 16)), r1 = row ^ (__float_as_uint(l1) & p.zero & (MODE + 16));
#pragma unroll
              for (int i = 0; i < 4 * NI; i++) {
                const int c = i - 4 * (NI - 8);
                S[i] = c < 0 ? 0.f : __int_as_float((c & 2 ? r1 : r0) + ((4 * (c & 2) - 2 * (c & ~3) - (c & 1) - 11) << 23));
                asm volatile("" : "+f"(S[i])::"memory");
              }
            }
            if (!ready_b()) mbar_wait_u(bfull0 + 8 * (pb & 3), (pb >> 2) & 1);
            turn();
            wg_fence();
#pragma unroll
            for (int k = 0; k < 8; k++) {
              const uint32_t da = dq + (k >> 2) * 512 + (k & 2) * 16 + (k & 1) * 2, db = dk + (k >> 1) * 32 + (k & 1) * 2;
              if (MODE == HALF) wgmma_n64(S, da, db, k != 0 || INIT);
              else wgmma_n128<0>(S, da, HIQ, db, HI64, k != 0 || INIT);
            }
            wg_commit();
            pass();
          }
          test_b(bfull0 + 8 * (tv & 3), (tv >> 2) & 1);
          if (!ready_b()) mbar_wait_u(bfull0 + 8 * (tv & 3), (tv >> 2) & 1);
          wg_wait<0>();
#pragma unroll
          for (int i = 0; i < 4 * NI; i++) asm volatile("" : "+f"(S[i])::"memory");
          mbar_arrive_if0(bempty0 + 8 * (pb & 3), sel | shared);
          if (MODE >= LAST) mbar_arrive_cta_if0(aempty + 8 * (pa & 1), wq & 1, (sel & 31) | (wq >> 1));
          uint32_t P[2 * NI];
          if (MODE >= LAST && !INIT) {
            const int lane = threadIdx.x & 31;
            const int row = wq * 16 + (lane >> 2) - 2 * (lane & 3);
#pragma unroll
            for (int i = 0; i < 8; i++) {
#pragma unroll
              for (int e = 0; e < 2; e++) {
                if (8 * i + e > row) S[4 * (NI - 8 + i) + e] = -INFINITY;
                if (8 * i + e > row + 8) S[4 * (NI - 8 + i) + 2 + e] = -INFINITY;
              }
            }
          }
          float s0 = 0.f, s1 = 0.f, t0 = 0.f, t1 = 0.f;
#pragma unroll
          for (int i = 0; i < NI; i++) {
#pragma unroll
            for (int e = 0; e < 4; e++) S[4 * i + e] = ex2(S[4 * i + e]);
            s0 += S[4 * i];
            t0 += S[4 * i + 1];
            s1 += S[4 * i + 2];
            t1 += S[4 * i + 3];
            P[2 * i] = pack_bf16(S[4 * i], S[4 * i + 1]);
            P[2 * i + 1] = pack_bf16(S[4 * i + 2], S[4 * i + 3]);
          }
          l0 += s0 + t0;
          l1 += s1 + t1;
          uint32_t dep = (__float_as_uint(l0) ^ __float_as_uint(l1)) ^ P[2 * NI - 1];
          fence_regs(O);
#pragma unroll
          for (int i = 0; i < 2 * NI; i++) asm volatile("" : "+r"(P[i])::"memory");
          turn(dep & p.zero);
          wg_fence();
          const uint32_t dv = (bdesc + (tv & 3) * 2048 + shared * 1024) | (32u << 16);
#pragma unroll
          for (int k = 0; k < NI / 2; k++)
            wgmma_n128_rs_tb(O, P[4 * k], P[4 * k + 1], P[4 * k + 2], P[4 * k + 3], dv + k * 256, 1);
          wg_commit();
          pass();
          pb = tv + 1;
          if (MODE >= LAST) {
            const int nskip = 1 + (g & 1);
            if (rho + nskip >= 3) pb += 3 - nskip;
            pa++;
          } else {
            test_b(bfull0 + 8 * (pb & 3), (pb >> 2) & 1);
          }
          if (MODE >= LAST) {
            l0 += __shfl_xor_sync(0xffffffffu, l0, 1);
            l1 += __shfl_xor_sync(0xffffffffu, l1, 1);
            l0 += __shfl_xor_sync(0xffffffffu, l0, 2);
            l1 += __shfl_xor_sync(0xffffffffu, l1, 2);
            sc0 = rcp(l0);
            sc1 = rcp(l1);
            zlim = l0 <= KB_LIMIT && l0 >= KB_LOW && l1 <= KB_LIMIT && l1 >= KB_LOW ? 3e38f : -1.f;
          }
          wg_wait<0>();
          fence_regs(O);
          mbar_arrive_if0(bempty0 + 8 * (tv & 3), sel);
        };
#pragma unroll 1
        for (int n = b >> 1; n; n--) round(std::integral_constant<int, MID>{});
        item = sched[++it];
        if (b & 1) round(std::integral_constant<int, LAST>{});
        else round(std::integral_constant<int, HALF>{});
        test_ab(pa, pb);
        float z[4] = {0.f, 0.f, 0.f, 0.f};
#pragma unroll
        for (int i = 0; i < 32; i++) z[i & 3] = fmaf(O[2 * i], O[2 * i + 1], z[i & 3]);
        const bool bad = !(fabsf(z[0]) + fabsf(z[1]) + fabsf(z[2]) + fabsf(z[3]) <= zlim);
        const int lane = threadIdx.x & 31;
        pdst = p.scr + (PL_CTX + 2 * j + rank) * PLANE + (b * 64 + wq * 16) * 16 + (lane ^ (lane >> 3));
        done = 0;
        if (__any_sync(0xffffffffu, bad)) {
          attn_fallback(p.scr + (PL_CTX + 2 * j + rank) * PLANE, p.scr + (PL_KV + j * 4 + rank) * PLANE, p.x,
                        p.wq + (2 * j + rank) * 128, b * 64 + wq * 16, threadIdx.x & 31);
          publish(it - 1);
          no_pending();
          test_ab(pa, pb);
        }
      }
    }

    bool relay = true;
    if (idle()) {
      flush();
      skip_item(2);
    } else {
      const uint32_t kind = item & 7;
      const int g = (item >> 3) & 15, j = (item >> 7) & 15;
      const int row = item_row(kind, g, rank_of(item) + (g == 0)) + wq * 16;
      auto epilogue = [&](float (&acc)[64], int cb, bool pace) {
        const int lane = threadIdx.x & 31;
        const uint32_t stg = abase + ((pa - 1) & 1) * A_STAGE + wq * 4096;
        const int srow = lane & 15;
#pragma unroll
        for (int jj = 0; jj < 8; jj++) {
          const uint32_t r0 = pack_bf16(acc[8 * jj + 0], acc[8 * jj + 1]);
          const uint32_t r1 = pack_bf16(acc[8 * jj + 2], acc[8 * jj + 3]);
          const uint32_t r2 = pack_bf16(acc[8 * jj + 4], acc[8 * jj + 5]);
          const uint32_t r3 = pack_bf16(acc[8 * jj + 6], acc[8 * jj + 7]);
          const int chunk = (2 * jj + (lane >> 4)) & 7;
          const uint32_t addr = stg + (jj >> 2) * 2048 + srow * 128 + ((chunk ^ (srow & 7)) << 4);
          asm volatile("stmatrix.sync.aligned.m8n8.x4.shared.b16 [%0], {%1,%2,%3,%4};" ::"r"(addr), "r"(r0), "r"(r1), "r"(r2), "r"(r3)
                       : "memory");
          if (jj < 7 && pace) __nanosleep(30);
        }
        asm volatile("fence.proxy.async.shared::cta;" ::: "memory");
        __syncwarp();
        if (lane == 0) {
          const int col = cb * 128 + (kind == K_OA ? (row >> 10) * 2048 : 1024);
          const int r = kind == K_OA ? row & 1023 : row;
          tma_store_2d(&p.mapO[kind - K_OA], stg, col, r);
          tma_store_2d(&p.mapO[kind - K_OA], stg + 2048, col + 64, r);
          asm volatile("cp.async.bulk.commit_group;" ::: "memory");
        }
      };
      float X[64];
      relay = g == 0;
      const int last = g && rank_of(item) == 1 ? back : fwd;
      if (item_narrow(item)) {
        int n = item_nk(item);
        first_two(ONCE, ONCE, YES, X);
#pragma unroll 1
        while (--n > 1) {
          if (n == 2) next = last;
          gturn(ONCE, false, mma128(YES, X, true), nothing);
        }
        fence_regs(X);
        epilogue(X, 2 * j + rank - 8, rank_of(item) == 0);
      } else {
        all_but_last_two(YES, X);
        gturn(Y0, false, mma128(YES, Y, true), nothing);
        epilogue(X, 4 * j + 2 * rank, true);
        next = last;
        gturn(SECOND, false, mma128(YES, Y, true), nothing);
        fence_regs(Y);
        epilogue(Y, 4 * j + 2 * rank + 1, rank_of(item) == 0);
      }
      publish(it);
      item = sched[++it];
    }
    const int rho = rank_of(item);
    if (rho == 0 && relay) {
      turn();
      pass();
    }
    if (rho == 1) turn();
    publish(MAXITEMS - 1);
    asm volatile("cp.async.bulk.wait_group.read 0;" ::: "memory");
  }
}

typedef CUresult (*EncodeFn)(CUtensorMap*, CUtensorMapDataType, cuuint32_t, void*, const cuuint64_t*, const cuuint64_t*,
                             const cuuint32_t*, const cuuint32_t*, CUtensorMapInterleave, CUtensorMapSwizzle, CUtensorMapL2promotion,
                             CUtensorMapFloatOOBfill);

void make_map(EncodeFn enc, CUtensorMap* m, const void* ptr, uint64_t d0, uint64_t d1, uint64_t d2, uint64_t s1, uint64_t s2, uint32_t b0,
              uint32_t b1, uint32_t b2) {
  cuuint64_t gd[3] = {d0, d1, d2}, gs[2] = {s1, s2};
  cuuint32_t bd[3] = {b0, b1, b2}, es[3] = {1, 1, 1};
  enc(m, CU_TENSOR_MAP_DATA_TYPE_BFLOAT16, d2 ? 3 : 2, const_cast<void*>(ptr), gd, gs, bd, es, CU_TENSOR_MAP_INTERLEAVE_NONE,
      CU_TENSOR_MAP_SWIZZLE_128B, CU_TENSOR_MAP_L2_PROMOTION_L2_128B, CU_TENSOR_MAP_FLOAT_OOB_FILL_NONE);
}

struct HostState {
  Params p;
  const void* in[9];
  void* out;
  bool valid;
};
HostState g_hs;

const uint16_t h_sched[NCLUSTERS * MAXITEMS] = {
    273, 667, 531, 1091, 1443, 949, 7, 7, 7, 7, 7, 7, 7, 7, 7, 7,
    793, 187, 947, 1211, 725, 7, 7, 7, 7, 7, 7, 7, 7, 7, 7, 7,
    657, 787, 587, 1977, 1953, 1611, 60, 7, 7, 7, 7, 7, 7, 7, 7, 7,
    289, 417, 521, 905, 921, 923, 1297, 1363, 645, 7, 7, 7, 7, 7, 7, 7,
    393, 403, 537, 979, 1345, 1971, 773, 7, 7, 7, 7, 7, 7, 7, 7, 7,
    313, 387, 433, 555, 51, 1739, 44, 7, 7, 7, 7, 7, 7, 7, 7, 7,
    849, 267, 339, 1227, 797, 7, 7, 7, 7, 7, 7, 7, 7, 7, 7, 7,
    785, 691, 971, 1579, 533, 7, 7, 7, 7, 7, 7, 7, 7, 7, 7, 7,
    457, 707, 945, 1153, 1155, 1737, 1433, 1603, 68, 7, 7, 7, 7, 7, 7, 7,
    145, 443, 1099, 1955, 669, 7, 7, 7, 7, 7, 7, 7, 7, 7, 7, 7,
    329, 451, 1027, 1081, 1473, 1929, 1441, 1427, 541, 7, 7, 7, 7, 7, 7, 7,
    185, 683, 955, 81, 1825, 1859, 140, 7, 7, 7, 7, 7, 7, 7, 7, 7,
    641, 211, 953, 1985, 1361, 1331, 525, 7, 7, 7, 7, 7, 7, 7, 7, 7,
    321, 147, 547, 67, 1691, 677, 7, 7, 7, 7, 7, 7, 7, 7, 7, 7,
    665, 315, 937, 1073, 1097, 1305, 1329, 1475, 180, 7, 7, 7, 7, 7, 7, 7,
    337, 843, 83, 1291, 973, 7, 7, 7, 7, 7, 7, 7, 7, 7, 7, 7,
    169, 771, 441, 595, 1219, 805, 7, 7, 7, 7, 7, 7, 7, 7, 7, 7,
    449, 139, 529, 539, 3, 1169, 1921, 1937, 1713, 1715, 188, 7, 7, 7, 7, 7,
    465, 851, 1865, 1281, 1185, 1203, 717, 7, 7, 7, 7, 7, 7, 7, 7, 7,
    841, 675, 913, 9, 593, 49, 1283, 1459, 597, 7, 7, 7, 7, 7, 7, 7,
    673, 171, 1033, 1083, 1539, 1731, 148, 7, 7, 7, 7, 7, 7, 7, 7, 7,
    649, 715, 35, 1339, 821, 7, 7, 7, 7, 7, 7, 7, 7, 7, 7, 7,
    177, 131, 291, 939, 1801, 1681, 1307, 589, 7, 7, 7, 7, 7, 7, 7, 7,
    809, 827, 1059, 65, 1673, 1867, 84, 7, 7, 7, 7, 7, 7, 7, 7, 7,
    721, 835, 907, 2001, 1601, 1553, 1179, 693, 7, 7, 7, 7, 7, 7, 7, 7,
    193, 179, 929, 1051, 1665, 1817, 1705, 1547, 573, 7, 7, 7, 7, 7, 7, 7,
    705, 467, 59, 2003, 132, 7, 7, 7, 7, 7, 7, 7, 7, 7, 7, 7,
    697, 155, 571, 1993, 1729, 1593, 1555, 781, 7, 7, 7, 7, 7, 7, 7, 7,
    825, 411, 897, 561, 1043, 1105, 1201, 1963, 941, 7, 7, 7, 7, 7, 7, 7,
    297, 163, 553, 1049, 1035, 1177, 1819, 1587, 20, 7, 7, 7, 7, 7, 7, 7,
    689, 659, 523, 963, 1843, 701, 7, 7, 7, 7, 7, 7, 7, 7, 7, 7,
    281, 195, 1075, 1931, 1811, 557, 7, 7, 7, 7, 7, 7, 7, 7, 7, 7,
    385, 819, 899, 17, 11, 1409, 1209, 1483, 172, 7, 7, 7, 7, 7, 7, 7,
    257, 459, 585, 41, 1793, 73, 1323, 581, 7, 7, 7, 7, 7, 7, 7, 7,
    833, 811, 931, 977, 1745, 1961, 1563, 957, 7, 7, 7, 7, 7, 7, 7, 7,
    2, 10, 18, 26, 34, 42, 1561, 1851, 52, 7, 7, 7, 7, 7, 7, 7,
    817, 395, 307, 961, 1289, 1193, 1195, 565, 7, 7, 7, 7, 7, 7, 7, 7,
    681, 795, 545, 1041, 43, 1321, 1571, 661, 7, 7, 7, 7, 7, 7, 7, 7,
    130, 138, 146, 154, 162, 170, 1569, 1467, 36, 7, 7, 7, 7, 7, 7, 7,
    265, 419, 515, 1, 1065, 969, 1489, 1545, 1699, 813, 7, 7, 7, 7, 7, 7,
    801, 425, 299, 1057, 1873, 1235, 933, 7, 7, 7, 7, 7, 7, 7, 7, 7,
    258, 266, 274, 282, 290, 298, 1577, 1595, 76, 7, 7, 7, 7, 7, 7, 7,
    777, 427, 1025, 577, 19, 1609, 1945, 1435, 909, 7, 7, 7, 7, 7, 7, 7,
    209, 409, 513, 579, 1163, 1217, 1697, 1675, 845, 7, 7, 7, 7, 7, 7, 7,
    514, 522, 530, 538, 546, 554, 1689, 1723, 12, 7, 7, 7, 7, 7, 7, 7,
    161, 643, 331, 1849, 1355, 789, 7, 7, 7, 7, 7, 7, 7, 7, 7, 7,
    201, 723, 33, 1857, 1347, 917, 7, 7, 7, 7, 7, 7, 7, 7, 7, 7,
    642, 650, 658, 666, 674, 682, 1833, 1979, 196, 7, 7, 7, 7, 7, 7, 7,
    153, 435, 569, 25, 1089, 1481, 1411, 1315, 837, 7, 7, 7, 7, 7, 7, 7,
    401, 803, 563, 57, 1417, 1457, 1299, 685, 7, 7, 7, 7, 7, 7, 7, 7,
    50, 58, 66, 74, 82, 1617, 1491, 156, 7, 7, 7, 7, 7, 7, 7, 7,
    769, 699, 915, 1161, 1969, 1425, 1585, 1419, 653, 7, 7, 7, 7, 7, 7, 7,
    386, 394, 402, 410, 418, 426, 1827, 925, 7, 7, 7, 7, 7, 7, 7, 7,
    178, 186, 194, 202, 210, 1225, 1747, 212, 7, 7, 7, 7, 7, 7, 7, 7,
    713, 779, 275, 1107, 1187, 853, 7, 7, 7, 7, 7, 7, 7, 7, 7, 7,
    770, 778, 786, 794, 802, 810, 1923, 1451, 517, 7, 7, 7, 7, 7, 7, 7,
    306, 314, 322, 330, 338, 1537, 1337, 1987, 164, 7, 7, 7, 7, 7, 7, 7,
    129, 259, 323, 27, 1803, 1947, 829, 7, 7, 7, 7, 7, 7, 7, 7, 7,
    898, 906, 914, 922, 930, 938, 1667, 1835, 901, 7, 7, 7, 7, 7, 7, 7,
    434, 442, 450, 458, 466, 1233, 1875, 204, 7, 7, 7, 7, 7, 7, 7, 7,
    137, 203, 75, 1171, 709, 7, 7, 7, 7, 7, 7, 7, 7, 7, 7, 7,
    562, 570, 578, 586, 594, 1809, 1721, 1683, 549, 7, 7, 7, 7, 7, 7, 7,
    690, 698, 706, 714, 722, 1795, 1841, 1995, 4, 7, 7, 7, 7, 7, 7, 7,
    305, 651, 283, 1067, 1465, 1707, 981, 7, 7, 7, 7, 7, 7, 7, 7, 7,
    818, 826, 834, 842, 850, 1313, 1449, 1939, 965, 7, 7, 7, 7, 7, 7, 7,
    946, 954, 962, 970, 978, 1353, 1619, 28, 7, 7, 7, 7, 7, 7, 7, 7,
};

void setup(void* const* d_in, void* d_out) {
  void* fn = nullptr;
  cudaDriverEntryPointQueryResult qr;
  cudaGetDriverEntryPoint("cuTensorMapEncodeTiled", &fn, cudaEnableDefault, &qr);
  EncodeFn enc = (EncodeFn)fn;
  void *scr, *carry, *flags;
  cudaGetSymbolAddress(&scr, g_scr);
  cudaGetSymbolAddress(&carry, g_carry);
  cudaGetSymbolAddress(&flags, g_flags);
  Params& p = g_hs.p;
  make_map(enc, &p.mapA[2], d_in[3], 64, 2048, 16, 2048, 128, 64, 64, 1);
  make_map(enc, &p.mapA[0], d_in[4], 64, 2048, 8, 1024, 128, 64, 64, 1);
  make_map(enc, &p.mapA[1], d_in[0], 64, 1024, 32, 4096, 128, 64, 64, 1);
  make_map(enc, &p.mapB[3], d_in[5], 64, 1024, 64, 8192, 128, 64, 128, 2);
  make_map(enc, &p.mapB[1], d_in[6], 64, 512, 64, 8192, 128, 64, 128, 2);
  make_map(enc, &p.mapB[2], d_in[1], 1024, 1024, 3, 6144, 2048, 64, 64, 3);
  make_map(enc, &p.mapB[0], d_in[7], 64, 512, 64, 8192, 128, 64, 128, 2);
  make_map(enc, &p.mapB[5], d_in[8], 64, 4096, 16, 2048, 128, 64, 128, 2);
  {
    cuuint64_t gd[5] = {1024, 2, 4, 4, 32}, gs[4] = {2048, 8 * 2048, 2 * 2048, 32 * 2048};
    cuuint32_t bd[5] = {64, 2, 4, 4, 4}, es[5] = {1, 1, 1, 1, 1};
    enc(&p.mapB[4], CU_TENSOR_MAP_DATA_TYPE_BFLOAT16, 5, d_in[2], gd, gs, bd, es, CU_TENSOR_MAP_INTERLEAVE_NONE, CU_TENSOR_MAP_SWIZZLE_128B,
        CU_TENSOR_MAP_L2_PROMOTION_L2_128B, CU_TENSOR_MAP_FLOAT_OOB_FILL_NONE);
  }
  make_map(enc, &p.mapO[0], d_out, 4096, 1024, 0, 8192, 0, 64, 16, 1);
  make_map(enc, &p.mapO[1], d_out, 2048, 2048, 0, 4096, 0, 64, 16, 1);
  p.scr = (uint4*)scr;
  p.carry = (uint4*)carry;
  p.flags = (uint32_t*)flags;
  p.x = (const uint32_t*)d_in[3];
  p.wq = (const uint16_t*)d_in[5];
  p.zero = 0;
  for (int c = 0; c < NCLUSTERS; c++) {
    int rot = 0;
    for (int i = c * MAXITEMS; i < (c + 1) * MAXITEMS; i++) {
      const int kind = h_sched[i] & 7, g = (h_sched[i] >> 3) & 15;
      p.sched[i] = (uint16_t)(h_sched[i] | rot << 11);
      rot = (rot + (kind == K_T ? 1 + (g & 1) : g == 0)) % 3;
    }
  }
  cudaFuncSetAttribute(fused_kernel, cudaFuncAttributeMaxDynamicSharedMemorySize, SM_TOTAL);
  for (int i = 0; i < 9; i++) g_hs.in[i] = d_in[i];
  g_hs.out = d_out;
  g_hs.valid = true;
}

}

extern "C" void kernel_launch(void* const* d_in, const int* in_sizes, int n_in, void* d_out, int out_size) {
  (void)in_sizes;
  (void)n_in;
  (void)out_size;
  bool ok = g_hs.valid && g_hs.out == d_out;
  for (int i = 0; ok && i < 9; i++) ok = g_hs.in[i] == d_in[i];
  if (!ok) setup(d_in, d_out);
  fused_kernel<<<NCLUSTERS * 2, 512, SM_TOTAL, cudaStreamPerThread>>>(g_hs.p);
}
```

```cpp
#include <cuda_runtime.h>
#include <cuda_bf16.h>
#include <cuda.h>
#include <stdint.h>
#include <type_traits>

namespace {

typedef __nv_bfloat16 bf16;

__device__ __forceinline__ uint32_t smem_u32(const void* p) { return (uint32_t)__cvta_generic_to_shared(p); }
__device__ __forceinline__ void mbar_init(uint32_t bar, uint32_t cnt) {
  asm volatile("mbarrier.init.shared::cta.b64 [%0], %1;" ::"r"(bar), "r"(cnt) : "memory");
}
__device__ __forceinline__ void mbar_expect_tx(uint32_t bar, uint32_t bytes) {
  asm volatile("mbarrier.arrive.expect_tx.shared::cta.b64 _, [%0], %1;" ::"r"(bar), "r"(bytes) : "memory");
}
__device__ __forceinline__ void mbar_arrive_n(uint32_t bar, uint32_t n) {
  asm volatile("mbarrier.arrive.shared::cta.b64 _, [%0], %1;" ::"r"(bar), "r"(n) : "memory");
}
__device__ __forceinline__ void mbar_arrive_if0(uint32_t bar, uint32_t sel) {
  asm volatile("{\n.reg .pred p;\nsetp.eq.u32 p, %1, 0;\n@p mbarrier.arrive.shared::cta.b64 _, [%0];\n}" ::"r"(bar), "r"(sel) : "memory");
}
__device__ __forceinline__ void mbar_arrive_cta_if0(uint32_t bar, uint32_t cta, uint32_t sel) {
  asm volatile("{\n.reg .pred p;\n.reg .b32 ra;\nsetp.eq.u32 p, %2, 0;\nmapa.shared::cluster.u32 ra, %0, %1;\n"
               "@p mbarrier.arrive.shared::cluster.b64 _, [ra];\n}" ::"r"(bar),
               "r"(cta), "r"(sel)
               : "memory");
}
__device__ __forceinline__ void mbar_wait(uint32_t bar, uint32_t parity) {
  uint32_t done;
  uint32_t it = 0;
#pragma unroll 1
  while (true) {
    asm volatile("{\n.reg .pred p;\nmbarrier.try_wait.parity.shared::cta.b64 p, [%1], %2, 1000;\nselp.u32 %0, 1, 0, p;\n}"
                 : "=r"(done)
                 : "r"(bar), "r"(parity)
                 : "memory");
    if (done) break;
    if (++it > (1u << 24)) __trap();
  }
}
__device__ __forceinline__ void mbar_wait_u(uint32_t bar, uint32_t parity) {
  uint32_t it = 0;
#pragma unroll 1
  while (true) {
    uint32_t done;
    asm volatile("{\n.reg .pred p, q;\nmbarrier.try_wait.parity.shared::cta.b64 p, [%1], %2;\nvote.sync.all.pred q, p, 0xffffffff;\nselp.u32 %0, 1, 0, q;\n}"
                 : "=r"(done)
                 : "r"(bar), "r"(parity)
                 : "memory");
    if (done) break;
    if (++it > (1u << 20)) break;
  }
}
#define DECLARE_READY() asm volatile(".reg .pred RDYA, RDYB;")
__device__ __forceinline__ void test_a(uint32_t bar, uint32_t parity) {
  asm volatile("mbarrier.test_wait.parity.shared::cta.b64 RDYA, [%0], %1;" ::"r"(bar), "r"(parity) : "memory");
}
__device__ __forceinline__ void test_b(uint32_t bar, uint32_t parity) {
  asm volatile("mbarrier.test_wait.parity.shared::cta.b64 RDYB, [%0], %1;" ::"r"(bar), "r"(parity) : "memory");
}
__device__ __forceinline__ uint32_t ready_b(uint32_t dep = 0) {
  uint32_t r;
  asm volatile("{\n.reg .pred q;\nsetp.eq.and.u32 q, %1, 0, RDYB;\nvote.sync.all.pred q, q, 0xffffffff;\nselp.u32 %0, 1, 0, q;\n}" : "=r"(r) : "r"(dep) : "memory");
  return r;
}
__device__ __forceinline__ uint32_t ready_ab() {
  uint32_t r;
  asm volatile("{\n.reg .pred q;\nand.pred q, RDYA, RDYB;\nvote.sync.all.pred q, q, 0xffffffff;\nselp.u32 %0, 1, 0, q;\n}" : "=r"(r)::"memory");
  return r;
}
__device__ __forceinline__ void tma_load_3d(uint32_t dst, const CUtensorMap* m, uint32_t bar, int c0, int c1, int c2) {
  asm volatile("cp.async.bulk.tensor.3d.shared::cluster.global.mbarrier::complete_tx::bytes [%0], [%1, {%3, %4, %5}], [%2];" ::"r"(dst),
               "l"(m), "r"(bar), "r"(c0), "r"(c1), "r"(c2)
               : "memory");
}
constexpr uint32_t L2_NORMAL = 0x10000000u, L2_FIRST = 0x12F00000u;
__device__ __forceinline__ void tma_load_3d(uint32_t dst, const CUtensorMap* m, uint32_t bar, int c0, int c1, int c2, uint32_t pol) {
  asm volatile("{\n.reg .b64 h;\nmov.b64 h, {0, %6};\n"
               "cp.async.bulk.tensor.3d.shared::cluster.global.mbarrier::complete_tx::bytes.L2::cache_hint [%0], [%1, {%3, %4, %5}], [%2], h;\n}" ::"r"(dst),
               "l"(m), "r"(bar), "r"(c0), "r"(c1), "r"(c2), "r"(pol)
               : "memory");
}
__device__ __forceinline__ void bulk_load(uint32_t dst, const void* src, uint32_t bytes, uint32_t bar, uint32_t pol) {
  asm volatile("{\n.reg .b64 h;\nmov.b64 h, {0, %4};\n"
               "cp.async.bulk.shared::cluster.global.mbarrier::complete_tx::bytes.L2::cache_hint [%0], [%1], %2, [%3], h;\n}" ::"r"(dst),
               "l"(src), "r"(bytes), "r"(bar), "r"(pol)
               : "memory");
}
__device__ __forceinline__ void tma_load_3d_mc(uint32_t dst, const CUtensorMap* m, uint32_t bar, int c0, int c1, int c2, uint16_t mask) {
  asm volatile(
      "cp.async.bulk.tensor.3d.shared::cluster.global.mbarrier::complete_tx::bytes.multicast::cluster [%0], [%1, {%3, %4, %5}], [%2], %6;" ::"r"(dst),
      "l"(m), "r"(bar), "r"(c0), "r"(c1), "r"(c2), "h"(mask)
      : "memory");
}
__device__ __forceinline__ void tma_load_5d(uint32_t dst, const CUtensorMap* m, uint32_t bar, int c0, int c4) {
  asm volatile("cp.async.bulk.tensor.5d.shared::cluster.global.mbarrier::complete_tx::bytes [%0], [%1, {%3, 0, 0, 0, %4}], [%2];" ::"r"(dst),
               "l"(m), "r"(bar), "r"(c0), "r"(c4)
               : "memory");
}
__device__ __forceinline__ void bulk_load(uint32_t dst, const void* src, uint32_t bytes, uint32_t bar) {
  asm volatile("cp.async.bulk.shared::cluster.global.mbarrier::complete_tx::bytes [%0], [%1], %2, [%3];" ::"r"(dst), "l"(src), "r"(bytes), "r"(bar)
               : "memory");
}
__device__ __forceinline__ void bulk_load_mc(uint32_t dst, const void* src, uint32_t bytes, uint32_t bar, uint16_t mask) {
  asm volatile("cp.async.bulk.shared::cluster.global.mbarrier::complete_tx::bytes.multicast::cluster [%0], [%1], %2, [%3], %4;" ::"r"(dst),
               "l"(src), "r"(bytes), "r"(bar), "h"(mask)
               : "memory");
}
__device__ __forceinline__ void prefetch_l2(const void* src, uint32_t bytes) {
  asm volatile("cp.async.bulk.prefetch.L2.global [%0], %1;" ::"l"(src), "r"(bytes) : "memory");
}
__device__ __forceinline__ void tma_store_2d(const CUtensorMap* m, uint32_t src, int c0, int c1) {
  asm volatile("cp.async.bulk.tensor.2d.global.shared::cta.bulk_group [%0, {%2, %3}], [%1];" ::"l"(m), "r"(src), "r"(c0), "r"(c1)
               : "memory");
}
__device__ __forceinline__ void prefetch_tmap(const CUtensorMap* m) { asm volatile("prefetch.tensormap [%0];" ::"l"(m) : "memory"); }
__device__ __forceinline__ uint32_t pack_bf16(float lo, float hi) {
  uint32_t r;
  asm("cvt.rn.bf16x2.f32 %0, %1, %2;" : "=r"(r) : "f"(hi), "f"(lo));
  return r;
}
__device__ __forceinline__ float ex2(float x) {
  float y;
  asm("ex2.approx.ftz.f32 %0, %1;" : "=f"(y) : "f"(x));
  return y;
}
__device__ __forceinline__ float rcp(float x) {
  float y;
  asm("rcp.approx.ftz.f32 %0, %1;" : "=f"(y) : "f"(x));
  return y;
}
__device__ __forceinline__ void wg_fence() { asm volatile("wgmma.fence.sync.aligned;" ::: "memory"); }
__device__ __forceinline__ void wg_commit() { asm volatile("wgmma.commit_group.sync.aligned;" ::: "memory"); }
template <int N>
__device__ __forceinline__ void wg_wait() {
  asm volatile("wgmma.wait_group.sync.aligned %0;" ::"n"(N) : "memory");
}
template <int N>
__device__ __forceinline__ void fence_regs(float (&d)[N]) {
#pragma unroll
  for (int i = 0; i < N; i++) asm volatile("" : "+f"(d[i])::"memory");
}
__device__ __forceinline__ uint32_t sched_fence() {
  uint32_t t;
  asm volatile("mov.u32 %0, %%clock;" : "=r"(t)::"memory");
  return t;
}
__device__ __forceinline__ void bar_sync(int id, int n) { asm volatile("bar.sync %0, %1;" ::"r"(id), "r"(n) : "memory"); }
__device__ __forceinline__ void bar_arrive_if(bool c, int id, int n) {
  asm volatile("{\n.reg .pred p;\nsetp.ne.u32 p, %2, 0;\n@p bar.arrive %0, %1;\n}" ::"r"(id), "r"(n), "r"((uint32_t)c) : "memory");
}
__device__ __forceinline__ void bar_arrive(int id, int n) { asm volatile("bar.arrive %0, %1;" ::"r"(id), "r"(n) : "memory"); }

#define R8(a, i) "+f"(a[i]), "+f"(a[i + 1]), "+f"(a[i + 2]), "+f"(a[i + 3]), "+f"(a[i + 4]), "+f"(a[i + 5]), "+f"(a[i + 6]), "+f"(a[i + 7])
#define OP32(d, o) R8(d, o), R8(d, o + 8), R8(d, o + 16), R8(d, o + 24)
#define L32A "%0,%1,%2,%3,%4,%5,%6,%7,%8,%9,%10,%11,%12,%13,%14,%15,%16,%17,%18,%19,%20,%21,%22,%23,%24,%25,%26,%27,%28,%29,%30,%31"
#define L32B "%32,%33,%34,%35,%36,%37,%38,%39,%40,%41,%42,%43,%44,%45,%46,%47,%48,%49,%50,%51,%52,%53,%54,%55,%56,%57,%58,%59,%60,%61,%62,%63"
#define L32C "%64,%65,%66,%67,%68,%69,%70,%71,%72,%73,%74,%75,%76,%77,%78,%79,%80,%81,%82,%83,%84,%85,%86,%87,%88,%89,%90,%91,%92,%93,%94,%95"
#define WG_PRE(a, b, s, ha, hb) "{\n.reg .pred p;\n.reg .b64 da, db;\nmov.b64 da, {" a ", " ha "};\nmov.b64 db, {" b ", " hb "};\nsetp.ne.b32 p, " s ", 0;\n"

constexpr uint32_t HI128 = 0x40000040;
constexpr uint32_t HI64 = 0x80000080;
constexpr uint32_t HIQ = 0x80000040;
template <int TB>
__device__ __forceinline__ void wgmma_n128(float (&d)[64], uint32_t da, uint32_t ha, uint32_t db, uint32_t hb, int scale_d) {
  asm volatile(WG_PRE("%64", "%65", "%66", "%67", "%68") "wgmma.mma_async.sync.aligned.m64n128k16.f32.bf16.bf16 {" L32A "," L32B "}, da, db, p, 1, 1, 0, %69;\n}\n"
               : OP32(d, 0), OP32(d, 32)
               : "r"(da), "r"(db), "r"(scale_d), "r"(ha), "r"(hb), "n"(TB));
}
__device__ __forceinline__ void wgmma_n192_tb(float (&d)[96], uint32_t da, uint32_t db, int scale_d) {
  asm volatile(WG_PRE("%96", "%97", "%98", "%99", "%99") "wgmma.mma_async.sync.aligned.m64n192k16.f32.bf16.bf16 {" L32A "," L32B "," L32C "}, da, db, p, 1, 1, 0, 1;\n}\n"
               : OP32(d, 0), OP32(d, 32), OP32(d, 64)
               : "r"(da), "r"(db), "r"(scale_d), "r"(HI128));
}
__device__ __forceinline__ void wgmma_n64(float (&d)[64], uint32_t da, uint32_t db, int scale_d) {
  asm volatile(WG_PRE("%32", "%33", "%34", "%35", "%36") "wgmma.mma_async.sync.aligned.m64n64k16.f32.bf16.bf16 {" L32A "}, da, db, p, 1, 1, 0, 0;\n}\n"
               : OP32(d, 0)
               : "r"(da), "r"(db), "r"(scale_d), "r"(HIQ), "r"(HI64));
}
__device__ __forceinline__ void wgmma_n128_rs_tb(float (&d)[64], uint32_t a0, uint32_t a1, uint32_t a2, uint32_t a3, uint32_t db, int scale_d) {
  asm volatile("{\n.reg .pred p;\n.reg .b64 db;\nmov.b64 db, {%68, %70};\nsetp.ne.b32 p, %69, 0;\n"
               "wgmma.mma_async.sync.aligned.m64n128k16.f32.bf16.bf16 {" L32A "," L32B "}, {%64,%65,%66,%67}, db, p, 1, 1, 1;\n}\n"
               : OP32(d, 0), OP32(d, 32)
               : "r"(a0), "r"(a1), "r"(a2), "r"(a3), "r"(db), "r"(scale_d), "r"(HI64));
}
__device__ __forceinline__ void mma_16816(float (&c)[4], uint32_t a0, uint32_t a1, uint32_t a2, uint32_t a3, uint32_t b0, uint32_t b1) {
  asm volatile("mma.sync.aligned.m16n8k16.row.col.f32.bf16.bf16.f32 {%0,%1,%2,%3}, {%4,%5,%6,%7}, {%8,%9}, {%0,%1,%2,%3};"
               : "+f"(c[0]), "+f"(c[1]), "+f"(c[2]), "+f"(c[3])
               : "r"(a0), "r"(a1), "r"(a2), "r"(a3), "r"(b0), "r"(b1));
}
__device__ __forceinline__ uint32_t movm_t(uint32_t x) {
  uint32_t y;
  asm volatile("movmatrix.sync.aligned.m8n8.trans.b16 %0, %1;" : "=r"(y) : "r"(x));
  return y;
}
__device__ __forceinline__ void sts128(uint32_t a, uint32_t x, uint32_t y, uint32_t z, uint32_t w) {
  asm volatile("st.shared.v4.u32 [%0], {%1,%2,%3,%4};" ::"r"(a), "r"(x), "r"(y), "r"(z), "r"(w) : "memory");
}
__device__ __forceinline__ void stsm4(uint32_t a, uint32_t x, uint32_t y, uint32_t z, uint32_t w) {
  asm volatile("stmatrix.sync.aligned.m8n8.x4.shared.b16 [%0], {%1,%2,%3,%4};" ::"r"(a), "r"(x), "r"(y), "r"(z), "r"(w) : "memory");
}
__device__ __forceinline__ void ldsm4_t(uint32_t a, uint32_t (&r)[4]) {
  asm volatile("ldmatrix.sync.aligned.m8n8.x4.trans.shared.b16 {%0,%1,%2,%3}, [%4];"
               : "=r"(r[0]), "=r"(r[1]), "=r"(r[2]), "=r"(r[3])
               : "r"(a)
               : "memory");
}
__device__ __forceinline__ void stg128_if0(uint4* a, uint32_t x, uint32_t y, uint32_t z, uint32_t w, uint32_t sel) {
  asm volatile("{\n.reg .pred p;\nsetp.eq.u32 p, %5, 0;\n@p st.global.cs.v4.u32 [%0], {%1,%2,%3,%4};\n}" ::"l"(a), "r"(x), "r"(y), "r"(z), "r"(w),
               "r"(sel)
               : "memory");
}
template <int OFS>
__device__ __forceinline__ void stg128_sel(uint4* a, uint32_t x, uint32_t y, uint32_t z, uint32_t w, uint32_t sel) {
  asm volatile("{\n.reg .pred p;\nsetp.eq.u32 p, %5, 0;\n@p st.global.v4.u32 [%0+%6], {%1,%2,%3,%4};\n"
               "setp.eq.u32 p, %5, 2;\n@p st.global.cs.v4.u32 [%0+%6], {%1,%2,%3,%4};\n}" ::"l"(a), "r"(x), "r"(y), "r"(z), "r"(w), "r"(sel), "n"(OFS * 16)
               : "memory");
}
__device__ __forceinline__ void lds128(uint32_t a, uint32_t& x, uint32_t& y, uint32_t& z, uint32_t& w) {
  asm volatile("ld.shared.v4.u32 {%0,%1,%2,%3}, [%4];" : "=r"(x), "=r"(y), "=r"(z), "=r"(w) : "r"(a) : "memory");
}

constexpr int PLANE = 2048 * 16;
constexpr int PL_CTX = 0, PL_KV = 32, PL_OA = PL_KV + 64, NPLANES = PL_OA + 8;
__device__ __align__(1024) uint4 g_scr[NPLANES * PLANE];
__device__ uint4 g_carry[16 * 128];
constexpr int F_CTX = 0, F_KV = 512, F_L = 1040, F_CAR = 1056, F_EPOCH = 1072, F_END = 1072 + 132;
__device__ uint32_t g_flags[F_END];

#define NTURN 256

enum { K_KV = 1, K_L = 2, K_T = 3, K_OA = 4, K_OB = 5, K_END = 7 };
constexpr int NCLUSTERS = 66, MAXITEMS = 16;
constexpr int A_STAGE = 16384, B_SLOT = 32768;
constexpr int SM_B = 6 * A_STAGE, SM_CARRY = SM_B + 4 * B_SLOT, SM_BAR = SM_CARRY + 2048, SM_TOTAL = SM_BAR + 512;

struct Params {
  CUtensorMap mapA[3];
  CUtensorMap mapB[6];
  CUtensorMap mapO[2];
  uint4* scr;
  uint4* carry;
  uint32_t* flags;
  const uint32_t* x;
  const uint16_t* wq;
  uint32_t zero;
  uint16_t sched[NCLUSTERS * MAXITEMS];
  uint8_t keep[NCLUSTERS * MAXITEMS];
};

__device__ __forceinline__ bool item_narrow(uint32_t item) { return (item & 0x204) == 0x204 || (item & 7) == K_T; }
__device__ __forceinline__ int item_nk(uint32_t item) {
  const uint32_t kind = item & 7;
  return (kind == K_KV ? 8 : kind == K_OB ? 64 : 16) >> item_narrow(item);
}
__device__ __forceinline__ int item_row(uint32_t kind, int g, int pos) {
  if (kind == K_L || kind == K_OA) return g == 0 ? (pos - 1) * 1024 : 64 * (3 * g - 2 + pos + (g > 5));
  return 64 * (3 * g - 1 + pos);
}

__device__ __forceinline__ void wait_flag(const uint32_t* f, uint32_t target) {
  uint32_t it = 0;
#pragma unroll 1
  while (true) {
    uint32_t v;
    asm volatile("ld.acquire.gpu.global.u32 %0, [%1];" : "=r"(v) : "l"(f) : "memory");
    if ((int)(v - target) >= 0) break;
    __nanosleep(40);
    if (++it > (1u << 18)) break;
  }
  asm volatile("fence.proxy.async.global;" ::: "memory");
}
__device__ __forceinline__ uint32_t wait_bits(const uint32_t* f, uint32_t inv, uint32_t mask) {
  uint32_t it = 0, v;
#pragma unroll 1
  while (true) {
    asm volatile("ld.acquire.gpu.global.u32 %0, [%1];" : "=r"(v) : "l"(f) : "memory");
    v ^= inv;
    if (!(~v & mask)) break;
    __nanosleep(40);
    if (++it > (1u << 18)) break;
  }
  asm volatile("fence.proxy.async.global;" ::: "memory");
  return v;
}
__device__ __forceinline__ void red_add(uint32_t* f) { asm volatile("red.relaxed.gpu.global.add.u32 [%0], 1;" ::"l"(f) : "memory"); }
__device__ __forceinline__ void red_xor(uint32_t* f, uint32_t v) {
  asm volatile("red.relaxed.gpu.global.xor.b32 [%0], %1;" ::"l"(f), "r"(v) : "memory");
}

constexpr float QS = 0.08838834764831845f * 1.4426950408889634f;
__device__ __noinline__ void attn_fallback(uint4* q, const uint4* __restrict__ k, const uint32_t* __restrict__ x,
                                           const uint16_t* __restrict__ w, int row0, int lane) {
  const int g = lane >> 2, tq = lane & 3;
  q += row0 * 16;
  k += lane ^ (lane >> 3);
  const uint4* v = k + 2 * PLANE;
  float o[16][4];
#pragma unroll
  for (int i = 0; i < 16; i++) o[i][0] = o[i][1] = o[i][2] = o[i][3] = 0.f;
  x += (row0 + g) * 512 + tq;
  w += 2 * tq * 4096 + g;
#pragma unroll 1
  for (int k0 = 0; k0 < 64; k0++, x += 8, w += 16 * 4096) {
#pragma unroll
    for (int i = 0; i < 16; i++)
      mma_16816(o[i], x[0], x[4096], x[4], x[4100], w[8 * i] | w[4096 + 8 * i] << 16, w[8 * 4096 + 8 * i] | w[9 * 4096 + 8 * i] << 16);
  }
#pragma unroll
  for (int i = 0; i < 8; i++) {
    const int c = 4 * (i >> 1), e = 2 * (i & 1);
    __stcg(q + (i >> 1) * 32 + (i & 1) * 128 + (lane ^ (lane >> 3)),
           make_uint4(pack_bf16(o[c][e], o[c][e + 1]), pack_bf16(o[c + 1][e], o[c + 1][e + 1]),
                      pack_bf16(o[c + 2][e], o[c + 2][e + 1]), pack_bf16(o[c + 3][e], o[c + 3][e + 1])));
  }
  __syncwarp();
#pragma unroll
  for (int i = 0; i < 16; i++) o[i][0] = o[i][1] = o[i][2] = o[i][3] = 0.f;
  float m0 = -INFINITY, m1 = -INFINITY, l0 = 0.f, l1 = 0.f;
#pragma unroll 1
  for (int k0 = 0; k0 < row0 + 16; k0 += 16) {
    float sc[2][4] = {{0.f, 0.f, 0.f, 0.f}, {0.f, 0.f, 0.f, 0.f}};
#pragma unroll 1
    for (int cg = 0; cg < 4; cg++) {
      const uint4 qa = __ldcg(q + cg * 32 + (lane ^ (lane >> 3)));
      const uint4 qb = __ldcg(q + 128 + cg * 32 + (lane ^ (lane >> 3)));
#pragma unroll
      for (int t = 0; t < 2; t++) {
        const uint4 kk = __ldcg(k + (k0 + 8 * t) * 16 + cg * 32);
        mma_16816(sc[t], qa.x, qb.x, qa.y, qb.y, kk.x, kk.y);
        mma_16816(sc[t], qa.z, qb.z, qa.w, qb.w, kk.z, kk.w);
      }
    }
    float x0 = -INFINITY, x1 = -INFINITY;
#pragma unroll
    for (int t = 0; t < 2; t++) {
#pragma unroll
      for (int e = 0; e < 2; e++) {
        const int key = k0 + 8 * t + 2 * tq + e;
        if (key > row0 + g) sc[t][e] = -INFINITY;
        if (key > row0 + g + 8) sc[t][2 + e] = -INFINITY;
        x0 = fmaxf(x0, sc[t][e]);
        x1 = fmaxf(x1, sc[t][2 + e]);
      }
    }
    x0 = fmaxf(x0, __shfl_xor_sync(0xffffffffu, x0, 1));
    x1 = fmaxf(x1, __shfl_xor_sync(0xffffffffu, x1, 1));
    x0 = fmaxf(x0, __shfl_xor_sync(0xffffffffu, x0, 2));
    x1 = fmaxf(x1, __shfl_xor_sync(0xffffffffu, x1, 2));
    const float n0 = fmaxf(m0, x0), n1 = fmaxf(m1, x1);
    const float a0 = ex2(m0 - n0), a1 = ex2(m1 - n1);
    m0 = n0;
    m1 = n1;
    l0 *= a0;
    l1 *= a1;
    uint32_t pa[4];
#pragma unroll
    for (int t = 0; t < 2; t++) {
      const float e0 = ex2(sc[t][0] - m0), e1 = ex2(sc[t][1] - m0);
      const float e2 = ex2(sc[t][2] - m1), e3 = ex2(sc[t][3] - m1);
      l0 += e0 + e1;
      l1 += e2 + e3;
      pa[2 * t] = pack_bf16(e0, e1);
      pa[2 * t + 1] = pack_bf16(e2, e3);
    }
#pragma unroll
    for (int cg = 0; cg < 4; cg++) {
      const uint4 va = __ldcg(v + k0 * 16 + cg * 32);
      const uint4 vb = __ldcg(v + k0 * 16 + 128 + cg * 32);
#pragma unroll
      for (int r = 0; r < 4; r++) {
        const uint32_t w0 = r == 0 ? va.x : r == 1 ? va.y : r == 2 ? va.z : va.w;
        const uint32_t w1 = r == 0 ? vb.x : r == 1 ? vb.y : r == 2 ? vb.z : vb.w;
        float(&oo)[4] = o[4 * cg + r];
        oo[0] *= a0;
        oo[1] *= a0;
        oo[2] *= a1;
        oo[3] *= a1;
        mma_16816(oo, pa[0], pa[1], pa[2], pa[3], movm_t(w0), movm_t(w1));
      }
    }
  }
  l0 += __shfl_xor_sync(0xffffffffu, l0, 1);
  l1 += __shfl_xor_sync(0xffffffffu, l1, 1);
  l0 += __shfl_xor_sync(0xffffffffu, l0, 2);
  l1 += __shfl_xor_sync(0xffffffffu, l1, 2);
  const float i0 = 1.f / l0, i1 = 1.f / l1;
  __syncwarp();
  uint32_t* o0 = reinterpret_cast<uint32_t*>(q + g * 4) + tq;
#pragma unroll
  for (int i = 0; i < 16; i++) {
    uint32_t* d = o0 + (i >> 2) * 128 + ((i & 3) ^ (g >> 1)) * 4;
    d[0] = pack_bf16(o[i][0] * i0, o[i][1] * i0);
    d[512] = pack_bf16(o[i][2] * i1, o[i][3] * i1);
  }
}

#define KB_LIMIT 1.2089258e24f
#define KB_LOW 9.094947e-13f

__device__ __forceinline__ void local_scores(float (&s)[2][4], const uint32_t (&lo)[24], const uint32_t (&hi)[24], const uint32_t* k) {
#pragma unroll
  for (int h = 0; h < 2; h++) s[h][0] = s[h][1] = s[h][2] = s[h][3] = 0.f;
#pragma unroll
  for (int c = 0; c < 4; c += 2)
#pragma unroll
    for (int h = 0; h < 8; h += 4) mma_16816(s[h >> 2], lo[h + c], hi[h + c], lo[h + c + 1], hi[h + c + 1], k[h + c], k[h + c + 1]);
}
__device__ __forceinline__ void local_attn(float (&o)[2][4][4], float (&l)[2][4], const float (&s)[3][2][4], const uint32_t (&vt)[2][4][4],
                                           bool first, int lane) {
  const int g = lane >> 2, tq = lane & 3;
  const bool h0 = 2 * tq > g, h1 = 2 * tq + 1 > g;
  const uint32_t m = (h0 ? 0xFFFFu : 0u) | (h1 ? 0xFFFF0000u : 0u);
  float u0[2], u1[2], w0[2], w1[2], mu[2], mw[2];
#pragma unroll
  for (int h = 0; h < 2; h++) {
    u0[h] = h0 ? s[0][h][0] : s[1][h][0];
    u1[h] = h1 ? s[0][h][1] : s[1][h][1];
    w0[h] = h0 ? s[1][h][2] : s[2][h][2];
    w1[h] = h1 ? s[1][h][3] : s[2][h][3];
    if (first) {
      if (h0) u0[h] = -INFINITY;
      if (h1) u1[h] = -INFINITY;
    }
    mu[h] = fmaxf(u0[h], u1[h]);
    mw[h] = fmaxf(w0[h], w1[h]);
  }
#pragma unroll
  for (int o = 1; o <= 2; o++)
#pragma unroll
    for (int h = 0; h < 2; h++) {
      mw[h] = fmaxf(mw[h], __shfl_xor_sync(0xffffffffu, mw[h], o));
      mu[h] = fmaxf(mu[h], __shfl_xor_sync(0xffffffffu, mu[h], o));
    }
  const float c = 0.17677669529663687f * 1.4426950408889634f;
#pragma unroll
  for (int h = 0; h < 2; h++) {
    const uint32_t pu = pack_bf16(ex2((u0[h] - mu[h]) * c), ex2((u1[h] - mu[h]) * c));
    const uint32_t pw = pack_bf16(ex2((w0[h] - mw[h]) * c), ex2((w1[h] - mw[h]) * c));
    l[h][0] = l[h][1] = l[h][2] = l[h][3] = 0.f;
    mma_16816(l[h], 0x3F803F80, 0u, 0u, 0x3F803F80, pu, pw);
#pragma unroll
    for (int i = 0; i < 4; i++) {
      const uint32_t(&v)[4] = vt[i >> 1][2 * h + (i & 1)];
      o[h][i][0] = o[h][i][1] = o[h][i][2] = o[h][i][3] = 0.f;
      mma_16816(o[h][i], v[0], v[1], v[2], v[3], i < 2 ? pu & m : pw & ~m, i < 2 ? pu & ~m : pw & m);
    }
  }
}

__global__ __cluster_dims__(2, 1, 1) __launch_bounds__(512, 1) void fused_kernel(const __grid_constant__ Params p) {
  extern __shared__ __align__(1024) uint8_t smem_dyn[];
  DECLARE_READY();
  const uint32_t sbase = smem_u32(smem_dyn);
  const uint32_t afull0 = sbase + SM_BAR, aempty0 = afull0 + 48, bfull0 = afull0 + 96, bempty0 = afull0 + 128, carbar = afull0 + 160,
                 pub0 = afull0 + 200;
  const uint32_t bbase = sbase + SM_B;
  const int wg = __reduce_min_sync(0xffffffffu, (int)(threadIdx.x >> 7));
  const uint32_t rank = blockIdx.x & 1;
  const uint16_t* sched = p.sched + (blockIdx.x >> 1) * MAXITEMS;

  auto fill_b = [&](uint32_t item, int t, uint32_t pb, uint32_t pol) {
    const uint32_t kind = item & 7, j = (item >> 7) & 15, sl = pb & 3;
    if (((item >> 3) & 15) == 0) mbar_arrive_n(bempty0 + 8 * sl, 1);
    mbar_expect_tx(bfull0 + 8 * sl, kind == K_L ? 24576 : 32768);
    const uint32_t nt = kind == K_KV ? j : 2 * j + rank, dst = bbase + sl * B_SLOT;
    const uint32_t cb = kind == K_T ? nt : item_narrow(item) ? nt - 8 : nt * 2 + (t >> 1 & 1);
    const uint32_t ks = item_narrow(item) ? t : (t >> 1 & ~1) + (t & 1);
    if (kind == K_OA) {
      tma_load_5d(dst, &p.mapB[K_OA], bfull0 + 8 * sl, cb * 128, ks * 4);
      tma_load_5d(dst + 16384, &p.mapB[K_OA], bfull0 + 8 * sl, cb * 128 + 64, ks * 4);
    } else if (kind == K_L) {
      tma_load_3d(dst, &p.mapB[K_L], bfull0 + 8 * sl, nt * 64, t * 64, 0, pol);
    } else {
      tma_load_3d(dst, &p.mapB[kind == K_KV ? 1 - rank : kind], bfull0 + 8 * sl, 0, ks * 128, cb * 2, pol);
    }
  };
  auto first_a = [&](uint32_t item0, uint32_t u, bool mc) {
    const bool local0 = (item0 & 7) == K_L;
    const int g0 = (item0 >> 3) & 15;
    const int row = item_row(local0 ? K_L : K_KV, g0, (u >> 1) + (g0 == 0));
    const int r = local0 ? row & 1023 : row, blk = (local0 ? (row >> 10) * 16 : 0) + 2 * (u & 1);
    if (mc) {
      mbar_expect_tx(afull0 + 8 * u, A_STAGE);
      tma_load_3d_mc(sbase + u * A_STAGE + rank * 8192, &p.mapA[local0], afull0 + 8 * u, 0, r, blk + rank, (uint16_t)3);
    } else
      for (int h = 0; h < 2; h++) tma_load_3d(sbase + u * A_STAGE + h * 8192, &p.mapA[local0], afull0 + 8 * u, 0, r, blk + h);
  };
  auto first_b = [&](uint32_t item0, uint32_t t) {
    const bool local0 = (item0 & 7) == K_L;
    const int j = (item0 >> 7) & 15;
    mbar_expect_tx(bfull0 + 8 * t, local0 ? 24576 : 32768);
    tma_load_3d(bbase + t * B_SLOT, &p.mapB[local0 ? K_L : 1 - rank], bfull0 + 8 * t, local0 ? (2 * j + rank) * 64 : 0,
                local0 ? t * 64 : (t & 1) * 128, local0 ? 0 : 4 * j + (t & 2));
    if ((item0 & 0x78) == 0) mbar_arrive_n(bempty0 + 8 * t, 1);
  };
  if (threadIdx.x == 0) {
    mbar_init(bfull0, 1);
    mbar_init(bempty0, 3);
    asm volatile("fence.mbarrier_init.release.cluster;" ::: "memory");
    first_b(sched[0], 0);
  } else if (threadIdx.x == 32) {
    mbar_init(afull0, 1);
    asm volatile("fence.mbarrier_init.release.cluster;" ::: "memory");
    mbar_expect_tx(afull0, A_STAGE);
    first_a(sched[0], 0, false);
  } else if (threadIdx.x == 64) {
    for (int i = 20; i < 25 + MAXITEMS; i++) mbar_init(afull0 + 8 * i, i < 25 ? 1 : 12);
  } else if (threadIdx.x == 96) {
    for (int i = 1; i < 20; i++)
      if (i != 12 && i != 16) mbar_init(afull0 + 8 * i, i < 6 ? 1 : i < 12 ? 2 : i < 16 ? 1 : 3);
    asm volatile("fence.mbarrier_init.release.cluster;" ::: "memory");
  }
  __syncthreads();
  asm volatile("barrier.cluster.arrive.relaxed.aligned;\nbarrier.cluster.wait.aligned;" ::: "memory");

  if (wg == 0) {
    asm volatile("setmaxnreg.dec.sync.aligned.u32 32;");
    const uint32_t item0 = sched[0];
    const bool local0 = (item0 & 7) == K_L;
    const int g0 = (item0 >> 3) & 15;
    if (threadIdx.x == 96) {
#pragma unroll 1
      for (uint32_t x = local0 ? 0x6B42A593u : 0xB6A45239u; x; x >>= 4) {
        if (x & 8) first_b(item0, x & 3);
        else if (g0 != 0 || (x & 7) < 5) first_a(item0, (x & 7) - 1, true);
      }
    }
    if (__reduce_min_sync(0xffffffffu, (int)(threadIdx.x >> 5)) == 1) {
      const uint32_t e = __ldcg(p.flags + F_EPOCH + blockIdx.x) + 1;
      const uint32_t w = threadIdx.x - 32;
      uint32_t n = w < 2 || ((sched[0] >> 3) & 15) != 0 ? 2 : 0;
      uint32_t bar0 = afull0 + 16 * w, dst0 = sbase + w * (2 * A_STAGE) + rank * 8192;
      asm volatile("" : "+r"(bar0), "+r"(dst0));
      uint32_t bar, dst, par, prev = 0;
      auto position = [&]() {
        bar = bar0 + 8 * (n & 1), dst = dst0 + (n & 1) * A_STAGE, par = (~n >> 1) & 1;
        asm volatile("" : "+r"(bar), "+r"(dst), "+r"(par));
      };
      position();
      for (int it = 0; it < MAXITEMS; it++) {
        const uint32_t item = sched[it];
        const uint32_t kind = item & 7;
        if (kind == K_END) break;
        const int g = (item >> 3) & 15;
        const int nd = kind == K_T ? 8 : item_nk(kind) >> 1;
        if (kind == K_OA) wait_flag(p.flags + F_L + g, 16 * e);
        int rho = w + (item >> 11);
        if (rho >= 3) rho -= 3;
        const int row = item_row(kind, g, kind == K_T ? 2 - rho : rho + (g == 0));
        const uint32_t on = w > 2 || (g == 0 && rho == 2) ? 0 : ~0u, swap = rho == 1 ? 0 : on, base = (0x924924 >> rho) & on;
        uint32_t m = base ^ (swap & (kind == K_L ? 0xB6DB6D : (item_narrow(item) ? (prev == K_KV ? 1 : 0x6D) : prev == K_KV ? 0x861861 : 0x86186D)));
        prev = kind;
        auto step = [&](auto load) {
          if (m & 1) {
            mbar_wait(bar + 48, par);
            mbar_expect_tx(bar, A_STAGE);
            load();
            n++;
            position();
          }
          m >>= 1;
          __syncwarp();
        };
        if (kind >= K_OA) {
          const uint4* src = p.scr + (kind == K_OA ? PL_OA : PL_CTX) * PLANE + row * 16 + rank * 512;
          uint32_t heads = kind == K_OA ? ~0u : 0, need = 1;
          for (int t = 0; t <= nd; t++, need <<= 1) {
            if (~heads & need) heads = wait_bits(p.flags + F_CTX + g * 32, (e & 1) - 1, need);
            if (item_narrow(item) && t > 2) m = (base >> 2) ^ (t == nd ? swap : 0);
#pragma unroll 1
            for (int x = t == 0; x < (t == nd ? 1 : 3); x++)
              step([&]() {
                bulk_load_mc(dst, src, 8192, bar, (uint16_t)3);
                src += PLANE;
              });
          }
        } else {
          const int r = kind == K_L ? row & 1023 : row;
          int blk = (kind == K_L ? (row >> 10) * 16 : 0) + rank;
          if (kind == K_T) m ^= swap & 0x800000;
          if (it == 0) m &= m - 1, m &= m - 1, blk += 4;
#pragma unroll 1
          for (int x = 3 * nd; x; x--)
            step([&]() {
              tma_load_3d_mc(dst, &p.mapA[kind - 1], bar, 0, r, blk, (uint16_t)3);
              blk += 2;
            });
        }
      }
      if (w < 3) {
        mbar_wait(bar0 + 48, (~(n + 1) >> 1) & 1);
        mbar_wait(bar0 + 56, (~n >> 1) & 1);
      }
    } else if (threadIdx.x == 0) {
      const uint32_t e = __ldcg(p.flags + F_EPOCH + blockIdx.x) + 1;
      uint32_t pb = 4;
      for (int it = 0; it < MAXITEMS; it++) {
        const uint32_t item = sched[it];
        const uint32_t kind = item & 7;
        if (kind == K_END) break;
        const int nk = item_nk(item);
        uint32_t heads = kind == K_OB ? wait_bits(p.flags + F_CTX + ((item >> 3) & 15) * 32, (e & 1) - 1, 0) : 0;
        const int keep = p.keep[(blockIdx.x >> 1) * MAXITEMS + it];
        for (int t = it == 0 ? 4 : 0; t < nk; t++, pb++) {
          mbar_wait(bempty0 + 8 * (pb & 3), ((pb >> 2) & 1) ^ 1);
          fill_b(item, t, pb, keep & 32 ? L2_NORMAL : L2_FIRST);
          if (item_narrow(item) && kind == K_OB) {
            const uint32_t g = (item >> 3) & 15, nb = g ? 3 : 2;
            if (!(heads >> t & 2)) heads = wait_bits(p.flags + F_CTX + g * 32, (e & 1) - 1, 0);
            if (heads >> t & 2) prefetch_l2(p.scr + (PL_CTX + t + 1) * PLANE + (3 * g + 2 - nb) * 1024 + rank * nb * 512, nb * 8192);
          }
        }
        if (kind == K_T) {
          const int g = (item >> 3) & 15, j = (item >> 7) & 15;
          const uint4* src = p.scr + (PL_KV + j * 4 + rank) * PLANE;
          const int n = ((3 * g + 1) >> 1) + 1;
          uint32_t groups = 0;
          for (int t = 0; t < n; t++, src += 2048) {
            const uint32_t need = (4u << 2 * min((2 * t + 2) / 3, g)) - 1;
            if (~groups & need) groups = wait_bits(p.flags + F_KV + j * 32, (e & 1) - 1, need);
            const uint32_t nskip = t == n - 1 ? 1 + (g & 1) : 0;
            const uint32_t pol = t < (keep & 31) ? L2_NORMAL : L2_FIRST;
            uint32_t sl = pb & 3;
            mbar_wait(bempty0 + 8 * sl, ((pb >> 2) & 1) ^ 1);
            if (nskip) mbar_arrive_n(bempty0 + 8 * sl, nskip);
            mbar_expect_tx(bfull0 + 8 * sl, 32768);
            pb++;
            if (nskip == 2) {
              bulk_load(bbase + sl * B_SLOT, src, 16384, bfull0 + 8 * sl, pol);
              bulk_load(bbase + sl * B_SLOT + 16384, src + 2 * PLANE, 16384, bfull0 + 8 * sl, pol);
              continue;
            }
            bulk_load(bbase + sl * B_SLOT, src, 32768, bfull0 + 8 * sl, pol);
            sl = pb & 3;
            mbar_wait(bempty0 + 8 * sl, ((pb >> 2) & 1) ^ 1);
            if (nskip) mbar_arrive_n(bempty0 + 8 * sl, nskip);
            mbar_expect_tx(bfull0 + 8 * sl, 32768);
            bulk_load(bbase + sl * B_SLOT, src + 2 * PLANE, 32768, bfull0 + 8 * sl, pol);
            pb++;
          }
        }
      }
    } else if (threadIdx.x == 64) {
      const uint32_t pair = 2 * ((sched[0] >> 7) & 15) + rank;
      if ((sched[0] & 127) == K_L) {
        mbar_wait(carbar + 24, 0);
        asm volatile("fence.proxy.async.shared::cta;\ncp.async.bulk.global.shared::cta.bulk_group [%0], [%1], 2048;\n"
                     "cp.async.bulk.commit_group;\ncp.async.bulk.wait_group 0;\nfence.proxy.async.global;\nfence.acq_rel.gpu;" ::"l"(p.carry + pair * 128),
                     "r"(sbase + SM_CARRY - 2048)
                     : "memory");
        red_add(p.flags + F_CAR + pair);
      }
      if ((sched[0] & 127) == (K_L | 6 << 3)) {
        wait_flag(p.flags + F_CAR + pair, __ldcg(p.flags + F_EPOCH + blockIdx.x) + 1);
        mbar_expect_tx(carbar + 32, 2048);
        bulk_load(sbase + SM_CARRY, p.carry + pair * 128, 2048, carbar + 32);
      }
      for (int it = 0; it < MAXITEMS; it++) {
        const uint32_t item = sched[it];
        const uint32_t kind = item & 7;
        const int g = (item >> 3) & 15, j = (item >> 7) & 15;
        mbar_wait(pub0 + 8 * (kind == K_END ? MAXITEMS - 1 : it), 0);
        if (kind == K_END) break;
        if (kind >= K_OA) continue;
        asm volatile("fence.acq_rel.gpu;" ::: "memory");
        if (kind == K_KV) red_xor(p.flags + F_KV + j * 32, 1u << (2 * g + rank));
        if (kind == K_L) red_add(p.flags + F_L + g);
        if (kind == K_T) red_xor(p.flags + F_CTX + g * 32, 1u << (2 * j + rank));
      }
      red_add(p.flags + F_EPOCH + blockIdx.x);
    } else if (threadIdx.x == 96) {
      for (int i = 0; i < 3; i++) prefetch_tmap(&p.mapA[i]);
      for (int i = 0; i < 6; i++) prefetch_tmap(&p.mapB[i]);
      prefetch_tmap(&p.mapO[0]);
      prefetch_tmap(&p.mapO[1]);
    }
  } else {
    asm volatile("setmaxnreg.inc.sync.aligned.u32 160;");
    const int cw = wg - 1;
    const int wq = __reduce_min_sync(0xffffffffu, (int)((threadIdx.x >> 5) & 3));
    auto turn = [&](uint32_t dep = 0) {
      bar_sync((1 + cw) | dep, NTURN);
    };
    const int fwd = cw == 0 ? 3 : cw, back = cw == 2 ? 1 : cw + 2;
    int next = fwd;
    auto pass = [&]() {
      bar_arrive(next, NTURN);
      next = fwd;
    };
    auto rank_of = [&](uint32_t item) {
      const int r = cw + (item >> 11);
      return r >= 3 ? r - 3 : r;
    };
    if (cw == 1) pass();
    if (cw == 2) { turn(); pass(); }
    const uint32_t abase = sbase + cw * (2 * A_STAGE), afull = afull0 + 16 * cw, aempty = aempty0 + 16 * cw;
    const uint32_t adesc = ((abase & 0x3FFFF) >> 4) | (1u << 16), bdesc = (bbase & 0x3FFFF) >> 4;
    uint32_t pa = 0, pb = 0;
    int it = 0;
    uint32_t item = sched[0];
    auto publish = [&](int i, uint32_t skip = 0) {
      __syncwarp();
      mbar_arrive_if0(pub0 + 8 * i, (threadIdx.x & 31) | skip);
    };
    auto test_ab = [&](uint32_t a, uint32_t b) {
      test_a(afull + 8 * (a & 1), (a >> 1) & 1);
      test_b(bfull0 + 8 * (b & 3), (b >> 2) & 1);
    };
    auto wait_ab = [&]() {
      if (!ready_ab()) {
        mbar_wait_u(afull + 8 * (pa & 1), (pa >> 1) & 1);
        mbar_wait_u(bfull0 + 8 * (pb & 3), (pb >> 2) & 1);
      }
    };
    auto release_ab = [&](uint32_t a, uint32_t b, uint32_t skip) {
      mbar_arrive_cta_if0(wq < 2 ? aempty + 8 * (a & 1) : bempty0 + 8 * (b & 3), wq < 2 ? wq : rank, (threadIdx.x & 31) | (wq == 3) | skip);
    };
    test_ab(0, 0);
    enum { NEW = 1, REL = 2, FWD = 4, TEST = 8, BACK = 16 };
    auto gturn = [&](auto mode_c, bool hold, auto mma, auto meanwhile) {
      constexpr int MODE = decltype(mode_c)::value;
      const uint32_t da = adesc + (pa & 1) * (A_STAGE >> 4), db = bdesc + (pb & 3) * (B_SLOT >> 4);
      if (MODE & NEW) wait_ab();
      else if (!ready_b()) mbar_wait_u(bfull0 + 8 * (pb & 3), (pb >> 2) & 1);
      turn();
      wg_fence();
      mma(da, db);
      wg_commit();
      if (!hold) pass();
      if (hold) {
      } else if (MODE & TEST) test_ab(pa + 1, pb + 1);
      else test_b(bfull0 + 8 * ((pb + 1) & 3), ((pb + 1) >> 2) & 1);
      meanwhile();
      wg_wait<0>();
      if (MODE & REL) {
        if (!hold) release_ab(pa, pb, 0);
      } else {
        mbar_arrive_if0(bempty0 + 8 * (pb & 3), threadIdx.x & 127);
      }
      if (MODE & FWD) pa++;
      if (MODE & BACK) pa--;
      __syncwarp();
      pb++;
    };
    constexpr std::true_type YES{};
    constexpr std::false_type NO{};
    constexpr std::integral_constant<int, NEW> FIRST{};
    constexpr std::integral_constant<int, REL | FWD | TEST> SECOND{};
    constexpr std::integral_constant<int, NEW | REL | FWD | TEST> ONCE{};
    constexpr std::integral_constant<int, NEW | FWD | TEST> X0{};
    constexpr std::integral_constant<int, NEW | BACK> X1{};
    constexpr std::integral_constant<int, REL | FWD> Y0{};
    auto nothing = []() {};
    auto idle = [&]() { return ((item >> 3) & 15) == 0 && rank_of(item) == 2; };
    auto skip_item = [&](int passed) {
      const int n = (item & 7) == K_T ? 10 : item_nk(item);
      publish(it);
#pragma unroll 1
      for (int i = 2 + passed; i < n; i++) {
        turn();
        pass();
      }
      pb += n;
      test_ab(pa, pb);
      item = sched[++it];
    };

    if ((item & 7) == K_L && idle()) skip_item(0);
    float lo_[2][4][4] = {}, ll[2][4] = {};
    uint4* ldst = p.scr;
    uint32_t lnone = 1;
    auto lrelease = [&]() { release_ab(1, 3, lnone); };
    auto lflush = [&]() {
      const uint32_t t = sched_fence() & p.zero;
#pragma unroll
      for (int i = 0; i < 4; i++) {
        const int h = i >> 1, e = i & 1 ? 2 : 0;
        const float f0 = rcp(__uint_as_float(__float_as_uint(ll[h][e]) | t)), f1 = rcp(__uint_as_float(__float_as_uint(ll[h][e + 1]) | t));
        const float(&r0)[4] = lo_[h][e], (&r1)[4] = lo_[h][e + 1];
        stg128_if0(ldst + h * 32 + e * 64, movm_t(pack_bf16(r0[0] * f0, r0[1] * f1)), movm_t(pack_bf16(r0[2] * f0, r0[3] * f1)),
                   movm_t(pack_bf16(r1[0] * f0, r1[1] * f1)), movm_t(pack_bf16(r1[2] * f0, r1[3] * f1)), lnone);
      }
      publish(it - 1, lnone);
    };
    while ((item & 7) == K_L) {
      const int g = (item >> 3) & 15, j = (item >> 7) & 15;
      const int rho = rank_of(item);
      float acc[96];
      auto mma = [&](int kb, bool first) {
        return [&acc, kb, first](uint32_t da, uint32_t db) {
#pragma unroll
          for (int k = 0; k < 4; k++) wgmma_n192_tb(acc, da + kb * 512 + k * 2, (db | (512u << 16)) + k * 128, !(first && k == 0));
        };
      };
      gturn(FIRST, false, mma(0, true), lrelease);
      gturn(SECOND, false, mma(1, false), lflush);
#pragma unroll 1
      for (int d = 7;;) {
        gturn(FIRST, false, mma(0, false), nothing);
        if (--d == 0) break;
        gturn(SECOND, false, mma(1, false), nothing);
      }
      const int lane = threadIdx.x & 31;
      const int from = rho ? rho : 4 * (~g & 1), to = g == 0 ? 3 * rho : rho == 2 ? 4 * (g & 1) : rho + 1;
      uint32_t own, front, vlo;
      gturn(SECOND, true, mma(1, false), [&]() {
        bar_arrive_if(rho != 2, g && rho ? back : next, NTURN);
        own = (wq < 3 ? abase + A_STAGE + wq * 2048 : sbase + SM_CARRY - 8192 + to * 2048) + lane * 16;
        front = (wq > 0 ? abase + A_STAGE + wq * 2048 - 2048 : g == 0 ? abase + A_STAGE : sbase + SM_CARRY - 8192 + from * 2048) + lane * 16;
        vlo = abase + A_STAGE + 8192 + wq * 1024 + lane * 16;
        ldst = p.scr + (PL_OA + j) * PLANE + (item_row(K_L, g, rho + (g == 0)) + wq * 16) * 16 + rank * 64 + (lane ^ (lane >> 3));
        asm volatile("" : "+r"(own), "+r"(front), "+r"(vlo), "+l"(ldst));
        lnone = 0;
        item = sched[++it];
        if (wq == 0 && g != 0) mbar_wait_u(carbar + 8 * from, ((g - (g <= 5 ? 1 : 6)) >> (rho == 0)) & 1);
      });
      if (g && rho == 0) next = back;
      fence_regs(acc);
      uint32_t lo[24], hi[24], hk[8], vt[2][4][4];
#pragma unroll
      for (int i = 0; i < 24; i++) {
        lo[i] = pack_bf16(acc[4 * i], acc[4 * i + 1]);
        hi[i] = pack_bf16(acc[4 * i + 2], acc[4 * i + 3]);
      }
      sts128(own, hi[8], hi[9], hi[10], hi[11]);
      sts128(own + 512, hi[12], hi[13], hi[14], hi[15]);
      stsm4(own + 1024, hi[16], hi[17], hi[18], hi[19]);
      stsm4(own + 1536, hi[20], hi[21], hi[22], hi[23]);
      __syncwarp();
      mbar_arrive_if0(carbar + 8 * to, lane | (wq ^ 3));
      stsm4(vlo, lo[16], lo[17], lo[18], lo[19]);
      stsm4(vlo + 512, lo[20], lo[21], lo[22], lo[23]);
      bar_sync(4 + cw, 128);
      lds128(front, hk[0], hk[1], hk[2], hk[3]);
      lds128(front + 512, hk[4], hk[5], hk[6], hk[7]);
#pragma unroll
      for (int i = 0; i < 8; i++) ldsm4_t((lane < 16 ? (i < 4 ? front : own) + 1024 : vlo - 256) + (i & 3) * 256, vt[i >> 2][i & 3]);
      float sc[3][2][4];
      local_scores(sc[2], lo, hi, hi + 8);
      local_scores(sc[1], lo, hi, lo + 8);
      local_scores(sc[0], lo, hi, hk);
      test_ab(pa, pb);
      local_attn(lo_, ll, sc, vt, g == 0 && wq == 0, lane);
      bar_arrive_if(rho == 2, back, NTURN);
    }
    if (!lnone) {
      bar_sync(4 + cw, 128);
      lrelease();
      lflush();
    }

    float Y[64];
    float sc0 = 0.f, sc1 = 0.f;
    uint32_t done;
    uint4* pdst;
    auto pack = [&](uint32_t (&r)[16], const float (&acc)[64], int h, float s0, float s1) {
#pragma unroll
      for (int i = 0; i < 8; i++) {
        const int c = 32 * h + 4 * i;
        r[8 * (i >> 2) + (i & 3)] = pack_bf16(acc[c] * s0, acc[c + 1] * s0);
        r[8 * (i >> 2) + (i & 3) + 4] = pack_bf16(acc[c + 2] * s1, acc[c + 3] * s1);
      }
    };
    auto pack_now = [&](uint32_t (&r)[16], const float (&acc)[64], int h) {
      pack(r, acc, h, sc0, sc1);
#pragma unroll
      for (int i = 0; i < 16; i++) asm volatile("" : "+r"(r[i])::"memory");
    };
    auto stores = [&](auto ofs_c, const uint32_t (&r)[16], uint32_t sel) {
      constexpr int OFS = decltype(ofs_c)::value;
      stg128_sel<OFS>(pdst, r[0], r[1], r[2], r[3], sel);
      stg128_sel<OFS + 128>(pdst, r[4], r[5], r[6], r[7], sel);
      stg128_sel<OFS + 32>(pdst, r[8], r[9], r[10], r[11], sel);
      stg128_sel<OFS + 160>(pdst, r[12], r[13], r[14], r[15], sel);
    };
    constexpr std::integral_constant<int, 0> H0{};
    constexpr std::integral_constant<int, 64> H1{};
    auto flush = [&]() {
      uint32_t r[16];
      turn();
      pass();
      sched_fence();
      pack(r, Y, 0, sc0, sc1);
      stores(H0, r, done);
      turn();
      pass();
      sched_fence();
      pack(r, Y, 1, sc0, sc1);
      stores(H1, r, done);
      publish(it - 1, done & 1);
    };
    auto no_pending = [&]() {
      done = 1;
      pdst = p.scr;
#pragma unroll
      for (int i = 0; i < 64; i++) Y[i] = 0.f;
    };
    no_pending();
    auto mma128 = [&](auto scr_c, float (&acc)[64], int keep) {
      return [&acc, keep](uint32_t da, uint32_t db) {
        constexpr bool SCR = decltype(scr_c)::value;
#pragma unroll
        for (int k = 0; k < 8; k++)
          wgmma_n128<1>(acc, da + (k & 1) * 2 + ((k >> 1) & 1) * (SCR ? 32 : 4) + (k >> 2) * (SCR ? 64 : 512), SCR ? HI64 : HI128,
                        (db | (1024u << 16)) + k * 128, HI128, k != 0 || keep);
      };
    };
    auto first_two = [&](auto mode0, auto mode1, auto scr_c, float (&X)[64]) {
      uint32_t r0[16], r1[16];
      gturn(mode0, false, mma128(scr_c, X, false), [&]() { pack_now(r0, Y, 0); });
      stores(H0, r0, done);
      gturn(mode1, false, mma128(scr_c, X, true), [&]() { pack_now(r1, Y, 1); });
      stores(H1, r1, done);
      publish(it - 1, done & 1);
    };
    auto all_but_last_two = [&](auto scr_c, float (&X)[64]) {
      int n = item_nk(item);
      first_two(X0, X1, scr_c, X);
      gturn(Y0, false, mma128(scr_c, Y, false), nothing);
#pragma unroll 1
      while (true) {
        gturn(SECOND, false, mma128(scr_c, Y, true), nothing);
        gturn(X0, false, mma128(scr_c, X, true), nothing);
        gturn(X1, false, mma128(scr_c, X, true), nothing);
        if (!decltype(scr_c)::value || (n -= 4) == 4) break;
        gturn(Y0, false, mma128(scr_c, Y, true), nothing);
      }
      fence_regs(X);
    };
    while ((item & 7) < K_OA) {
      if (idle()) {
        flush();
        done = 1;
        skip_item(2);
        continue;
      }
      const uint32_t kind = item & 7;
      const int g = (item >> 3) & 15, j = (item >> 7) & 15;
      const int rho = rank_of(item);
      if (kind != K_T) {
        float X[64];
        all_but_last_two(NO, X);
        const int lane = threadIdx.x & 31;
        const int row = item_row(K_KV, g, rho + (g == 0)) + wq * 16;
        sc0 = sc1 = rank ? 1.f : QS;
        pdst = p.scr + (PL_KV + j * 4 + rank * 2 + 1) * PLANE + row * 16 + (lane ^ (lane >> 3));
        uint32_t r0[16], r1[16];
        pack(r0, X, 0, sc0, sc1);
        stores(std::integral_constant<int, -PLANE>{}, r0, 0);
        gturn(Y0, false, mma128(NO, Y, true), [&]() { pack_now(r1, X, 1); });
        stores(std::integral_constant<int, 64 - PLANE>{}, r1, 0);
        item = sched[++it];
        gturn(SECOND, false, mma128(NO, Y, true), nothing);
        test_ab(pa, pb);
        fence_regs(Y);
        done = 0;
      } else {
        float(&O)[64] = Y;
        float S[64];
        float l0 = 0.f, l1 = 0.f;
        float zlim;
        const uint32_t sel = threadIdx.x & 127;
        const int b = 3 * g + 1 - rho;
        first_two(ONCE, ONCE, NO, S);
#pragma unroll 1
        for (int n = 0; n < 5; n++) gturn(ONCE, false, mma128(NO, S, true), nothing);
#pragma unroll
        for (int i = 0; i < 64; i++) O[i] = 0.f;
        fence_regs(O);
        gturn(FIRST, false, mma128(NO, S, true), nothing);
        fence_regs(S);
        {
          const uint32_t lane = threadIdx.x & 31, dst = abase + (pa & 1) * A_STAGE + wq * 2048 + (lane ^ (lane >> 3)) * 16;
#pragma unroll
          for (int h = 0; h < 2; h++) {
            uint32_t r[16];
            pack(r, S, h, 1.f, 1.f);
#pragma unroll
            for (int i = 0; i < 4; i++) {
              sts128(dst + h * 8192 + (i >> 1) * 512 + (i & 1) * 1024, r[4 * i], r[4 * i + 1], r[4 * i + 2], r[4 * i + 3]);
              if (4 * h + i < 7) __nanosleep(30);
            }
          }
          asm volatile("fence.proxy.async.shared::cta;" ::: "memory");
        }
        enum { MID, LAST, HALF };
        auto round = [&](auto mode_c) {
          constexpr int MODE = decltype(mode_c)::value;
          constexpr bool INIT = MODE == LAST;
          constexpr int NI = MODE == HALF ? 8 : 16;
          const uint32_t shared = MODE == HALF ? rho == 0 : 0;
          const uint32_t tv = pb + 1 - shared;
          {
            const uint32_t dq = adesc + (pa & 1) * (A_STAGE >> 4);
            const uint32_t dk = (bdesc + (pb & 3) * 2048) | (1u << 16);
            if (INIT) {
              const int lane = threadIdx.x & 31;
              const int row = (wq * 16 + (lane >> 2) - 2 * (lane & 3) + 11) << 23;
              const int r0 = row ^ (__float_as_uint(l0) & p.zero & (MODE + 16)), r1 = row ^ (__float_as_uint(l1) & p.zero & (MODE + 16));
#pragma unroll
              for (int i = 0; i < 4 * NI; i++) {
                const int c = i - 4 * (NI - 8);
                S[i] = c < 0 ? 0.f : __int_as_float((c & 2 ? r1 : r0) + ((4 * (c & 2) - 2 * (c & ~3) - (c & 1) - 11) << 23));
                asm volatile("" : "+f"(S[i])::"memory");
              }
            }
            if (!ready_b()) mbar_wait_u(bfull0 + 8 * (pb & 3), (pb >> 2) & 1);
            turn();
            wg_fence();
#pragma unroll
            for (int k = 0; k < 8; k++) {
              const uint32_t da = dq + (k >> 2) * 512 + (k & 2) * 16 + (k & 1) * 2, db = dk + (k >> 1) * 32 + (k & 1) * 2;
              if (MODE == HALF) wgmma_n64(S, da, db, k != 0 || INIT);
              else wgmma_n128<0>(S, da, HIQ, db, HI64, k != 0 || INIT);
            }
            wg_commit();
            pass();
          }
          test_b(bfull0 + 8 * (tv & 3), (tv >> 2) & 1);
          if (!ready_b()) mbar_wait_u(bfull0 + 8 * (tv & 3), (tv >> 2) & 1);
          wg_wait<0>();
#pragma unroll
          for (int i = 0; i < 4 * NI; i++) asm volatile("" : "+f"(S[i])::"memory");
          mbar_arrive_if0(bempty0 + 8 * (pb & 3), sel | shared);
          if (MODE >= LAST) mbar_arrive_cta_if0(aempty + 8 * (pa & 1), wq & 1, (sel & 31) | (wq >> 1));
          uint32_t P[2 * NI];
          if (MODE >= LAST && !INIT) {
            const int lane = threadIdx.x & 31;
            const int row = wq * 16 + (lane >> 2) - 2 * (lane & 3);
#pragma unroll
            for (int i = 0; i < 8; i++) {
#pragma unroll
              for (int e = 0; e < 2; e++) {
                if (8 * i + e > row) S[4 * (NI - 8 + i) + e] = -INFINITY;
                if (8 * i + e > row + 8) S[4 * (NI - 8 + i) + 2 + e] = -INFINITY;
              }
            }
          }
          float s0 = 0.f, s1 = 0.f, t0 = 0.f, t1 = 0.f;
#pragma unroll
          for (int i = 0; i < NI; i++) {
#pragma unroll
            for (int e = 0; e < 4; e++) S[4 * i + e] = ex2(S[4 * i + e]);
            s0 += S[4 * i];
            t0 += S[4 * i + 1];
            s1 += S[4 * i + 2];
            t1 += S[4 * i + 3];
            P[2 * i] = pack_bf16(S[4 * i], S[4 * i + 1]);
            P[2 * i + 1] = pack_bf16(S[4 * i + 2], S[4 * i + 3]);
          }
          l0 += s0 + t0;
          l1 += s1 + t1;
          uint32_t dep = (__float_as_uint(l0) ^ __float_as_uint(l1)) ^ P[2 * NI - 1];
          fence_regs(O);
#pragma unroll
          for (int i = 0; i < 2 * NI; i++) asm volatile("" : "+r"(P[i])::"memory");
          turn(dep & p.zero);
          wg_fence();
          const uint32_t dv = (bdesc + (tv & 3) * 2048 + shared * 1024) | (32u << 16);
#pragma unroll
          for (int k = 0; k < NI / 2; k++)
            wgmma_n128_rs_tb(O, P[4 * k], P[4 * k + 1], P[4 * k + 2], P[4 * k + 3], dv + k * 256, 1);
          wg_commit();
          pass();
          pb = tv + 1;
          if (MODE >= LAST) {
            const int nskip = 1 + (g & 1);
            if (rho + nskip >= 3) pb += 3 - nskip;
            pa++;
          } else {
            test_b(bfull0 + 8 * (pb & 3), (pb >> 2) & 1);
          }
          if (MODE >= LAST) {
            l0 += __shfl_xor_sync(0xffffffffu, l0, 1);
            l1 += __shfl_xor_sync(0xffffffffu, l1, 1);
            l0 += __shfl_xor_sync(0xffffffffu, l0, 2);
            l1 += __shfl_xor_sync(0xffffffffu, l1, 2);
            sc0 = rcp(l0);
            sc1 = rcp(l1);
            zlim = l0 <= KB_LIMIT && l0 >= KB_LOW && l1 <= KB_LIMIT && l1 >= KB_LOW ? 3e38f : -1.f;
          }
          wg_wait<0>();
          fence_regs(O);
          mbar_arrive_if0(bempty0 + 8 * (tv & 3), sel);
        };
#pragma unroll 1
        for (int n = b >> 1; n; n--) round(std::integral_constant<int, MID>{});
        item = sched[++it];
        if (b & 1) round(std::integral_constant<int, LAST>{});
        else round(std::integral_constant<int, HALF>{});
        test_ab(pa, pb);
        float z[4] = {0.f, 0.f, 0.f, 0.f};
#pragma unroll
        for (int i = 0; i < 32; i++) z[i & 3] = fmaf(O[2 * i], O[2 * i + 1], z[i & 3]);
        const bool bad = !(fabsf(z[0]) + fabsf(z[1]) + fabsf(z[2]) + fabsf(z[3]) <= zlim);
        const int lane = threadIdx.x & 31;
        pdst = p.scr + (PL_CTX + 2 * j + rank) * PLANE + (b * 64 + wq * 16) * 16 + (lane ^ (lane >> 3));
        done = p.keep[(blockIdx.x >> 1) * MAXITEMS + it - 1] >> 6;
        if (__any_sync(0xffffffffu, bad)) {
          attn_fallback(p.scr + (PL_CTX + 2 * j + rank) * PLANE, p.scr + (PL_KV + j * 4 + rank) * PLANE, p.x,
                        p.wq + (2 * j + rank) * 128, b * 64 + wq * 16, threadIdx.x & 31);
          publish(it - 1);
          no_pending();
          test_ab(pa, pb);
        }
      }
    }

    bool relay = true;
    if (idle()) {
      flush();
      skip_item(2);
    } else {
      const uint32_t kind = item & 7;
      const int g = (item >> 3) & 15, j = (item >> 7) & 15;
      const int row = item_row(kind, g, rank_of(item) + (g == 0)) + wq * 16;
      auto epilogue = [&](float (&acc)[64], int cb, bool pace) {
        const int lane = threadIdx.x & 31;
        const uint32_t stg = abase + ((pa - 1) & 1) * A_STAGE + wq * 4096;
        const int srow = lane & 15;
#pragma unroll
        for (int jj = 0; jj < 8; jj++) {
          const uint32_t r0 = pack_bf16(acc[8 * jj + 0], acc[8 * jj + 1]);
          const uint32_t r1 = pack_bf16(acc[8 * jj + 2], acc[8 * jj + 3]);
          const uint32_t r2 = pack_bf16(acc[8 * jj + 4], acc[8 * jj + 5]);
          const uint32_t r3 = pack_bf16(acc[8 * jj + 6], acc[8 * jj + 7]);
          const int chunk = (2 * jj + (lane >> 4)) & 7;
          const uint32_t addr = stg + (jj >> 2) * 2048 + srow * 128 + ((chunk ^ (srow & 7)) << 4);
          asm volatile("stmatrix.sync.aligned.m8n8.x4.shared.b16 [%0], {%1,%2,%3,%4};" ::"r"(addr), "r"(r0), "r"(r1), "r"(r2), "r"(r3)
                       : "memory");
          if (jj < 7 && pace) __nanosleep(30);
        }
        asm volatile("fence.proxy.async.shared::cta;" ::: "memory");
        __syncwarp();
        if (lane == 0) {
          const int col = cb * 128 + (kind == K_OA ? (row >> 10) * 2048 : 1024);
          const int r = kind == K_OA ? row & 1023 : row;
          tma_store_2d(&p.mapO[kind - K_OA], stg, col, r);
          tma_store_2d(&p.mapO[kind - K_OA], stg + 2048, col + 64, r);
          asm volatile("cp.async.bulk.commit_group;" ::: "memory");
        }
      };
      float X[64];
      relay = g == 0;
      const int last = g && rank_of(item) == 1 ? back : fwd;
      if (item_narrow(item)) {
        int n = item_nk(item);
        first_two(ONCE, ONCE, YES, X);
#pragma unroll 1
        while (--n > 1) {
          if (n == 2) next = last;
          gturn(ONCE, false, mma128(YES, X, true), nothing);
        }
        fence_regs(X);
        epilogue(X, 2 * j + rank - 8, rank_of(item) == 0);
      } else {
        all_but_last_two(YES, X);
        gturn(Y0, false, mma128(YES, Y, true), nothing);
        epilogue(X, 4 * j + 2 * rank, true);
        next = last;
        gturn(SECOND, false, mma128(YES, Y, true), nothing);
        fence_regs(Y);
        epilogue(Y, 4 * j + 2 * rank + 1, rank_of(item) == 0);
      }
      publish(it);
      item = sched[++it];
    }
    const int rho = rank_of(item);
    if (rho == 0 && relay) {
      turn();
      pass();
    }
    if (rho == 1) turn();
    publish(MAXITEMS - 1);
    asm volatile("cp.async.bulk.wait_group.read 0;" ::: "memory");
  }
}

typedef CUresult (*EncodeFn)(CUtensorMap*, CUtensorMapDataType, cuuint32_t, void*, const cuuint64_t*, const cuuint64_t*,
                             const cuuint32_t*, const cuuint32_t*, CUtensorMapInterleave, CUtensorMapSwizzle, CUtensorMapL2promotion,
                             CUtensorMapFloatOOBfill);

void make_map(EncodeFn enc, CUtensorMap* m, const void* ptr, uint64_t d0, uint64_t d1, uint64_t d2, uint64_t s1, uint64_t s2, uint32_t b0,
              uint32_t b1, uint32_t b2) {
  cuuint64_t gd[3] = {d0, d1, d2}, gs[2] = {s1, s2};
  cuuint32_t bd[3] = {b0, b1, b2}, es[3] = {1, 1, 1};
  enc(m, CU_TENSOR_MAP_DATA_TYPE_BFLOAT16, d2 ? 3 : 2, const_cast<void*>(ptr), gd, gs, bd, es, CU_TENSOR_MAP_INTERLEAVE_NONE,
      CU_TENSOR_MAP_SWIZZLE_128B, CU_TENSOR_MAP_L2_PROMOTION_L2_128B, CU_TENSOR_MAP_FLOAT_OOB_FILL_NONE);
}

struct HostState {
  Params p;
  const void* in[9];
  void* out;
  bool valid;
};
HostState g_hs;

const uint16_t h_sched[NCLUSTERS * MAXITEMS] = {
    690, 698, 706, 714, 722, 1425, 1561, 1977, 1601, 829, 7, 7, 7, 7, 7, 7,
    265, 851, 969, 1315, 1833, 1843, 60, 7, 7, 7, 7, 7, 7, 7, 7, 7,
    705, 643, 521, 515, 979, 1451, 957, 7, 7, 7, 7, 7, 7, 7, 7, 7,
    386, 394, 402, 410, 418, 426, 1825, 1595, 148, 7, 7, 7, 7, 7, 7, 7,
    337, 795, 897, 937, 1083, 1353, 1987, 188, 7, 7, 7, 7, 7, 7, 7, 7,
    329, 187, 1099, 1699, 661, 7, 7, 7, 7, 7, 7, 7, 7, 7, 7, 7,
    178, 186, 194, 202, 210, 1337, 1689, 1473, 1873, 701, 7, 7, 7, 7, 7, 7,
    433, 153, 331, 1305, 1163, 1457, 1707, 517, 7, 7, 7, 7, 7, 7, 7, 7,
    281, 779, 529, 523, 1059, 1307, 1555, 813, 7, 7, 7, 7, 7, 7, 7, 7,
    833, 179, 929, 1067, 1809, 1995, 52, 7, 7, 7, 7, 7, 7, 7, 7, 7,
    665, 163, 571, 57, 1945, 1569, 1419, 909, 7, 7, 7, 7, 7, 7, 7, 7,
    385, 139, 275, 963, 1545, 1739, 156, 7, 7, 7, 7, 7, 7, 7, 7, 7,
    129, 145, 307, 1075, 1209, 1875, 4, 7, 7, 7, 7, 7, 7, 7, 7, 7,
    441, 211, 1289, 1347, 1745, 717, 7, 7, 7, 7, 7, 7, 7, 7, 7, 7,
    193, 411, 595, 1211, 693, 7, 7, 7, 7, 7, 7, 7, 7, 7, 7, 7,
    393, 161, 315, 1281, 11, 1801, 1747, 84, 7, 7, 7, 7, 7, 7, 7, 7,
    689, 683, 561, 1051, 1177, 1955, 1617, 845, 7, 7, 7, 7, 7, 7, 7, 7,
    793, 835, 577, 19, 1417, 1491, 36, 7, 7, 7, 7, 7, 7, 7, 7, 7,
    673, 811, 907, 1065, 49, 1329, 1971, 981, 7, 7, 7, 7, 7, 7, 7, 7,
    681, 387, 513, 547, 81, 35, 1225, 1579, 773, 7, 7, 7, 7, 7, 7, 7,
    2, 10, 18, 26, 34, 42, 1961, 1723, 196, 7, 7, 7, 7, 7, 7, 7,
    417, 171, 1033, 1043, 1313, 1195, 1729, 653, 7, 7, 7, 7, 7, 7, 7, 7,
    201, 403, 537, 971, 1673, 1611, 76, 7, 7, 7, 7, 7, 7, 7, 7, 7,
    185, 169, 291, 569, 51, 1593, 1481, 1609, 949, 7, 7, 7, 7, 7, 7, 7,
    769, 435, 923, 1105, 1227, 853, 7, 7, 7, 7, 7, 7, 7, 7, 7, 7,
    817, 155, 587, 1921, 1483, 645, 7, 7, 7, 7, 7, 7, 7, 7, 7, 7,
    649, 147, 531, 1107, 1459, 901, 7, 7, 7, 7, 7, 7, 7, 7, 7, 7,
    642, 650, 658, 666, 674, 682, 1795, 1979, 204, 7, 7, 7, 7, 7, 7, 7,
    258, 266, 274, 282, 290, 298, 1539, 1467, 164, 7, 7, 7, 7, 7, 7, 7,
    305, 203, 961, 1331, 1867, 132, 7, 7, 7, 7, 7, 7, 7, 7, 7, 7,
    130, 138, 146, 154, 162, 170, 1697, 1851, 212, 7, 7, 7, 7, 7, 7, 7,
    514, 522, 530, 538, 546, 554, 1411, 1427, 797, 7, 7, 7, 7, 7, 7, 7,
    465, 691, 947, 1929, 1817, 1731, 20, 7, 7, 7, 7, 7, 7, 7, 7, 7,
    457, 659, 563, 3, 1321, 1441, 1443, 589, 7, 7, 7, 7, 7, 7, 7, 7,
    257, 699, 915, 1097, 1355, 941, 7, 7, 7, 7, 7, 7, 7, 7, 7, 7,
    770, 778, 786, 794, 802, 810, 1923, 1683, 549, 7, 7, 7, 7, 7, 7, 7,
    713, 451, 1057, 977, 1363, 917, 7, 7, 7, 7, 7, 7, 7, 7, 7, 7,
    946, 954, 962, 970, 978, 1283, 1217, 1705, 1865, 677, 7, 7, 7, 7, 7, 7,
    306, 314, 322, 330, 338, 1665, 1819, 1993, 805, 7, 7, 7, 7, 7, 7, 7,
    273, 675, 913, 1091, 1681, 1475, 44, 7, 7, 7, 7, 7, 7, 7, 7, 7,
    137, 723, 67, 1577, 1857, 565, 7, 7, 7, 7, 7, 7, 7, 7, 7, 7,
    297, 443, 1035, 1089, 65, 1345, 1827, 933, 7, 7, 7, 7, 7, 7, 7, 7,
    209, 177, 339, 1169, 1219, 525, 7, 7, 7, 7, 7, 7, 7, 7, 7, 7,
    825, 467, 75, 1803, 821, 7, 7, 7, 7, 7, 7, 7, 7, 7, 7, 7,
    849, 803, 539, 1081, 73, 1489, 1835, 725, 7, 7, 7, 7, 7, 7, 7, 7,
    801, 195, 9, 83, 2001, 789, 7, 7, 7, 7, 7, 7, 7, 7, 7, 7,
    697, 667, 905, 955, 1201, 1619, 12, 7, 7, 7, 7, 7, 7, 7, 7, 7,
    898, 906, 914, 922, 930, 938, 1667, 1811, 573, 7, 7, 7, 7, 7, 7, 7,
    449, 787, 267, 931, 1179, 1465, 1547, 965, 7, 7, 7, 7, 7, 7, 7, 7,
    50, 58, 66, 74, 82, 1409, 1433, 1947, 597, 7, 7, 7, 7, 7, 7, 7,
    777, 459, 585, 1323, 1969, 1587, 172, 7, 7, 7, 7, 7, 7, 7, 7, 7,
    289, 819, 939, 1185, 1931, 1841, 1849, 709, 7, 7, 7, 7, 7, 7, 7, 7,
    401, 395, 545, 555, 1161, 1203, 1985, 781, 7, 7, 7, 7, 7, 7, 7, 7,
    313, 715, 1073, 1153, 1291, 1585, 1603, 28, 7, 7, 7, 7, 7, 7, 7, 7,
    409, 827, 945, 25, 1299, 1553, 1691, 541, 7, 7, 7, 7, 7, 7, 7, 7,
    785, 707, 953, 33, 1235, 973, 7, 7, 7, 7, 7, 7, 7, 7, 7, 7,
    809, 131, 283, 1041, 1027, 41, 1187, 1713, 1737, 533, 7, 7, 7, 7, 7, 7,
    721, 419, 579, 1193, 1953, 1859, 140, 7, 7, 7, 7, 7, 7, 7, 7, 7,
    841, 771, 323, 1297, 1171, 1233, 1939, 669, 7, 7, 7, 7, 7, 7, 7, 7,
    641, 843, 17, 43, 1571, 837, 7, 7, 7, 7, 7, 7, 7, 7, 7, 7,
    321, 299, 921, 1, 27, 1937, 2003, 68, 7, 7, 7, 7, 7, 7, 7, 7,
    562, 570, 578, 586, 594, 1537, 1361, 1435, 581, 7, 7, 7, 7, 7, 7, 7,
    434, 442, 450, 458, 466, 1155, 1963, 925, 7, 7, 7, 7, 7, 7, 7, 7,
    818, 826, 834, 842, 850, 1793, 1449, 1563, 557, 7, 7, 7, 7, 7, 7, 7,
    425, 427, 1025, 1049, 59, 1721, 1715, 180, 7, 7, 7, 7, 7, 7, 7, 7,
    657, 651, 259, 553, 899, 593, 1339, 1675, 685, 7, 7, 7, 7, 7, 7, 7,
};

void setup(void* const* d_in, void* d_out) {
  void* fn = nullptr;
  cudaDriverEntryPointQueryResult qr;
  cudaGetDriverEntryPoint("cuTensorMapEncodeTiled", &fn, cudaEnableDefault, &qr);
  EncodeFn enc = (EncodeFn)fn;
  void *scr, *carry, *flags;
  cudaGetSymbolAddress(&scr, g_scr);
  cudaGetSymbolAddress(&carry, g_carry);
  cudaGetSymbolAddress(&flags, g_flags);
  Params& p = g_hs.p;
  make_map(enc, &p.mapA[2], d_in[3], 64, 2048, 16, 2048, 128, 64, 64, 1);
  make_map(enc, &p.mapA[0], d_in[4], 64, 2048, 8, 1024, 128, 64, 64, 1);
  make_map(enc, &p.mapA[1], d_in[0], 64, 1024, 32, 4096, 128, 64, 64, 1);
  make_map(enc, &p.mapB[3], d_in[5], 64, 1024, 64, 8192, 128, 64, 128, 2);
  make_map(enc, &p.mapB[1], d_in[6], 64, 512, 64, 8192, 128, 64, 128, 2);
  make_map(enc, &p.mapB[2], d_in[1], 1024, 1024, 3, 6144, 2048, 64, 64, 3);
  make_map(enc, &p.mapB[0], d_in[7], 64, 512, 64, 8192, 128, 64, 128, 2);
  make_map(enc, &p.mapB[5], d_in[8], 64, 4096, 16, 2048, 128, 64, 128, 2);
  {
    cuuint64_t gd[5] = {1024, 2, 4, 4, 32}, gs[4] = {2048, 8 * 2048, 2 * 2048, 32 * 2048};
    cuuint32_t bd[5] = {64, 2, 4, 4, 4}, es[5] = {1, 1, 1, 1, 1};
    enc(&p.mapB[4], CU_TENSOR_MAP_DATA_TYPE_BFLOAT16, 5, d_in[2], gd, gs, bd, es, CU_TENSOR_MAP_INTERLEAVE_NONE, CU_TENSOR_MAP_SWIZZLE_128B,
        CU_TENSOR_MAP_L2_PROMOTION_L2_128B, CU_TENSOR_MAP_FLOAT_OOB_FILL_NONE);
  }
  make_map(enc, &p.mapO[0], d_out, 4096, 1024, 0, 8192, 0, 64, 16, 1);
  make_map(enc, &p.mapO[1], d_out, 2048, 2048, 0, 4096, 0, 64, 16, 1);
  p.scr = (uint4*)scr;
  p.carry = (uint4*)carry;
  p.flags = (uint32_t*)flags;
  p.x = (const uint32_t*)d_in[3];
  p.wq = (const uint16_t*)d_in[5];
  p.zero = 0;
  for (int c = 0; c < NCLUSTERS; c++) {
    int rot = 0;
    for (int i = c * MAXITEMS; i < (c + 1) * MAXITEMS; i++) {
      const int kind = h_sched[i] & 7, g = (h_sched[i] >> 3) & 15;
      p.sched[i] = (uint16_t)(h_sched[i] | rot << 11);
      rot = (rot + (kind == K_T ? 1 + (g & 1) : g == 0)) % 3;
    }
  }
  int start[NCLUSTERS * MAXITEMS];
  for (int i = 0, t = 0; i < NCLUSTERS * MAXITEMS; i++) {
    const int kind = h_sched[i] & 7, g = (h_sched[i] >> 3) & 15;
    if (i % MAXITEMS == 0) t = 0;
    start[i] = t;
    t += (g ? 3 : 2) * (kind == K_L ? 13 : 8) + (kind == K_T ? 9 * g + 6 : 0);
  }
  for (int i = 0; i < NCLUSTERS * MAXITEMS; i++) {
    int keep = 0;
    for (int k = 0; k < NCLUSTERS * MAXITEMS; k++)
      if (!((h_sched[i] ^ h_sched[k]) & 0x787) && start[k] > start[i] + 3) {
        const int n = 32 | ((3 * ((h_sched[k] >> 3) & 15) + 3) >> 1);
        if (n > keep) keep = n;
      }
    if (start[i] + 9 * ((h_sched[i] >> 3) & 15) < 200) keep |= 128;
    p.keep[i] = (uint8_t)keep;
  }
  cudaFuncSetAttribute(fused_kernel, cudaFuncAttributeMaxDynamicSharedMemorySize, SM_TOTAL);
  for (int i = 0; i < 9; i++) g_hs.in[i] = d_in[i];
  g_hs.out = d_out;
  g_hs.valid = true;
}

}

extern "C" void kernel_launch(void* const* d_in, const int* in_sizes, int n_in, void* d_out, int out_size) {
  (void)in_sizes;
  (void)n_in;
  (void)out_size;
  bool ok = g_hs.valid && g_hs.out == d_out;
  for (int i = 0; ok && i < 9; i++) ok = g_hs.in[i] == d_in[i];
  if (!ok) setup(d_in, d_out);
  fused_kernel<<<NCLUSTERS * 2, 512, SM_TOTAL, cudaStreamPerThread>>>(g_hs.p);
}
```

```cpp
#include <cuda_runtime.h>
#include <cuda_bf16.h>
#include <cuda.h>
#include <stdint.h>
#include <type_traits>

namespace {

typedef __nv_bfloat16 bf16;

__device__ __forceinline__ uint32_t smem_u32(const void* p) { return (uint32_t)__cvta_generic_to_shared(p); }
__device__ __forceinline__ void mbar_init(uint32_t bar, uint32_t cnt) {
  asm volatile("mbarrier.init.shared::cta.b64 [%0], %1;" ::"r"(bar), "r"(cnt) : "memory");
}
__device__ __forceinline__ void mbar_expect_tx(uint32_t bar, uint32_t bytes) {
  asm volatile("mbarrier.arrive.expect_tx.shared::cta.b64 _, [%0], %1;" ::"r"(bar), "r"(bytes) : "memory");
}
__device__ __forceinline__ void mbar_arrive_n(uint32_t bar, uint32_t n) {
  asm volatile("mbarrier.arrive.shared::cta.b64 _, [%0], %1;" ::"r"(bar), "r"(n) : "memory");
}
__device__ __forceinline__ void mbar_arrive_if0(uint32_t bar, uint32_t sel) {
  asm volatile("{\n.reg .pred p;\nsetp.eq.u32 p, %1, 0;\n@p mbarrier.arrive.shared::cta.b64 _, [%0];\n}" ::"r"(bar), "r"(sel) : "memory");
}
__device__ __forceinline__ void mbar_arrive_cta_if0(uint32_t bar, uint32_t cta, uint32_t sel) {
  asm volatile("{\n.reg .pred p;\n.reg .b32 ra;\nsetp.eq.u32 p, %2, 0;\nmapa.shared::cluster.u32 ra, %0, %1;\n"
               "@p mbarrier.arrive.shared::cluster.b64 _, [ra];\n}" ::"r"(bar),
               "r"(cta), "r"(sel)
               : "memory");
}
__device__ __forceinline__ void mbar_wait(uint32_t bar, uint32_t parity) {
  uint32_t done;
  uint32_t it = 0;
#pragma unroll 1
  while (true) {
    asm volatile("{\n.reg .pred p;\nmbarrier.try_wait.parity.shared::cta.b64 p, [%1], %2, 1000;\nselp.u32 %0, 1, 0, p;\n}"
                 : "=r"(done)
                 : "r"(bar), "r"(parity)
                 : "memory");
    if (done) break;
    if (++it > (1u << 24)) __trap();
  }
}
__device__ __forceinline__ void mbar_wait_u(uint32_t bar, uint32_t parity) {
  uint32_t it = 0;
#pragma unroll 1
  while (true) {
    uint32_t done;
    asm volatile("{\n.reg .pred p, q;\nmbarrier.try_wait.parity.shared::cta.b64 p, [%1], %2;\nvote.sync.all.pred q, p, 0xffffffff;\nselp.u32 %0, 1, 0, q;\n}"
                 : "=r"(done)
                 : "r"(bar), "r"(parity)
                 : "memory");
    if (done) break;
    if (++it > (1u << 20)) break;
  }
}
#define DECLARE_READY() asm volatile(".reg .pred RDYA, RDYB;")
__device__ __forceinline__ void test_a(uint32_t bar, uint32_t parity) {
  asm volatile("mbarrier.test_wait.parity.shared::cta.b64 RDYA, [%0], %1;" ::"r"(bar), "r"(parity) : "memory");
}
__device__ __forceinline__ void test_b(uint32_t bar, uint32_t parity) {
  asm volatile("mbarrier.test_wait.parity.shared::cta.b64 RDYB, [%0], %1;" ::"r"(bar), "r"(parity) : "memory");
}
__device__ __forceinline__ uint32_t ready_b(uint32_t dep = 0) {
  uint32_t r;
  asm volatile("{\n.reg .pred q;\nsetp.eq.and.u32 q, %1, 0, RDYB;\nvote.sync.all.pred q, q, 0xffffffff;\nselp.u32 %0, 1, 0, q;\n}" : "=r"(r) : "r"(dep) : "memory");
  return r;
}
__device__ __forceinline__ uint32_t ready_ab() {
  uint32_t r;
  asm volatile("{\n.reg .pred q;\nand.pred q, RDYA, RDYB;\nvote.sync.all.pred q, q, 0xffffffff;\nselp.u32 %0, 1, 0, q;\n}" : "=r"(r)::"memory");
  return r;
}
__device__ __forceinline__ void tma_load_3d(uint32_t dst, const CUtensorMap* m, uint32_t bar, int c0, int c1, int c2) {
  asm volatile("cp.async.bulk.tensor.3d.shared::cluster.global.mbarrier::complete_tx::bytes [%0], [%1, {%3, %4, %5}], [%2];" ::"r"(dst),
               "l"(m), "r"(bar), "r"(c0), "r"(c1), "r"(c2)
               : "memory");
}
constexpr uint32_t L2_NORMAL = 0x10000000u, L2_FIRST = 0x12F00000u;
__device__ __forceinline__ void tma_load_3d(uint32_t dst, const CUtensorMap* m, uint32_t bar, int c0, int c1, int c2, uint32_t pol) {
  asm volatile("{\n.reg .b64 h;\nmov.b64 h, {0, %6};\n"
               "cp.async.bulk.tensor.3d.shared::cluster.global.mbarrier::complete_tx::bytes.L2::cache_hint [%0], [%1, {%3, %4, %5}], [%2], h;\n}" ::"r"(dst),
               "l"(m), "r"(bar), "r"(c0), "r"(c1), "r"(c2), "r"(pol)
               : "memory");
}
__device__ __forceinline__ void bulk_load(uint32_t dst, const void* src, uint32_t bytes, uint32_t bar, uint32_t pol) {
  asm volatile("{\n.reg .b64 h;\nmov.b64 h, {0, %4};\n"
               "cp.async.bulk.shared::cluster.global.mbarrier::complete_tx::bytes.L2::cache_hint [%0], [%1], %2, [%3], h;\n}" ::"r"(dst),
               "l"(src), "r"(bytes), "r"(bar), "r"(pol)
               : "memory");
}
__device__ __forceinline__ void tma_load_3d_mc(uint32_t dst, const CUtensorMap* m, uint32_t bar, int c0, int c1, int c2, uint16_t mask) {
  asm volatile(
      "cp.async.bulk.tensor.3d.shared::cluster.global.mbarrier::complete_tx::bytes.multicast::cluster [%0], [%1, {%3, %4, %5}], [%2], %6;" ::"r"(dst),
      "l"(m), "r"(bar), "r"(c0), "r"(c1), "r"(c2), "h"(mask)
      : "memory");
}
__device__ __forceinline__ void tma_load_5d(uint32_t dst, const CUtensorMap* m, uint32_t bar, int c0, int c4) {
  asm volatile("cp.async.bulk.tensor.5d.shared::cluster.global.mbarrier::complete_tx::bytes [%0], [%1, {%3, 0, 0, 0, %4}], [%2];" ::"r"(dst),
               "l"(m), "r"(bar), "r"(c0), "r"(c4)
               : "memory");
}
__device__ __forceinline__ void bulk_load(uint32_t dst, const void* src, uint32_t bytes, uint32_t bar) {
  asm volatile("cp.async.bulk.shared::cluster.global.mbarrier::complete_tx::bytes [%0], [%1], %2, [%3];" ::"r"(dst), "l"(src), "r"(bytes), "r"(bar)
               : "memory");
}
__device__ __forceinline__ void bulk_load_mc(uint32_t dst, const void* src, uint32_t bytes, uint32_t bar, uint16_t mask) {
  asm volatile("cp.async.bulk.shared::cluster.global.mbarrier::complete_tx::bytes.multicast::cluster [%0], [%1], %2, [%3], %4;" ::"r"(dst),
               "l"(src), "r"(bytes), "r"(bar), "h"(mask)
               : "memory");
}
__device__ __forceinline__ void prefetch_l2(const void* src, uint32_t bytes) {
  asm volatile("cp.async.bulk.prefetch.L2.global [%0], %1;" ::"l"(src), "r"(bytes) : "memory");
}
__device__ __forceinline__ void tma_store_2d(const CUtensorMap* m, uint32_t src, int c0, int c1) {
  asm volatile("cp.async.bulk.tensor.2d.global.shared::cta.bulk_group [%0, {%2, %3}], [%1];" ::"l"(m), "r"(src), "r"(c0), "r"(c1)
               : "memory");
}
__device__ __forceinline__ void prefetch_tmap(const CUtensorMap* m) { asm volatile("prefetch.tensormap [%0];" ::"l"(m) : "memory"); }
__device__ __forceinline__ uint32_t pack_bf16(float lo, float hi) {
  uint32_t r;
  asm("cvt.rn.bf16x2.f32 %0, %1, %2;" : "=r"(r) : "f"(hi), "f"(lo));
  return r;
}
__device__ __forceinline__ float ex2(float x) {
  float y;
  asm("ex2.approx.ftz.f32 %0, %1;" : "=f"(y) : "f"(x));
  return y;
}
__device__ __forceinline__ float rcp(float x) {
  float y;
  asm("rcp.approx.ftz.f32 %0, %1;" : "=f"(y) : "f"(x));
  return y;
}
__device__ __forceinline__ void wg_fence() { asm volatile("wgmma.fence.sync.aligned;" ::: "memory"); }
__device__ __forceinline__ void wg_commit() { asm volatile("wgmma.commit_group.sync.aligned;" ::: "memory"); }
template <int N>
__device__ __forceinline__ void wg_wait() {
  asm volatile("wgmma.wait_group.sync.aligned %0;" ::"n"(N) : "memory");
}
template <int N>
__device__ __forceinline__ void fence_regs(float (&d)[N]) {
#pragma unroll
  for (int i = 0; i < N; i++) asm volatile("" : "+f"(d[i])::"memory");
}
__device__ __forceinline__ uint32_t sched_fence() {
  uint32_t t;
  asm volatile("mov.u32 %0, %%clock;" : "=r"(t)::"memory");
  return t;
}
__device__ __forceinline__ void bar_sync(int id, int n) { asm volatile("bar.sync %0, %1;" ::"r"(id), "r"(n) : "memory"); }
__device__ __forceinline__ void bar_arrive_if(bool c, int id, int n) {
  asm volatile("{\n.reg .pred p;\nsetp.ne.u32 p, %2, 0;\n@p bar.arrive %0, %1;\n}" ::"r"(id), "r"(n), "r"((uint32_t)c) : "memory");
}
__device__ __forceinline__ void bar_arrive(int id, int n) { asm volatile("bar.arrive %0, %1;" ::"r"(id), "r"(n) : "memory"); }

#define R8(a, i) "+f"(a[i]), "+f"(a[i + 1]), "+f"(a[i + 2]), "+f"(a[i + 3]), "+f"(a[i + 4]), "+f"(a[i + 5]), "+f"(a[i + 6]), "+f"(a[i + 7])
#define OP32(d, o) R8(d, o), R8(d, o + 8), R8(d, o + 16), R8(d, o + 24)
#define L32A "%0,%1,%2,%3,%4,%5,%6,%7,%8,%9,%10,%11,%12,%13,%14,%15,%16,%17,%18,%19,%20,%21,%22,%23,%24,%25,%26,%27,%28,%29,%30,%31"
#define L32B "%32,%33,%34,%35,%36,%37,%38,%39,%40,%41,%42,%43,%44,%45,%46,%47,%48,%49,%50,%51,%52,%53,%54,%55,%56,%57,%58,%59,%60,%61,%62,%63"
#define L32C "%64,%65,%66,%67,%68,%69,%70,%71,%72,%73,%74,%75,%76,%77,%78,%79,%80,%81,%82,%83,%84,%85,%86,%87,%88,%89,%90,%91,%92,%93,%94,%95"
#define WG_PRE(a, b, s, ha, hb) "{\n.reg .pred p;\n.reg .b64 da, db;\nmov.b64 da, {" a ", " ha "};\nmov.b64 db, {" b ", " hb "};\nsetp.ne.b32 p, " s ", 0;\n"

constexpr uint32_t HI128 = 0x40000040;
constexpr uint32_t HI64 = 0x80000080;
constexpr uint32_t HIQ = 0x80000040;
template <int TB>
__device__ __forceinline__ void wgmma_n128(float (&d)[64], uint32_t da, uint32_t ha, uint32_t db, uint32_t hb, int scale_d) {
  asm volatile(WG_PRE("%64", "%65", "%66", "%67", "%68") "wgmma.mma_async.sync.aligned.m64n128k16.f32.bf16.bf16 {" L32A "," L32B "}, da, db, p, 1, 1, 0, %69;\n}\n"
               : OP32(d, 0), OP32(d, 32)
               : "r"(da), "r"(db), "r"(scale_d), "r"(ha), "r"(hb), "n"(TB));
}
__device__ __forceinline__ void wgmma_n192_tb(float (&d)[96], uint32_t da, uint32_t db, int scale_d) {
  asm volatile(WG_PRE("%96", "%97", "%98", "%99", "%99") "wgmma.mma_async.sync.aligned.m64n192k16.f32.bf16.bf16 {" L32A "," L32B "," L32C "}, da, db, p, 1, 1, 0, 1;\n}\n"
               : OP32(d, 0), OP32(d, 32), OP32(d, 64)
               : "r"(da), "r"(db), "r"(scale_d), "r"(HI128));
}
__device__ __forceinline__ void wgmma_n64(float (&d)[64], uint32_t da, uint32_t db, int scale_d) {
  asm volatile(WG_PRE("%32", "%33", "%34", "%35", "%36") "wgmma.mma_async.sync.aligned.m64n64k16.f32.bf16.bf16 {" L32A "}, da, db, p, 1, 1, 0, 0;\n}\n"
               : OP32(d, 0)
               : "r"(da), "r"(db), "r"(scale_d), "r"(HIQ), "r"(HI64));
}
__device__ __forceinline__ void wgmma_n128_rs_tb(float (&d)[64], uint32_t a0, uint32_t a1, uint32_t a2, uint32_t a3, uint32_t db, int scale_d) {
  asm volatile("{\n.reg .pred p;\n.reg .b64 db;\nmov.b64 db, {%68, %70};\nsetp.ne.b32 p, %69, 0;\n"
               "wgmma.mma_async.sync.aligned.m64n128k16.f32.bf16.bf16 {" L32A "," L32B "}, {%64,%65,%66,%67}, db, p, 1, 1, 1;\n}\n"
               : OP32(d, 0), OP32(d, 32)
               : "r"(a0), "r"(a1), "r"(a2), "r"(a3), "r"(db), "r"(scale_d), "r"(HI64));
}
__device__ __forceinline__ void mma_16816(float (&c)[4], uint32_t a0, uint32_t a1, uint32_t a2, uint32_t a3, uint32_t b0, uint32_t b1) {
  asm volatile("mma.sync.aligned.m16n8k16.row.col.f32.bf16.bf16.f32 {%0,%1,%2,%3}, {%4,%5,%6,%7}, {%8,%9}, {%0,%1,%2,%3};"
               : "+f"(c[0]), "+f"(c[1]), "+f"(c[2]), "+f"(c[3])
               : "r"(a0), "r"(a1), "r"(a2), "r"(a3), "r"(b0), "r"(b1));
}
__device__ __forceinline__ uint32_t movm_t(uint32_t x) {
  uint32_t y;
  asm volatile("movmatrix.sync.aligned.m8n8.trans.b16 %0, %1;" : "=r"(y) : "r"(x));
  return y;
}
__device__ __forceinline__ void sts128(uint32_t a, uint32_t x, uint32_t y, uint32_t z, uint32_t w) {
  asm volatile("st.shared.v4.u32 [%0], {%1,%2,%3,%4};" ::"r"(a), "r"(x), "r"(y), "r"(z), "r"(w) : "memory");
}
__device__ __forceinline__ void stsm4(uint32_t a, uint32_t x, uint32_t y, uint32_t z, uint32_t w) {
  asm volatile("stmatrix.sync.aligned.m8n8.x4.shared.b16 [%0], {%1,%2,%3,%4};" ::"r"(a), "r"(x), "r"(y), "r"(z), "r"(w) : "memory");
}
__device__ __forceinline__ void ldsm4_t(uint32_t a, uint32_t (&r)[4]) {
  asm volatile("ldmatrix.sync.aligned.m8n8.x4.trans.shared.b16 {%0,%1,%2,%3}, [%4];"
               : "=r"(r[0]), "=r"(r[1]), "=r"(r[2]), "=r"(r[3])
               : "r"(a)
               : "memory");
}
__device__ __forceinline__ void stg128_if0(uint4* a, uint32_t x, uint32_t y, uint32_t z, uint32_t w, uint32_t sel) {
  asm volatile("{\n.reg .pred p;\nsetp.eq.u32 p, %5, 0;\n@p st.global.cs.v4.u32 [%0], {%1,%2,%3,%4};\n}" ::"l"(a), "r"(x), "r"(y), "r"(z), "r"(w),
               "r"(sel)
               : "memory");
}
template <int OFS>
__device__ __forceinline__ void stg128_sel(uint4* a, uint32_t x, uint32_t y, uint32_t z, uint32_t w, uint32_t sel) {
  asm volatile("{\n.reg .pred p;\nsetp.eq.u32 p, %5, 0;\n@p st.global.v4.u32 [%0+%6], {%1,%2,%3,%4};\n"
               "setp.eq.u32 p, %5, 2;\n@p st.global.cs.v4.u32 [%0+%6], {%1,%2,%3,%4};\n}" ::"l"(a), "r"(x), "r"(y), "r"(z), "r"(w), "r"(sel), "n"(OFS * 16)
               : "memory");
}
__device__ __forceinline__ void lds128(uint32_t a, uint32_t& x, uint32_t& y, uint32_t& z, uint32_t& w) {
  asm volatile("ld.shared.v4.u32 {%0,%1,%2,%3}, [%4];" : "=r"(x), "=r"(y), "=r"(z), "=r"(w) : "r"(a) : "memory");
}

constexpr int PLANE = 2048 * 16;
constexpr int PL_CTX = 0, PL_KV = 32, PL_OA = PL_KV + 64, NPLANES = PL_OA + 8;
__device__ __align__(1024) uint4 g_scr[NPLANES * PLANE];
__device__ uint4 g_carry[16 * 128];
constexpr int F_CTX = 0, F_KV = 512, F_L = 1040, F_CAR = 1056, F_EPOCH = 1072, F_END = 1072 + 132;
__device__ uint32_t g_flags[F_END];

#define NTURN 256

enum { K_KV = 1, K_L = 2, K_T = 3, K_OA = 4, K_OB = 5, K_END = 7 };
constexpr int NCLUSTERS = 66, MAXITEMS = 16;
constexpr int A_STAGE = 16384, B_SLOT = 32768;
constexpr int SM_B = 6 * A_STAGE, SM_CARRY = SM_B + 4 * B_SLOT, SM_BAR = SM_CARRY + 2048, SM_TOTAL = SM_BAR + 512;

struct Params {
  CUtensorMap mapA[3];
  CUtensorMap mapB[6];
  CUtensorMap mapO[2];
  uint4* scr;
  uint4* carry;
  uint32_t* flags;
  const uint32_t* x;
  const uint16_t* wq;
  uint32_t zero;
  uint16_t sched[NCLUSTERS * MAXITEMS];
  uint8_t keep[NCLUSTERS * MAXITEMS];
};

__device__ __forceinline__ bool item_narrow(uint32_t item) { return (item & 0x204) == 0x204 || (item & 7) == K_T; }
__device__ __forceinline__ int item_nk(uint32_t item) {
  const uint32_t kind = item & 7;
  return (kind == K_KV ? 8 : kind == K_OB ? 64 : 16) >> item_narrow(item);
}
__device__ __forceinline__ int item_row(uint32_t kind, int g, int pos) {
  if (kind == K_L || kind == K_OA) return g == 0 ? (pos - 1) * 1024 : 64 * (3 * g - 2 + pos + (g > 5));
  return 64 * (3 * g - 1 + pos);
}

__device__ __forceinline__ void wait_flag(const uint32_t* f, uint32_t target) {
  uint32_t it = 0;
#pragma unroll 1
  while (true) {
    uint32_t v;
    asm volatile("ld.acquire.gpu.global.u32 %0, [%1];" : "=r"(v) : "l"(f) : "memory");
    if ((int)(v - target) >= 0) break;
    __nanosleep(40);
    if (++it > (1u << 18)) break;
  }
  asm volatile("fence.proxy.async.global;" ::: "memory");
}
__device__ __forceinline__ uint32_t wait_bits(const uint32_t* f, uint32_t inv, uint32_t mask) {
  uint32_t it = 0, v;
#pragma unroll 1
  while (true) {
    asm volatile("ld.acquire.gpu.global.u32 %0, [%1];" : "=r"(v) : "l"(f) : "memory");
    v ^= inv;
    if (!(~v & mask)) break;
    __nanosleep(40);
    if (++it > (1u << 18)) break;
  }
  asm volatile("fence.proxy.async.global;" ::: "memory");
  return v;
}
__device__ __forceinline__ void red_add(uint32_t* f) { asm volatile("red.relaxed.gpu.global.add.u32 [%0], 1;" ::"l"(f) : "memory"); }
__device__ __forceinline__ void red_xor(uint32_t* f, uint32_t v) {
  asm volatile("red.relaxed.gpu.global.xor.b32 [%0], %1;" ::"l"(f), "r"(v) : "memory");
}

constexpr float QS = 0.08838834764831845f * 1.4426950408889634f;
__device__ __noinline__ void attn_fallback(uint4* q, const uint4* __restrict__ k, const uint32_t* __restrict__ x,
                                           const uint16_t* __restrict__ w, int row0, int lane) {
  const int g = lane >> 2, tq = lane & 3;
  q += row0 * 16;
  k += lane ^ (lane >> 3);
  const uint4* v = k + 2 * PLANE;
  float o[16][4];
#pragma unroll
  for (int i = 0; i < 16; i++) o[i][0] = o[i][1] = o[i][2] = o[i][3] = 0.f;
  x += (row0 + g) * 512 + tq;
  w += 2 * tq * 4096 + g;
#pragma unroll 1
  for (int k0 = 0; k0 < 64; k0++, x += 8, w += 16 * 4096) {
#pragma unroll
    for (int i = 0; i < 16; i++)
      mma_16816(o[i], x[0], x[4096], x[4], x[4100], w[8 * i] | w[4096 + 8 * i] << 16, w[8 * 4096 + 8 * i] | w[9 * 4096 + 8 * i] << 16);
  }
#pragma unroll
  for (int i = 0; i < 8; i++) {
    const int c = 4 * (i >> 1), e = 2 * (i & 1);
    __stcg(q + (i >> 1) * 32 + (i & 1) * 128 + (lane ^ (lane >> 3)),
           make_uint4(pack_bf16(o[c][e], o[c][e + 1]), pack_bf16(o[c + 1][e], o[c + 1][e + 1]),
                      pack_bf16(o[c + 2][e], o[c + 2][e + 1]), pack_bf16(o[c + 3][e], o[c + 3][e + 1])));
  }
  __syncwarp();
#pragma unroll
  for (int i = 0; i < 16; i++) o[i][0] = o[i][1] = o[i][2] = o[i][3] = 0.f;
  float m0 = -INFINITY, m1 = -INFINITY, l0 = 0.f, l1 = 0.f;
#pragma unroll 1
  for (int k0 = 0; k0 < row0 + 16; k0 += 16) {
    float sc[2][4] = {{0.f, 0.f, 0.f, 0.f}, {0.f, 0.f, 0.f, 0.f}};
#pragma unroll 1
    for (int cg = 0; cg < 4; cg++) {
      const uint4 qa = __ldcg(q + cg * 32 + (lane ^ (lane >> 3)));
      const uint4 qb = __ldcg(q + 128 + cg * 32 + (lane ^ (lane >> 3)));
#pragma unroll
      for (int t = 0; t < 2; t++) {
        const uint4 kk = __ldcg(k + (k0 + 8 * t) * 16 + cg * 32);
        mma_16816(sc[t], qa.x, qb.x, qa.y, qb.y, kk.x, kk.y);
        mma_16816(sc[t], qa.z, qb.z, qa.w, qb.w, kk.z, kk.w);
      }
    }
    float x0 = -INFINITY, x1 = -INFINITY;
#pragma unroll
    for (int t = 0; t < 2; t++) {
#pragma unroll
      for (int e = 0; e < 2; e++) {
        const int key = k0 + 8 * t + 2 * tq + e;
        if (key > row0 + g) sc[t][e] = -INFINITY;
        if (key > row0 + g + 8) sc[t][2 + e] = -INFINITY;
        x0 = fmaxf(x0, sc[t][e]);
        x1 = fmaxf(x1, sc[t][2 + e]);
      }
    }
    x0 = fmaxf(x0, __shfl_xor_sync(0xffffffffu, x0, 1));
    x1 = fmaxf(x1, __shfl_xor_sync(0xffffffffu, x1, 1));
    x0 = fmaxf(x0, __shfl_xor_sync(0xffffffffu, x0, 2));
    x1 = fmaxf(x1, __shfl_xor_sync(0xffffffffu, x1, 2));
    const float n0 = fmaxf(m0, x0), n1 = fmaxf(m1, x1);
    const float a0 = ex2(m0 - n0), a1 = ex2(m1 - n1);
    m0 = n0;
    m1 = n1;
    l0 *= a0;
    l1 *= a1;
    uint32_t pa[4];
#pragma unroll
    for (int t = 0; t < 2; t++) {
      const float e0 = ex2(sc[t][0] - m0), e1 = ex2(sc[t][1] - m0);
      const float e2 = ex2(sc[t][2] - m1), e3 = ex2(sc[t][3] - m1);
      l0 += e0 + e1;
      l1 += e2 + e3;
      pa[2 * t] = pack_bf16(e0, e1);
      pa[2 * t + 1] = pack_bf16(e2, e3);
    }
#pragma unroll
    for (int cg = 0; cg < 4; cg++) {
      const uint4 va = __ldcg(v + k0 * 16 + cg * 32);
      const uint4 vb = __ldcg(v + k0 * 16 + 128 + cg * 32);
#pragma unroll
      for (int r = 0; r < 4; r++) {
        const uint32_t w0 = r == 0 ? va.x : r == 1 ? va.y : r == 2 ? va.z : va.w;
        const uint32_t w1 = r == 0 ? vb.x : r == 1 ? vb.y : r == 2 ? vb.z : vb.w;
        float(&oo)[4] = o[4 * cg + r];
        oo[0] *= a0;
        oo[1] *= a0;
        oo[2] *= a1;
        oo[3] *= a1;
        mma_16816(oo, pa[0], pa[1], pa[2], pa[3], movm_t(w0), movm_t(w1));
      }
    }
  }
  l0 += __shfl_xor_sync(0xffffffffu, l0, 1);
  l1 += __shfl_xor_sync(0xffffffffu, l1, 1);
  l0 += __shfl_xor_sync(0xffffffffu, l0, 2);
  l1 += __shfl_xor_sync(0xffffffffu, l1, 2);
  const float i0 = 1.f / l0, i1 = 1.f / l1;
  __syncwarp();
  uint32_t* o0 = reinterpret_cast<uint32_t*>(q + g * 4) + tq;
#pragma unroll
  for (int i = 0; i < 16; i++) {
    uint32_t* d = o0 + (i >> 2) * 128 + ((i & 3) ^ (g >> 1)) * 4;
    d[0] = pack_bf16(o[i][0] * i0, o[i][1] * i0);
    d[512] = pack_bf16(o[i][2] * i1, o[i][3] * i1);
  }
}

#define KB_LIMIT 1.2089258e24f
#define KB_LOW 9.094947e-13f

__device__ __forceinline__ void local_scores(float (&s)[2][4], const uint32_t (&lo)[24], const uint32_t (&hi)[24], const uint32_t* k) {
#pragma unroll
  for (int h = 0; h < 2; h++) s[h][0] = s[h][1] = s[h][2] = s[h][3] = 0.f;
#pragma unroll
  for (int c = 0; c < 4; c += 2)
#pragma unroll
    for (int h = 0; h < 8; h += 4) mma_16816(s[h >> 2], lo[h + c], hi[h + c], lo[h + c + 1], hi[h + c + 1], k[h + c], k[h + c + 1]);
}
__device__ __forceinline__ void local_attn(float (&o)[2][4][4], float (&l)[2][4], const float (&s)[3][2][4], const uint32_t (&vt)[2][4][4],
                                           bool first, int lane) {
  const int g = lane >> 2, tq = lane & 3;
  const bool h0 = 2 * tq > g, h1 = 2 * tq + 1 > g;
  const uint32_t m = (h0 ? 0xFFFFu : 0u) | (h1 ? 0xFFFF0000u : 0u);
  float u0[2], u1[2], w0[2], w1[2], mu[2], mw[2];
#pragma unroll
  for (int h = 0; h < 2; h++) {
    u0[h] = h0 ? s[0][h][0] : s[1][h][0];
    u1[h] = h1 ? s[0][h][1] : s[1][h][1];
    w0[h] = h0 ? s[1][h][2] : s[2][h][2];
    w1[h] = h1 ? s[1][h][3] : s[2][h][3];
    if (first) {
      if (h0) u0[h] = -INFINITY;
      if (h1) u1[h] = -INFINITY;
    }
    mu[h] = fmaxf(u0[h], u1[h]);
    mw[h] = fmaxf(w0[h], w1[h]);
  }
#pragma unroll
  for (int o = 1; o <= 2; o++)
#pragma unroll
    for (int h = 0; h < 2; h++) {
      mw[h] = fmaxf(mw[h], __shfl_xor_sync(0xffffffffu, mw[h], o));
      mu[h] = fmaxf(mu[h], __shfl_xor_sync(0xffffffffu, mu[h], o));
    }
  const float c = 0.17677669529663687f * 1.4426950408889634f;
#pragma unroll
  for (int h = 0; h < 2; h++) {
    const uint32_t pu = pack_bf16(ex2((u0[h] - mu[h]) * c), ex2((u1[h] - mu[h]) * c));
    const uint32_t pw = pack_bf16(ex2((w0[h] - mw[h]) * c), ex2((w1[h] - mw[h]) * c));
    l[h][0] = l[h][1] = l[h][2] = l[h][3] = 0.f;
    mma_16816(l[h], 0x3F803F80, 0u, 0u, 0x3F803F80, pu, pw);
#pragma unroll
    for (int i = 0; i < 4; i++) {
      const uint32_t(&v)[4] = vt[i >> 1][2 * h + (i & 1)];
      o[h][i][0] = o[h][i][1] = o[h][i][2] = o[h][i][3] = 0.f;
      mma_16816(o[h][i], v[0], v[1], v[2], v[3], i < 2 ? pu & m : pw & ~m, i < 2 ? pu & ~m : pw & m);
    }
  }
}

__global__ __cluster_dims__(2, 1, 1) __launch_bounds__(512, 1) void fused_kernel(const __grid_constant__ Params p) {
  extern __shared__ __align__(1024) uint8_t smem_dyn[];
  DECLARE_READY();
  const uint32_t sbase = smem_u32(smem_dyn);
  const uint32_t afull0 = sbase + SM_BAR, aempty0 = afull0 + 48, bfull0 = afull0 + 96, bempty0 = afull0 + 128, carbar = afull0 + 160,
                 pub0 = afull0 + 200;
  const uint32_t bbase = sbase + SM_B;
  const int wg = __reduce_min_sync(0xffffffffu, (int)(threadIdx.x >> 7));
  const uint32_t rank = blockIdx.x & 1;
  const uint16_t* sched = p.sched + (blockIdx.x >> 1) * MAXITEMS;

  auto fill_b = [&](uint32_t item, int t, uint32_t pb, uint32_t pol) {
    const uint32_t kind = item & 7, j = (item >> 7) & 15, sl = pb & 3;
    if (((item >> 3) & 15) == 0) mbar_arrive_n(bempty0 + 8 * sl, 1);
    mbar_expect_tx(bfull0 + 8 * sl, kind == K_L ? 24576 : 32768);
    const uint32_t nt = kind == K_KV ? j : 2 * j + rank, dst = bbase + sl * B_SLOT;
    const uint32_t cb = kind == K_T ? nt : item_narrow(item) ? nt - 8 : nt * 2 + (t >> 1 & 1);
    const uint32_t ks = item_narrow(item) ? t : (t >> 1 & ~1) + (t & 1);
    if (kind == K_OA) {
      tma_load_5d(dst, &p.mapB[K_OA], bfull0 + 8 * sl, cb * 128, ks * 4);
      tma_load_5d(dst + 16384, &p.mapB[K_OA], bfull0 + 8 * sl, cb * 128 + 64, ks * 4);
    } else if (kind == K_L) {
      tma_load_3d(dst, &p.mapB[K_L], bfull0 + 8 * sl, nt * 64, t * 64, 0, pol);
    } else {
      tma_load_3d(dst, &p.mapB[kind == K_KV ? 1 - rank : kind], bfull0 + 8 * sl, 0, ks * 128, cb * 2, pol);
    }
  };
  auto first_a = [&](uint32_t item0, uint32_t u, bool mc) {
    const bool local0 = (item0 & 7) == K_L;
    const int g0 = (item0 >> 3) & 15;
    const int row = item_row(local0 ? K_L : K_KV, g0, (u >> 1) + (g0 == 0));
    const int r = local0 ? row & 1023 : row, blk = (local0 ? (row >> 10) * 16 : 0) + 2 * (u & 1);
    if (mc) {
      mbar_expect_tx(afull0 + 8 * u, A_STAGE);
      tma_load_3d_mc(sbase + u * A_STAGE + rank * 8192, &p.mapA[local0], afull0 + 8 * u, 0, r, blk + rank, (uint16_t)3);
    } else
      for (int h = 0; h < 2; h++) tma_load_3d(sbase + u * A_STAGE + h * 8192, &p.mapA[local0], afull0 + 8 * u, 0, r, blk + h);
  };
  auto first_b = [&](uint32_t item0, uint32_t t) {
    const bool local0 = (item0 & 7) == K_L;
    const int j = (item0 >> 7) & 15;
    mbar_expect_tx(bfull0 + 8 * t, local0 ? 24576 : 32768);
    tma_load_3d(bbase + t * B_SLOT, &p.mapB[local0 ? K_L : 1 - rank], bfull0 + 8 * t, local0 ? (2 * j + rank) * 64 : 0,
                local0 ? t * 64 : (t & 1) * 128, local0 ? 0 : 4 * j + (t & 2));
    if ((item0 & 0x78) == 0) mbar_arrive_n(bempty0 + 8 * t, 1);
  };
  if (threadIdx.x == 0) {
    mbar_init(bfull0, 1);
    mbar_init(bempty0, 3);
    asm volatile("fence.mbarrier_init.release.cluster;" ::: "memory");
    first_b(sched[0], 0);
  } else if (threadIdx.x == 32) {
    mbar_init(afull0, 1);
    asm volatile("fence.mbarrier_init.release.cluster;" ::: "memory");
    mbar_expect_tx(afull0, A_STAGE);
    first_a(sched[0], 0, false);
  } else if (threadIdx.x == 64) {
    for (int i = 20; i < 25 + MAXITEMS; i++) mbar_init(afull0 + 8 * i, i < 25 ? 1 : 12);
  } else if (threadIdx.x == 96) {
    for (int i = 1; i < 20; i++)
      if (i != 12 && i != 16) mbar_init(afull0 + 8 * i, i < 6 ? 1 : i < 12 ? 2 : i < 16 ? 1 : 3);
    asm volatile("fence.mbarrier_init.release.cluster;" ::: "memory");
  }
  __syncthreads();
  asm volatile("barrier.cluster.arrive.relaxed.aligned;\nbarrier.cluster.wait.aligned;" ::: "memory");

  if (wg == 0) {
    asm volatile("setmaxnreg.dec.sync.aligned.u32 32;");
    const uint32_t item0 = sched[0];
    const bool local0 = (item0 & 7) == K_L;
    const int g0 = (item0 >> 3) & 15;
    if (threadIdx.x == 96) {
#pragma unroll 1
      for (uint32_t x = local0 ? 0x6B42A593u : 0xB6A45239u; x; x >>= 4) {
        if (x & 8) first_b(item0, x & 3);
        else if (g0 != 0 || (x & 7) < 5) first_a(item0, (x & 7) - 1, true);
      }
    }
    if (__reduce_min_sync(0xffffffffu, (int)(threadIdx.x >> 5)) == 1) {
      const uint32_t e = __ldcg(p.flags + F_EPOCH + blockIdx.x) + 1;
      const uint32_t w = threadIdx.x - 32;
      uint32_t n = w < 2 || ((sched[0] >> 3) & 15) != 0 ? 2 : 0;
      uint32_t bar0 = afull0 + 16 * w, dst0 = sbase + w * (2 * A_STAGE) + rank * 8192;
      asm volatile("" : "+r"(bar0), "+r"(dst0));
      uint32_t bar, dst, par, prev = 0;
      auto position = [&]() {
        bar = bar0 + 8 * (n & 1), dst = dst0 + (n & 1) * A_STAGE, par = (~n >> 1) & 1;
        asm volatile("" : "+r"(bar), "+r"(dst), "+r"(par));
      };
      position();
      for (int it = 0; it < MAXITEMS; it++) {
        const uint32_t item = sched[it];
        const uint32_t kind = item & 7;
        if (kind == K_END) break;
        const int g = (item >> 3) & 15;
        const int nd = kind == K_T ? 8 : item_nk(kind) >> 1;
        if (kind == K_OA) wait_flag(p.flags + F_L + g, 16 * e);
        int rho = w + (item >> 11);
        if (rho >= 3) rho -= 3;
        const int row = item_row(kind, g, kind == K_T ? 2 - rho : rho + (g == 0));
        const uint32_t on = w > 2 || (g == 0 && rho == 2) ? 0 : ~0u, swap = rho == 1 ? 0 : on, base = (0x924924 >> rho) & on;
        uint32_t m = base ^ (swap & (kind == K_L ? 0xB6DB6D : (item_narrow(item) ? (prev == K_KV ? 1 : 0x6D) : prev == K_KV ? 0x861861 : 0x86186D)));
        prev = kind;
        auto step = [&](auto load) {
          if (m & 1) {
            mbar_wait(bar + 48, par);
            mbar_expect_tx(bar, A_STAGE);
            load();
            n++;
            position();
          }
          m >>= 1;
          __syncwarp();
        };
        if (kind >= K_OA) {
          const uint4* src = p.scr + (kind == K_OA ? PL_OA : PL_CTX) * PLANE + row * 16 + rank * 512;
          uint32_t heads = kind == K_OA ? ~0u : 0, need = 1;
          for (int t = 0; t <= nd; t++, need <<= 1) {
            if (~heads & need) heads = wait_bits(p.flags + F_CTX + g * 32, (e & 1) - 1, need);
            if (item_narrow(item) && t > 2) m = (base >> 2) ^ (t == nd ? swap : 0);
#pragma unroll 1
            for (int x = t == 0; x < (t == nd ? 1 : 3); x++)
              step([&]() {
                bulk_load_mc(dst, src, 8192, bar, (uint16_t)3);
                src += PLANE;
              });
          }
        } else {
          const int r = kind == K_L ? row & 1023 : row;
          int blk = (kind == K_L ? (row >> 10) * 16 : 0) + rank;
          if (kind == K_T) m ^= swap & 0x800000;
          if (it == 0) m &= m - 1, m &= m - 1, blk += 4;
#pragma unroll 1
          for (int x = 3 * nd; x; x--)
            step([&]() {
              tma_load_3d_mc(dst, &p.mapA[kind - 1], bar, 0, r, blk, (uint16_t)3);
              blk += 2;
            });
        }
      }
      if (w < 3) {
        mbar_wait(bar0 + 48, (~(n + 1) >> 1) & 1);
        mbar_wait(bar0 + 56, (~n >> 1) & 1);
      }
    } else if (threadIdx.x == 0) {
      const uint32_t e = __ldcg(p.flags + F_EPOCH + blockIdx.x) + 1;
      uint32_t pb = 4;
      for (int it = 0; it < MAXITEMS; it++) {
        const uint32_t item = sched[it];
        const uint32_t kind = item & 7;
        if (kind == K_END) break;
        const int nk = item_nk(item);
        uint32_t heads = kind == K_OB ? wait_bits(p.flags + F_CTX + ((item >> 3) & 15) * 32, (e & 1) - 1, 0) : 0;
        const int keep = p.keep[(blockIdx.x >> 1) * MAXITEMS + it];
        for (int t = it == 0 ? 4 : 0; t < nk; t++, pb++) {
          mbar_wait(bempty0 + 8 * (pb & 3), ((pb >> 2) & 1) ^ 1);
          fill_b(item, t, pb, keep & 32 ? L2_NORMAL : L2_FIRST);
          if (item_narrow(item) && kind == K_OB) {
            const uint32_t g = (item >> 3) & 15, nb = g ? 3 : 2;
            if (!(heads >> t & 2)) heads = wait_bits(p.flags + F_CTX + g * 32, (e & 1) - 1, 0);
            if (heads >> t & 2) prefetch_l2(p.scr + (PL_CTX + t + 1) * PLANE + (3 * g + 2 - nb) * 1024 + rank * nb * 512, nb * 8192);
          }
        }
        if (kind == K_T) {
          const int g = (item >> 3) & 15, j = (item >> 7) & 15;
          const uint4* src = p.scr + (PL_KV + j * 4 + rank) * PLANE;
          const int n = ((3 * g + 1) >> 1) + 1;
          uint32_t groups = 0;
          for (int t = 0; t < n; t++, src += 2048) {
            const uint32_t need = (4u << 2 * min((2 * t + 2) / 3, g)) - 1;
            if (~groups & need) groups = wait_bits(p.flags + F_KV + j * 32, (e & 1) - 1, need);
            const uint32_t nskip = t == n - 1 ? 1 + (g & 1) : 0;
            const uint32_t pol = t < (keep & 31) ? L2_NORMAL : L2_FIRST;
            uint32_t sl = pb & 3;
            mbar_wait(bempty0 + 8 * sl, ((pb >> 2) & 1) ^ 1);
            if (nskip) mbar_arrive_n(bempty0 + 8 * sl, nskip);
            mbar_expect_tx(bfull0 + 8 * sl, 32768);
            pb++;
            if (nskip == 2) {
              bulk_load(bbase + sl * B_SLOT, src, 16384, bfull0 + 8 * sl, pol);
              bulk_load(bbase + sl * B_SLOT + 16384, src + 2 * PLANE, 16384, bfull0 + 8 * sl, pol);
              continue;
            }
            bulk_load(bbase + sl * B_SLOT, src, 32768, bfull0 + 8 * sl, pol);
            sl = pb & 3;
            mbar_wait(bempty0 + 8 * sl, ((pb >> 2) & 1) ^ 1);
            if (nskip) mbar_arrive_n(bempty0 + 8 * sl, nskip);
            mbar_expect_tx(bfull0 + 8 * sl, 32768);
            bulk_load(bbase + sl * B_SLOT, src + 2 * PLANE, 32768, bfull0 + 8 * sl, pol);
            pb++;
          }
        }
      }
    } else if (threadIdx.x == 64) {
      const uint32_t pair = 2 * ((sched[0] >> 7) & 15) + rank;
      if ((sched[0] & 127) == K_L) {
        mbar_wait(carbar + 24, 0);
        asm volatile("fence.proxy.async.shared::cta;\ncp.async.bulk.global.shared::cta.bulk_group [%0], [%1], 2048;\n"
                     "cp.async.bulk.commit_group;\ncp.async.bulk.wait_group 0;\nfence.proxy.async.global;\nfence.acq_rel.gpu;" ::"l"(p.carry + pair * 128),
                     "r"(sbase + SM_CARRY - 2048)
                     : "memory");
        red_add(p.flags + F_CAR + pair);
      }
      if ((sched[0] & 127) == (K_L | 6 << 3)) {
        wait_flag(p.flags + F_CAR + pair, __ldcg(p.flags + F_EPOCH + blockIdx.x) + 1);
        mbar_expect_tx(carbar + 32, 2048);
        bulk_load(sbase + SM_CARRY, p.carry + pair * 128, 2048, carbar + 32);
      }
      for (int it = 0; it < MAXITEMS; it++) {
        const uint32_t item = sched[it];
        const uint32_t kind = item & 7;
        const int g = (item >> 3) & 15, j = (item >> 7) & 15;
        if (kind >= K_OA) break;
        mbar_wait(pub0 + 8 * it, 0);
        asm volatile("fence.acq_rel.gpu;" ::: "memory");
        if (kind == K_KV) red_xor(p.flags + F_KV + j * 32, 1u << (2 * g + rank));
        if (kind == K_L) red_add(p.flags + F_L + g);
        if (kind == K_T) red_xor(p.flags + F_CTX + g * 32, 1u << (2 * j + rank));
      }
      red_add(p.flags + F_EPOCH + blockIdx.x);
    } else if (threadIdx.x == 96) {
      for (int i = 0; i < 3; i++) prefetch_tmap(&p.mapA[i]);
      for (int i = 0; i < 6; i++) prefetch_tmap(&p.mapB[i]);
      prefetch_tmap(&p.mapO[0]);
      prefetch_tmap(&p.mapO[1]);
    }
  } else {
    asm volatile("setmaxnreg.inc.sync.aligned.u32 160;");
    const int cw = wg - 1;
    const int wq = __reduce_min_sync(0xffffffffu, (int)((threadIdx.x >> 5) & 3));
    auto turn = [&](uint32_t dep = 0) {
      bar_sync((1 + cw) | dep, NTURN);
    };
    const int fwd = cw == 0 ? 3 : cw, back = cw == 2 ? 1 : cw + 2;
    int next = fwd;
    auto pass = [&]() {
      bar_arrive(next, NTURN);
      next = fwd;
    };
    auto rank_of = [&](uint32_t item) {
      const int r = cw + (item >> 11);
      return r >= 3 ? r - 3 : r;
    };
    if (cw == 1) pass();
    if (cw == 2) { turn(); pass(); }
    const uint32_t abase = sbase + cw * (2 * A_STAGE), afull = afull0 + 16 * cw, aempty = aempty0 + 16 * cw;
    const uint32_t adesc = ((abase & 0x3FFFF) >> 4) | (1u << 16), bdesc = (bbase & 0x3FFFF) >> 4;
    uint32_t pa = 0, pb = 0;
    int it = 0;
    uint32_t item = sched[0];
    auto publish = [&](int i, uint32_t skip = 0) {
      __syncwarp();
      mbar_arrive_if0(pub0 + 8 * i, (threadIdx.x & 31) | skip);
    };
    auto test_ab = [&](uint32_t a, uint32_t b) {
      test_a(afull + 8 * (a & 1), (a >> 1) & 1);
      test_b(bfull0 + 8 * (b & 3), (b >> 2) & 1);
    };
    auto wait_ab = [&]() {
      if (!ready_ab()) {
        mbar_wait_u(afull + 8 * (pa & 1), (pa >> 1) & 1);
        mbar_wait_u(bfull0 + 8 * (pb & 3), (pb >> 2) & 1);
      }
    };
    auto release_ab = [&](uint32_t a, uint32_t b, uint32_t skip) {
      mbar_arrive_cta_if0(wq < 2 ? aempty + 8 * (a & 1) : bempty0 + 8 * (b & 3), wq < 2 ? wq : rank, (threadIdx.x & 31) | (wq == 3) | skip);
    };
    test_ab(0, 0);
    uint32_t bflag = 512u << 16;
    enum { NEW = 1, REL = 2, FWD = 4, TEST = 8, BACK = 16 };
    auto gturn = [&](auto mode_c, bool hold, auto mma, auto meanwhile) {
      constexpr int MODE = decltype(mode_c)::value;
      uint32_t da = adesc + (pa & 1) * (A_STAGE >> 4), db = bdesc + (pb & 3) * (B_SLOT >> 4) + bflag;
      asm volatile("" : "+r"(da), "+r"(db));
      if (MODE & NEW) wait_ab();
      else if (!ready_b()) mbar_wait_u(bfull0 + 8 * (pb & 3), (pb >> 2) & 1);
      turn();
      wg_fence();
      mma(da, db);
      wg_commit();
      if (!hold) pass();
      if (hold) {
      } else if (MODE & TEST) test_ab(pa + 1, pb + 1);
      else test_b(bfull0 + 8 * ((pb + 1) & 3), ((pb + 1) >> 2) & 1);
      meanwhile();
      wg_wait<0>();
      if (MODE & REL) {
        if (!hold) release_ab(pa, pb, 0);
      } else {
        mbar_arrive_if0(bempty0 + 8 * (pb & 3), threadIdx.x & 127);
      }
      if (MODE & FWD) pa++;
      if (MODE & BACK) pa--;
      __syncwarp();
      pb++;
    };
    constexpr std::true_type YES{};
    constexpr std::false_type NO{};
    constexpr std::integral_constant<int, NEW> FIRST{};
    constexpr std::integral_constant<int, REL | FWD | TEST> SECOND{};
    constexpr std::integral_constant<int, NEW | REL | FWD | TEST> ONCE{};
    constexpr std::integral_constant<int, NEW | FWD | TEST> X0{};
    constexpr std::integral_constant<int, NEW | BACK> X1{};
    constexpr std::integral_constant<int, REL | FWD> Y0{};
    auto nothing = []() {};
    auto idle = [&]() { return ((item >> 3) & 15) == 0 && rank_of(item) == 2; };
    auto skip_item = [&](int passed) {
      const int n = (item & 7) == K_T ? 10 : item_nk(item);
      publish(it);
#pragma unroll 1
      for (int i = 2 + passed; i < n; i++) {
        turn();
        pass();
      }
      pb += n;
      test_ab(pa, pb);
      item = sched[++it];
    };

    if ((item & 7) == K_L && idle()) skip_item(0);
    float lo_[2][4][4] = {}, ll[2][4] = {};
    uint4* ldst = p.scr;
    uint32_t lnone = 1;
    auto lrelease = [&]() { release_ab(1, 3, lnone); };
    auto lflush = [&]() {
      const uint32_t t = sched_fence() & p.zero;
#pragma unroll
      for (int i = 0; i < 4; i++) {
        const int h = i >> 1, e = i & 1 ? 2 : 0;
        const float f0 = rcp(__uint_as_float(__float_as_uint(ll[h][e]) | t)), f1 = rcp(__uint_as_float(__float_as_uint(ll[h][e + 1]) | t));
        const float(&r0)[4] = lo_[h][e], (&r1)[4] = lo_[h][e + 1];
        stg128_if0(ldst + h * 32 + e * 64, movm_t(pack_bf16(r0[0] * f0, r0[1] * f1)), movm_t(pack_bf16(r0[2] * f0, r0[3] * f1)),
                   movm_t(pack_bf16(r1[0] * f0, r1[1] * f1)), movm_t(pack_bf16(r1[2] * f0, r1[3] * f1)), lnone);
      }
      publish(it - 1, lnone);
    };
    while ((item & 7) == K_L) {
      const int g = (item >> 3) & 15, j = (item >> 7) & 15;
      const int rho = rank_of(item);
      float acc[96];
      auto mma = [&](int kb, bool first) {
        return [&acc, kb, first](uint32_t da, uint32_t db) {
#pragma unroll
          for (int k = 0; k < 4; k++) wgmma_n192_tb(acc, da + kb * 512 + k * 2, db + k * 128, !(first && k == 0));
        };
      };
      gturn(FIRST, false, mma(0, true), lrelease);
      gturn(SECOND, false, mma(1, false), lflush);
#pragma unroll 1
      for (int d = 7;;) {
        gturn(FIRST, false, mma(0, false), nothing);
        if (--d == 0) break;
        gturn(SECOND, false, mma(1, false), nothing);
      }
      const int lane = threadIdx.x & 31;
      const int from = rho ? rho : 4 * (~g & 1), to = g == 0 ? 3 * rho : rho == 2 ? 4 * (g & 1) : rho + 1;
      uint32_t own, front, vlo;
      gturn(SECOND, true, mma(1, false), [&]() {
        bar_arrive_if(rho != 2, g && rho ? back : next, NTURN);
        own = (wq < 3 ? abase + A_STAGE + wq * 2048 : sbase + SM_CARRY - 8192 + to * 2048) + lane * 16;
        front = (wq > 0 ? abase + A_STAGE + wq * 2048 - 2048 : g == 0 ? abase + A_STAGE : sbase + SM_CARRY - 8192 + from * 2048) + lane * 16;
        vlo = abase + A_STAGE + 8192 + wq * 1024 + lane * 16;
        ldst = p.scr + (PL_OA + j) * PLANE + (item_row(K_L, g, rho + (g == 0)) + wq * 16) * 16 + rank * 64 + (lane ^ (lane >> 3));
        asm volatile("" : "+r"(own), "+r"(front), "+r"(vlo), "+l"(ldst));
        lnone = 0;
        item = sched[++it];
        if (wq == 0 && g != 0) mbar_wait_u(carbar + 8 * from, ((g - (g <= 5 ? 1 : 6)) >> (rho == 0)) & 1);
      });
      if (g && rho == 0) next = back;
      fence_regs(acc);
      uint32_t lo[24], hi[24], hk[8], vt[2][4][4];
#pragma unroll
      for (int i = 0; i < 24; i++) {
        lo[i] = pack_bf16(acc[4 * i], acc[4 * i + 1]);
        hi[i] = pack_bf16(acc[4 * i + 2], acc[4 * i + 3]);
      }
      sts128(own, hi[8], hi[9], hi[10], hi[11]);
      sts128(own + 512, hi[12], hi[13], hi[14], hi[15]);
      stsm4(own + 1024, hi[16], hi[17], hi[18], hi[19]);
      stsm4(own + 1536, hi[20], hi[21], hi[22], hi[23]);
      __syncwarp();
      mbar_arrive_if0(carbar + 8 * to, lane | (wq ^ 3));
      stsm4(vlo, lo[16], lo[17], lo[18], lo[19]);
      stsm4(vlo + 512, lo[20], lo[21], lo[22], lo[23]);
      bar_sync(4 + cw, 128);
      lds128(front, hk[0], hk[1], hk[2], hk[3]);
      lds128(front + 512, hk[4], hk[5], hk[6], hk[7]);
#pragma unroll
      for (int i = 0; i < 8; i++) ldsm4_t((lane < 16 ? (i < 4 ? front : own) + 1024 : vlo - 256) + (i & 3) * 256, vt[i >> 2][i & 3]);
      float sc[3][2][4];
      local_scores(sc[2], lo, hi, hi + 8);
      local_scores(sc[1], lo, hi, lo + 8);
      local_scores(sc[0], lo, hi, hk);
      test_ab(pa, pb);
      local_attn(lo_, ll, sc, vt, g == 0 && wq == 0, lane);
      bar_arrive_if(rho == 2, back, NTURN);
    }
    if (!lnone) {
      bar_sync(4 + cw, 128);
      lrelease();
      lflush();
    }

    bflag = 1024u << 16;
    float Y[64];
    float sc0 = 0.f, sc1 = 0.f;
    uint32_t done;
    uint4* pdst;
    auto pack = [&](uint32_t (&r)[16], const float (&acc)[64], int h, float s0, float s1) {
#pragma unroll
      for (int i = 0; i < 8; i++) {
        const int c = 32 * h + 4 * i;
        r[8 * (i >> 2) + (i & 3)] = pack_bf16(acc[c] * s0, acc[c + 1] * s0);
        r[8 * (i >> 2) + (i & 3) + 4] = pack_bf16(acc[c + 2] * s1, acc[c + 3] * s1);
      }
    };
    auto pack_now = [&](uint32_t (&r)[16], const float (&acc)[64], int h) {
      pack(r, acc, h, sc0, sc1);
#pragma unroll
      for (int i = 0; i < 16; i++) asm volatile("" : "+r"(r[i])::"memory");
    };
    auto stores = [&](auto ofs_c, const uint32_t (&r)[16], uint32_t sel) {
      constexpr int OFS = decltype(ofs_c)::value;
      stg128_sel<OFS>(pdst, r[0], r[1], r[2], r[3], sel);
      stg128_sel<OFS + 128>(pdst, r[4], r[5], r[6], r[7], sel);
      stg128_sel<OFS + 32>(pdst, r[8], r[9], r[10], r[11], sel);
      stg128_sel<OFS + 160>(pdst, r[12], r[13], r[14], r[15], sel);
    };
    constexpr std::integral_constant<int, 0> H0{};
    constexpr std::integral_constant<int, 64> H1{};
    auto flush = [&]() {
      uint32_t r[16];
      turn();
      pass();
      sched_fence();
      pack(r, Y, 0, sc0, sc1);
      stores(H0, r, done);
      turn();
      pass();
      sched_fence();
      pack(r, Y, 1, sc0, sc1);
      stores(H1, r, done);
      publish(it - 1, done & 1);
    };
    auto no_pending = [&]() {
      done = 1;
      pdst = p.scr;
#pragma unroll
      for (int i = 0; i < 64; i++) Y[i] = 0.f;
    };
    no_pending();
    auto mma128 = [&](auto scr_c, float (&acc)[64], int keep) {
      return [&acc, keep](uint32_t da, uint32_t db) {
        constexpr bool SCR = decltype(scr_c)::value;
#pragma unroll
        for (int k = 0; k < 8; k++)
          wgmma_n128<1>(acc, da + (k & 1) * 2 + ((k >> 1) & 1) * (SCR ? 32 : 4) + (k >> 2) * (SCR ? 64 : 512), SCR ? HI64 : HI128,
                        db + k * 128, HI128, k != 0 || keep);
      };
    };
    auto first_two = [&](auto mode0, auto mode1, auto scr_c, float (&X)[64]) {
      uint32_t r0[16], r1[16];
      gturn(mode0, false, mma128(scr_c, X, false), [&]() { pack_now(r0, Y, 0); });
      stores(H0, r0, done);
      gturn(mode1, false, mma128(scr_c, X, true), [&]() { pack_now(r1, Y, 1); });
      stores(H1, r1, done);
      publish(it - 1, done & 1);
    };
    auto all_but_last_two = [&](auto scr_c, float (&X)[64]) {
      int n = item_nk(item);
      first_two(X0, X1, scr_c, X);
      gturn(Y0, false, mma128(scr_c, Y, false), nothing);
#pragma unroll 1
      while (true) {
        gturn(SECOND, false, mma128(scr_c, Y, true), nothing);
        gturn(X0, false, mma128(scr_c, X, true), nothing);
        gturn(X1, false, mma128(scr_c, X, true), nothing);
        if (!decltype(scr_c)::value || (n -= 4) == 4) break;
        gturn(Y0, false, mma128(scr_c, Y, true), nothing);
      }
      fence_regs(X);
    };
    while ((item & 7) < K_OA) {
      if (idle()) {
        flush();
        done = 1;
        skip_item(2);
        continue;
      }
      const uint32_t kind = item & 7;
      const int g = (item >> 3) & 15, j = (item >> 7) & 15;
      const int rho = rank_of(item);
      if (kind != K_T) {
        float X[64];
        all_but_last_two(NO, X);
        const int lane = threadIdx.x & 31;
        const int row = item_row(K_KV, g, rho + (g == 0)) + wq * 16;
        sc0 = sc1 = rank ? 1.f : QS;
        pdst = p.scr + (PL_KV + j * 4 + rank * 2 + 1) * PLANE + row * 16 + (lane ^ (lane >> 3));
        uint32_t r0[16], r1[16];
        pack(r0, X, 0, sc0, sc1);
        stores(std::integral_constant<int, -PLANE>{}, r0, 0);
        gturn(Y0, false, mma128(NO, Y, true), [&]() { pack_now(r1, X, 1); });
        stores(std::integral_constant<int, 64 - PLANE>{}, r1, 0);
        item = sched[++it];
        gturn(SECOND, false, mma128(NO, Y, true), nothing);
        test_ab(pa, pb);
        fence_regs(Y);
        done = 0;
      } else {
        float(&O)[64] = Y;
        float S[64];
        float l0 = 0.f, l1 = 0.f;
        float zlim;
        const uint32_t sel = threadIdx.x & 127;
        const int b = 3 * g + 1 - rho;
        first_two(ONCE, ONCE, NO, S);
#pragma unroll 1
        for (int n = 0; n < 5; n++) gturn(ONCE, false, mma128(NO, S, true), nothing);
#pragma unroll
        for (int i = 0; i < 64; i++) O[i] = 0.f;
        fence_regs(O);
        gturn(FIRST, false, mma128(NO, S, true), nothing);
        fence_regs(S);
        {
          const uint32_t lane = threadIdx.x & 31, dst = abase + (pa & 1) * A_STAGE + wq * 2048 + (lane ^ (lane >> 3)) * 16;
#pragma unroll
          for (int h = 0; h < 2; h++) {
            uint32_t r[16];
            pack(r, S, h, 1.f, 1.f);
#pragma unroll
            for (int i = 0; i < 4; i++) {
              sts128(dst + h * 8192 + (i >> 1) * 512 + (i & 1) * 1024, r[4 * i], r[4 * i + 1], r[4 * i + 2], r[4 * i + 3]);
              if (4 * h + i < 7) __nanosleep(30);
            }
          }
          asm volatile("fence.proxy.async.shared::cta;" ::: "memory");
        }
        enum { MID, LAST, HALF };
        auto round = [&](auto mode_c) {
          constexpr int MODE = decltype(mode_c)::value;
          constexpr bool INIT = MODE == LAST;
          constexpr int NI = MODE == HALF ? 8 : 16;
          const uint32_t shared = MODE == HALF ? rho == 0 : 0;
          const uint32_t tv = pb + 1 - shared;
          {
            const uint32_t dq = adesc + (pa & 1) * (A_STAGE >> 4);
            const uint32_t dk = bdesc + (pb & 3) * 2048 + (1u << 16);
            if (INIT) {
              const int lane = threadIdx.x & 31;
              const int row = (wq * 16 + (lane >> 2) - 2 * (lane & 3) + 11) << 23;
              const int r0 = row ^ (__float_as_uint(l0) & p.zero & (MODE + 16)), r1 = row ^ (__float_as_uint(l1) & p.zero & (MODE + 16));
#pragma unroll
              for (int i = 0; i < 4 * NI; i++) {
                const int c = i - 4 * (NI - 8);
                S[i] = c < 0 ? 0.f : __int_as_float((c & 2 ? r1 : r0) + ((4 * (c & 2) - 2 * (c & ~3) - (c & 1) - 11) << 23));
                asm volatile("" : "+f"(S[i])::"memory");
              }
            }
            if (!ready_b()) mbar_wait_u(bfull0 + 8 * (pb & 3), (pb >> 2) & 1);
            turn();
            wg_fence();
#pragma unroll
            for (int k = 0; k < 8; k++) {
              const uint32_t da = dq + (k >> 2) * 512 + (k & 2) * 16 + (k & 1) * 2, db = dk + (k >> 1) * 32 + (k & 1) * 2;
              if (MODE == HALF) wgmma_n64(S, da, db, k != 0 || INIT);
              else wgmma_n128<0>(S, da, HIQ, db, HI64, k != 0 || INIT);
            }
            wg_commit();
            pass();
          }
          test_b(bfull0 + 8 * (tv & 3), (tv >> 2) & 1);
          if (!ready_b()) mbar_wait_u(bfull0 + 8 * (tv & 3), (tv >> 2) & 1);
          wg_wait<0>();
#pragma unroll
          for (int i = 0; i < 4 * NI; i++) asm volatile("" : "+f"(S[i])::"memory");
          mbar_arrive_if0(bempty0 + 8 * (pb & 3), sel | shared);
          if (MODE >= LAST) mbar_arrive_cta_if0(aempty + 8 * (pa & 1), wq & 1, (sel & 31) | (wq >> 1));
          uint32_t P[2 * NI];
          if (MODE >= LAST && !INIT) {
            const int lane = threadIdx.x & 31;
            const int row = wq * 16 + (lane >> 2) - 2 * (lane & 3);
#pragma unroll
            for (int i = 0; i < 8; i++) {
#pragma unroll
              for (int e = 0; e < 2; e++) {
                if (8 * i + e > row) S[4 * (NI - 8 + i) + e] = -INFINITY;
                if (8 * i + e > row + 8) S[4 * (NI - 8 + i) + 2 + e] = -INFINITY;
              }
            }
          }
          float s0 = 0.f, s1 = 0.f, t0 = 0.f, t1 = 0.f;
#pragma unroll
          for (int i = 0; i < NI; i++) {
#pragma unroll
            for (int e = 0; e < 4; e++) S[4 * i + e] = ex2(S[4 * i + e]);
            s0 += S[4 * i];
            t0 += S[4 * i + 1];
            s1 += S[4 * i + 2];
            t1 += S[4 * i + 3];
            P[2 * i] = pack_bf16(S[4 * i], S[4 * i + 1]);
            P[2 * i + 1] = pack_bf16(S[4 * i + 2], S[4 * i + 3]);
          }
          l0 += s0 + t0;
          l1 += s1 + t1;
          uint32_t dep = (__float_as_uint(l0) ^ __float_as_uint(l1)) ^ P[2 * NI - 1];
          fence_regs(O);
#pragma unroll
          for (int i = 0; i < 2 * NI; i++) asm volatile("" : "+r"(P[i])::"memory");
          const uint32_t dv = (bdesc + (tv & 3) * 2048 + shared * 1024) | (32u << 16);
          turn(dep & p.zero);
          wg_fence();
#pragma unroll
          for (int k = 0; k < NI / 2; k++)
            wgmma_n128_rs_tb(O, P[4 * k], P[4 * k + 1], P[4 * k + 2], P[4 * k + 3], dv + k * 256, 1);
          wg_commit();
          pass();
          pb = tv + 1;
          if (MODE >= LAST) {
            const int nskip = 1 + (g & 1);
            if (rho + nskip >= 3) pb += 3 - nskip;
            pa++;
          } else {
            test_b(bfull0 + 8 * (pb & 3), (pb >> 2) & 1);
          }
          if (MODE >= LAST) {
            l0 += __shfl_xor_sync(0xffffffffu, l0, 1);
            l1 += __shfl_xor_sync(0xffffffffu, l1, 1);
            l0 += __shfl_xor_sync(0xffffffffu, l0, 2);
            l1 += __shfl_xor_sync(0xffffffffu, l1, 2);
            sc0 = rcp(l0);
            sc1 = rcp(l1);
            zlim = l0 <= KB_LIMIT && l0 >= KB_LOW && l1 <= KB_LIMIT && l1 >= KB_LOW ? 3e38f : -1.f;
          }
          wg_wait<0>();
          fence_regs(O);
          mbar_arrive_if0(bempty0 + 8 * (tv & 3), sel);
        };
#pragma unroll 1
        for (int n = b >> 1; n; n--) round(std::integral_constant<int, MID>{});
        item = sched[++it];
        if (b & 1) round(std::integral_constant<int, LAST>{});
        else round(std::integral_constant<int, HALF>{});
        test_ab(pa, pb);
        float z[4] = {0.f, 0.f, 0.f, 0.f};
#pragma unroll
        for (int i = 0; i < 32; i++) z[i & 3] = fmaf(O[2 * i], O[2 * i + 1], z[i & 3]);
        const bool bad = !(fabsf(z[0]) + fabsf(z[1]) + fabsf(z[2]) + fabsf(z[3]) <= zlim);
        const int lane = threadIdx.x & 31;
        pdst = p.scr + (PL_CTX + 2 * j + rank) * PLANE + (b * 64 + wq * 16) * 16 + (lane ^ (lane >> 3));
        done = p.keep[(blockIdx.x >> 1) * MAXITEMS + it - 1] >> 6;
        if (__any_sync(0xffffffffu, bad)) {
          attn_fallback(p.scr + (PL_CTX + 2 * j + rank) * PLANE, p.scr + (PL_KV + j * 4 + rank) * PLANE, p.x,
                        p.wq + (2 * j + rank) * 128, b * 64 + wq * 16, threadIdx.x & 31);
          publish(it - 1);
          no_pending();
          test_ab(pa, pb);
        }
      }
    }

    bool relay = true;
    if (idle()) {
      flush();
      skip_item(2);
    } else {
      const uint32_t kind = item & 7;
      const int g = (item >> 3) & 15, j = (item >> 7) & 15;
      const int row = item_row(kind, g, rank_of(item) + (g == 0)) + wq * 16;
      auto epilogue = [&](float (&acc)[64], int cb, bool pace) {
        const int lane = threadIdx.x & 31;
        const uint32_t stg = abase + ((pa - 1) & 1) * A_STAGE + wq * 4096;
        const int srow = lane & 15;
#pragma unroll
        for (int jj = 0; jj < 8; jj++) {
          const uint32_t r0 = pack_bf16(acc[8 * jj + 0], acc[8 * jj + 1]);
          const uint32_t r1 = pack_bf16(acc[8 * jj + 2], acc[8 * jj + 3]);
          const uint32_t r2 = pack_bf16(acc[8 * jj + 4], acc[8 * jj + 5]);
          const uint32_t r3 = pack_bf16(acc[8 * jj + 6], acc[8 * jj + 7]);
          const int chunk = (2 * jj + (lane >> 4)) & 7;
          const uint32_t addr = stg + (jj >> 2) * 2048 + srow * 128 + ((chunk ^ (srow & 7)) << 4);
          asm volatile("stmatrix.sync.aligned.m8n8.x4.shared.b16 [%0], {%1,%2,%3,%4};" ::"r"(addr), "r"(r0), "r"(r1), "r"(r2), "r"(r3)
                       : "memory");
          if (jj < 7 && pace) __nanosleep(30);
        }
        asm volatile("fence.proxy.async.shared::cta;" ::: "memory");
        __syncwarp();
        if (lane == 0) {
          const int col = cb * 128 + (kind == K_OA ? (row >> 10) * 2048 : 1024);
          const int r = kind == K_OA ? row & 1023 : row;
          tma_store_2d(&p.mapO[kind - K_OA], stg, col, r);
          tma_store_2d(&p.mapO[kind - K_OA], stg + 2048, col + 64, r);
          asm volatile("cp.async.bulk.commit_group;" ::: "memory");
        }
      };
      float X[64];
      relay = g == 0;
      const int last = g && rank_of(item) == 1 ? back : fwd;
      if (item_narrow(item)) {
        int n = item_nk(item);
        first_two(ONCE, ONCE, YES, X);
#pragma unroll 1
        while (--n > 1) {
          if (n == 2) next = last;
          gturn(ONCE, false, mma128(YES, X, true), nothing);
        }
        fence_regs(X);
        epilogue(X, 2 * j + rank - 8, rank_of(item) == 0);
      } else {
        all_but_last_two(YES, X);
        gturn(Y0, false, mma128(YES, Y, true), nothing);
        epilogue(X, 4 * j + 2 * rank, true);
        next = last;
        gturn(SECOND, false, mma128(YES, Y, true), nothing);
        fence_regs(Y);
        epilogue(Y, 4 * j + 2 * rank + 1, rank_of(item) == 0);
      }
      item = sched[++it];
    }
    const int rho = rank_of(item);
    uint32_t id;
    asm volatile("mov.u32 %0, %%tid.x;" : "=r"(id));
    if (rho == 0 && relay) {
      bar_sync(id >> 7, NTURN);
      bar_arrive(id < 256 ? 3 : (id >> 7) - 1, NTURN);
    }
    if (rho == 1) bar_sync(id >> 7, NTURN);
    asm volatile("cp.async.bulk.wait_group.read 0;" ::: "memory");
  }
}

typedef CUresult (*EncodeFn)(CUtensorMap*, CUtensorMapDataType, cuuint32_t, void*, const cuuint64_t*, const cuuint64_t*,
                             const cuuint32_t*, const cuuint32_t*, CUtensorMapInterleave, CUtensorMapSwizzle, CUtensorMapL2promotion,
                             CUtensorMapFloatOOBfill);

void make_map(EncodeFn enc, CUtensorMap* m, const void* ptr, uint64_t d0, uint64_t d1, uint64_t d2, uint64_t s1, uint64_t s2, uint32_t b0,
              uint32_t b1, uint32_t b2) {
  cuuint64_t gd[3] = {d0, d1, d2}, gs[2] = {s1, s2};
  cuuint32_t bd[3] = {b0, b1, b2}, es[3] = {1, 1, 1};
  enc(m, CU_TENSOR_MAP_DATA_TYPE_BFLOAT16, d2 ? 3 : 2, const_cast<void*>(ptr), gd, gs, bd, es, CU_TENSOR_MAP_INTERLEAVE_NONE,
      CU_TENSOR_MAP_SWIZZLE_128B, CU_TENSOR_MAP_L2_PROMOTION_L2_128B, CU_TENSOR_MAP_FLOAT_OOB_FILL_NONE);
}

struct HostState {
  Params p;
  const void* in[9];
  void* out;
  bool valid;
};
HostState g_hs;

const uint16_t h_sched[NCLUSTERS * MAXITEMS] = {
    690, 698, 706, 714, 722, 1425, 1561, 1977, 1601, 829, 7, 7, 7, 7, 7, 7,
    265, 851, 969, 1315, 1833, 1843, 60, 7, 7, 7, 7, 7, 7, 7, 7, 7,
    705, 643, 521, 515, 979, 1451, 957, 7, 7, 7, 7, 7, 7, 7, 7, 7,
    386, 394, 402, 410, 418, 426, 1825, 1595, 148, 7, 7, 7, 7, 7, 7, 7,
    337, 795, 897, 937, 1083, 1353, 1987, 188, 7, 7, 7, 7, 7, 7, 7, 7,
    329, 187, 1099, 1699, 661, 7, 7, 7, 7, 7, 7, 7, 7, 7, 7, 7,
    178, 186, 194, 202, 210, 1337, 1689, 1473, 1873, 701, 7, 7, 7, 7, 7, 7,
    433, 153, 331, 1305, 1163, 1457, 1707, 517, 7, 7, 7, 7, 7, 7, 7, 7,
    281, 779, 529, 523, 1059, 1307, 1555, 813, 7, 7, 7, 7, 7, 7, 7, 7,
    833, 179, 929, 1067, 1809, 1995, 52, 7, 7, 7, 7, 7, 7, 7, 7, 7,
    665, 163, 571, 57, 1945, 1569, 1419, 909, 7, 7, 7, 7, 7, 7, 7, 7,
    385, 139, 275, 963, 1545, 1739, 156, 7, 7, 7, 7, 7, 7, 7, 7, 7,
    129, 145, 307, 1075, 1209, 1875, 4, 7, 7, 7, 7, 7, 7, 7, 7, 7,
    441, 211, 1289, 1347, 1745, 717, 7, 7, 7, 7, 7, 7, 7, 7, 7, 7,
    193, 411, 595, 1211, 693, 7, 7, 7, 7, 7, 7, 7, 7, 7, 7, 7,
    393, 161, 315, 1281, 11, 1801, 1747, 84, 7, 7, 7, 7, 7, 7, 7, 7,
    689, 683, 561, 1051, 1177, 1955, 1617, 845, 7, 7, 7, 7, 7, 7, 7, 7,
    793, 835, 577, 19, 1417, 1491, 36, 7, 7, 7, 7, 7, 7, 7, 7, 7,
    673, 811, 907, 1065, 49, 1329, 1971, 981, 7, 7, 7, 7, 7, 7, 7, 7,
    681, 387, 513, 547, 81, 35, 1225, 1579, 773, 7, 7, 7, 7, 7, 7, 7,
    2, 10, 18, 26, 34, 42, 1961, 1723, 196, 7, 7, 7, 7, 7, 7, 7,
    417, 171, 1033, 1043, 1313, 1195, 1729, 653, 7, 7, 7, 7, 7, 7, 7, 7,
    201, 403, 537, 971, 1673, 1611, 76, 7, 7, 7, 7, 7, 7, 7, 7, 7,
    185, 169, 291, 569, 51, 1593, 1481, 1609, 949, 7, 7, 7, 7, 7, 7, 7,
    769, 435, 923, 1105, 1227, 853, 7, 7, 7, 7, 7, 7, 7, 7, 7, 7,
    817, 155, 587, 1921, 1483, 645, 7, 7, 7, 7, 7, 7, 7, 7, 7, 7,
    649, 147, 531, 1107, 1459, 901, 7, 7, 7, 7, 7, 7, 7, 7, 7, 7,
    642, 650, 658, 666, 674, 682, 1795, 1979, 204, 7, 7, 7, 7, 7, 7, 7,
    258, 266, 274, 282, 290, 298, 1539, 1467, 164, 7, 7, 7, 7, 7, 7, 7,
    305, 203, 961, 1331, 1867, 132, 7, 7, 7, 7, 7, 7, 7, 7, 7, 7,
    130, 138, 146, 154, 162, 170, 1697, 1851, 212, 7, 7, 7, 7, 7, 7, 7,
    514, 522, 530, 538, 546, 554, 1411, 1427, 797, 7, 7, 7, 7, 7, 7, 7,
    465, 691, 947, 1929, 1817, 1731, 20, 7, 7, 7, 7, 7, 7, 7, 7, 7,
    457, 659, 563, 3, 1321, 1441, 1443, 589, 7, 7, 7, 7, 7, 7, 7, 7,
    257, 699, 915, 1097, 1355, 941, 7, 7, 7, 7, 7, 7, 7, 7, 7, 7,
    770, 778, 786, 794, 802, 810, 1923, 1683, 549, 7, 7, 7, 7, 7, 7, 7,
    713, 451, 1057, 977, 1363, 917, 7, 7, 7, 7, 7, 7, 7, 7, 7, 7,
    946, 954, 962, 970, 978, 1283, 1217, 1705, 1865, 677, 7, 7, 7, 7, 7, 7,
    306, 314, 322, 330, 338, 1665, 1819, 1993, 805, 7, 7, 7, 7, 7, 7, 7,
    273, 675, 913, 1091, 1681, 1475, 44, 7, 7, 7, 7, 7, 7, 7, 7, 7,
    137, 723, 67, 1577, 1857, 565, 7, 7, 7, 7, 7, 7, 7, 7, 7, 7,
    297, 443, 1035, 1089, 65, 1345, 1827, 933, 7, 7, 7, 7, 7, 7, 7, 7,
    209, 177, 339, 1169, 1219, 525, 7, 7, 7, 7, 7, 7, 7, 7, 7, 7,
    825, 467, 75, 1803, 821, 7, 7, 7, 7, 7, 7, 7, 7, 7, 7, 7,
    849, 803, 539, 1081, 73, 1489, 1835, 725, 7, 7, 7, 7, 7, 7, 7, 7,
    801, 195, 9, 83, 2001, 789, 7, 7, 7, 7, 7, 7, 7, 7, 7, 7,
    697, 667, 905, 955, 1201, 1619, 12, 7, 7, 7, 7, 7, 7, 7, 7, 7,
    898, 906, 914, 922, 930, 938, 1667, 1811, 573, 7, 7, 7, 7, 7, 7, 7,
    449, 787, 267, 931, 1179, 1465, 1547, 965, 7, 7, 7, 7, 7, 7, 7, 7,
    50, 58, 66, 74, 82, 1409, 1433, 1947, 597, 7, 7, 7, 7, 7, 7, 7,
    777, 459, 585, 1323, 1969, 1587, 172, 7, 7, 7, 7, 7, 7, 7, 7, 7,
    289, 819, 939, 1185, 1931, 1841, 1849, 709, 7, 7, 7, 7, 7, 7, 7, 7,
    401, 395, 545, 555, 1161, 1203, 1985, 781, 7, 7, 7, 7, 7, 7, 7, 7,
    313, 715, 1073, 1153, 1291, 1585, 1603, 28, 7, 7, 7, 7, 7, 7, 7, 7,
    409, 827, 945, 25, 1299, 1553, 1691, 541, 7, 7, 7, 7, 7, 7, 7, 7,
    785, 707, 953, 33, 1235, 973, 7, 7, 7, 7, 7, 7, 7, 7, 7, 7,
    809, 131, 283, 1041, 1027, 41, 1187, 1713, 1737, 533, 7, 7, 7, 7, 7, 7,
    721, 419, 579, 1193, 1953, 1859, 140, 7, 7, 7, 7, 7, 7, 7, 7, 7,
    841, 771, 323, 1297, 1171, 1233, 1939, 669, 7, 7, 7, 7, 7, 7, 7, 7,
    641, 843, 17, 43, 1571, 837, 7, 7, 7, 7, 7, 7, 7, 7, 7, 7,
    321, 299, 921, 1, 27, 1937, 2003, 68, 7, 7, 7, 7, 7, 7, 7, 7,
    562, 570, 578, 586, 594, 1537, 1361, 1435, 581, 7, 7, 7, 7, 7, 7, 7,
    434, 442, 450, 458, 466, 1155, 1963, 925, 7, 7, 7, 7, 7, 7, 7, 7,
    818, 826, 834, 842, 850, 1793, 1449, 1563, 557, 7, 7, 7, 7, 7, 7, 7,
    425, 427, 1025, 1049, 59, 1721, 1715, 180, 7, 7, 7, 7, 7, 7, 7, 7,
    657, 651, 259, 553, 899, 593, 1339, 1675, 685, 7, 7, 7, 7, 7, 7, 7,
};

void setup(void* const* d_in, void* d_out) {
  void* fn = nullptr;
  cudaDriverEntryPointQueryResult qr;
  cudaGetDriverEntryPoint("cuTensorMapEncodeTiled", &fn, cudaEnableDefault, &qr);
  EncodeFn enc = (EncodeFn)fn;
  void *scr, *carry, *flags;
  cudaGetSymbolAddress(&scr, g_scr);
  cudaGetSymbolAddress(&carry, g_carry);
  cudaGetSymbolAddress(&flags, g_flags);
  Params& p = g_hs.p;
  make_map(enc, &p.mapA[2], d_in[3], 64, 2048, 16, 2048, 128, 64, 64, 1);
  make_map(enc, &p.mapA[0], d_in[4], 64, 2048, 8, 1024, 128, 64, 64, 1);
  make_map(enc, &p.mapA[1], d_in[0], 64, 1024, 32, 4096, 128, 64, 64, 1);
  make_map(enc, &p.mapB[3], d_in[5], 64, 1024, 64, 8192, 128, 64, 128, 2);
  make_map(enc, &p.mapB[1], d_in[6], 64, 512, 64, 8192, 128, 64, 128, 2);
  make_map(enc, &p.mapB[2], d_in[1], 1024, 1024, 3, 6144, 2048, 64, 64, 3);
  make_map(enc, &p.mapB[0], d_in[7], 64, 512, 64, 8192, 128, 64, 128, 2);
  make_map(enc, &p.mapB[5], d_in[8], 64, 4096, 16, 2048, 128, 64, 128, 2);
  {
    cuuint64_t gd[5] = {1024, 2, 4, 4, 32}, gs[4] = {2048, 8 * 2048, 2 * 2048, 32 * 2048};
    cuuint32_t bd[5] = {64, 2, 4, 4, 4}, es[5] = {1, 1, 1, 1, 1};
    enc(&p.mapB[4], CU_TENSOR_MAP_DATA_TYPE_BFLOAT16, 5, d_in[2], gd, gs, bd, es, CU_TENSOR_MAP_INTERLEAVE_NONE, CU_TENSOR_MAP_SWIZZLE_128B,
        CU_TENSOR_MAP_L2_PROMOTION_L2_128B, CU_TENSOR_MAP_FLOAT_OOB_FILL_NONE);
  }
  make_map(enc, &p.mapO[0], d_out, 4096, 1024, 0, 8192, 0, 64, 16, 1);
  make_map(enc, &p.mapO[1], d_out, 2048, 2048, 0, 4096, 0, 64, 16, 1);
  p.scr = (uint4*)scr;
  p.carry = (uint4*)carry;
  p.flags = (uint32_t*)flags;
  p.x = (const uint32_t*)d_in[3];
  p.wq = (const uint16_t*)d_in[5];
  p.zero = 0;
  for (int c = 0; c < NCLUSTERS; c++) {
    int rot = 0;
    for (int i = c * MAXITEMS; i < (c + 1) * MAXITEMS; i++) {
      const int kind = h_sched[i] & 7, g = (h_sched[i] >> 3) & 15;
      p.sched[i] = (uint16_t)(h_sched[i] | rot << 11);
      rot = (rot + (kind == K_T ? 1 + (g & 1) : g == 0)) % 3;
    }
  }
  int start[NCLUSTERS * MAXITEMS];
  for (int i = 0, t = 0; i < NCLUSTERS * MAXITEMS; i++) {
    const int kind = h_sched[i] & 7, g = (h_sched[i] >> 3) & 15;
    if (i % MAXITEMS == 0) t = 0;
    start[i] = t;
    t += (g ? 3 : 2) * (kind == K_L ? 13 : 8) + (kind == K_T ? 9 * g + 6 : 0);
  }
  for (int i = 0; i < NCLUSTERS * MAXITEMS; i++) {
    int keep = 0;
    for (int k = 0; k < NCLUSTERS * MAXITEMS; k++)
      if (!((h_sched[i] ^ h_sched[k]) & 0x787) && start[k] > start[i] + 3) {
        const int n = 32 | ((3 * ((h_sched[k] >> 3) & 15) + 3) >> 1);
        if (n > keep) keep = n;
      }
    if (start[i] + 9 * ((h_sched[i] >> 3) & 15) < 200) keep |= 128;
    p.keep[i] = (uint8_t)keep;
  }
  cudaFuncSetAttribute(fused_kernel, cudaFuncAttributeMaxDynamicSharedMemorySize, SM_TOTAL);
  for (int i = 0; i < 9; i++) g_hs.in[i] = d_in[i];
  g_hs.out = d_out;
  g_hs.valid = true;
}

}

extern "C" void kernel_launch(void* const* d_in, const int* in_sizes, int n_in, void* d_out, int out_size) {
  (void)in_sizes;
  (void)n_in;
  (void)out_size;
  bool ok = g_hs.valid && g_hs.out == d_out;
  for (int i = 0; ok && i < 9; i++) ok = g_hs.in[i] == d_in[i];
  if (!ok) setup(d_in, d_out);
  fused_kernel<<<NCLUSTERS * 2, 512, SM_TOTAL, cudaStreamPerThread>>>(g_hs.p);
}
```

```cpp
#include <cuda_runtime.h>
#include <cuda_bf16.h>
#include <cuda.h>
#include <stdint.h>
#include <type_traits>

namespace {

typedef __nv_bfloat16 bf16;

__device__ __forceinline__ uint32_t smem_u32(const void* p) { return (uint32_t)__cvta_generic_to_shared(p); }
__device__ __forceinline__ void mbar_init(uint32_t bar, uint32_t cnt) {
  asm volatile("mbarrier.init.shared::cta.b64 [%0], %1;" ::"r"(bar), "r"(cnt) : "memory");
}
__device__ __forceinline__ void mbar_expect_tx(uint32_t bar, uint32_t bytes) {
  asm volatile("mbarrier.arrive.expect_tx.shared::cta.b64 _, [%0], %1;" ::"r"(bar), "r"(bytes) : "memory");
}
__device__ __forceinline__ void mbar_arrive_n(uint32_t bar, uint32_t n) {
  asm volatile("mbarrier.arrive.shared::cta.b64 _, [%0], %1;" ::"r"(bar), "r"(n) : "memory");
}
__device__ __forceinline__ void mbar_arrive_if0(uint32_t bar, uint32_t sel) {
  asm volatile("{\n.reg .pred p;\nsetp.eq.u32 p, %1, 0;\n@p mbarrier.arrive.shared::cta.b64 _, [%0];\n}" ::"r"(bar), "r"(sel) : "memory");
}
__device__ __forceinline__ void mbar_arrive_cta_if0(uint32_t bar, uint32_t cta, uint32_t sel) {
  asm volatile("{\n.reg .pred p;\n.reg .b32 ra;\nsetp.eq.u32 p, %2, 0;\nmapa.shared::cluster.u32 ra, %0, %1;\n"
               "@p mbarrier.arrive.shared::cluster.b64 _, [ra];\n}" ::"r"(bar),
               "r"(cta), "r"(sel)
               : "memory");
}
__device__ __forceinline__ void mbar_wait(uint32_t bar, uint32_t parity) {
  uint32_t done;
  uint32_t it = 0;
#pragma unroll 1
  while (true) {
    asm volatile("{\n.reg .pred p;\nmbarrier.try_wait.parity.shared::cta.b64 p, [%1], %2, 1000;\nselp.u32 %0, 1, 0, p;\n}"
                 : "=r"(done)
                 : "r"(bar), "r"(parity)
                 : "memory");
    if (done) break;
    if (++it > (1u << 24)) __trap();
  }
}
__device__ __forceinline__ void mbar_wait_u(uint32_t bar, uint32_t parity) {
  uint32_t it = 0;
#pragma unroll 1
  while (true) {
    uint32_t done;
    asm volatile("{\n.reg .pred p, q;\nmbarrier.try_wait.parity.shared::cta.b64 p, [%1], %2;\nvote.sync.all.pred q, p, 0xffffffff;\nselp.u32 %0, 1, 0, q;\n}"
                 : "=r"(done)
                 : "r"(bar), "r"(parity)
                 : "memory");
    if (done) break;
    if (++it > (1u << 20)) break;
  }
}
#define DECLARE_READY() asm volatile(".reg .pred RDYA, RDYB;")
__device__ __forceinline__ void test_a(uint32_t bar, uint32_t parity) {
  asm volatile("mbarrier.test_wait.parity.shared::cta.b64 RDYA, [%0], %1;" ::"r"(bar), "r"(parity) : "memory");
}
__device__ __forceinline__ void test_b(uint32_t bar, uint32_t parity) {
  asm volatile("mbarrier.test_wait.parity.shared::cta.b64 RDYB, [%0], %1;" ::"r"(bar), "r"(parity) : "memory");
}
__device__ __forceinline__ uint32_t ready_b(uint32_t dep = 0) {
  uint32_t r;
  asm volatile("{\n.reg .pred q;\nsetp.eq.and.u32 q, %1, 0, RDYB;\nvote.sync.all.pred q, q, 0xffffffff;\nselp.u32 %0, 1, 0, q;\n}" : "=r"(r) : "r"(dep) : "memory");
  return r;
}
__device__ __forceinline__ uint32_t ready_ab() {
  uint32_t r;
  asm volatile("{\n.reg .pred q;\nand.pred q, RDYA, RDYB;\nvote.sync.all.pred q, q, 0xffffffff;\nselp.u32 %0, 1, 0, q;\n}" : "=r"(r)::"memory");
  return r;
}
__device__ __forceinline__ void tma_load_3d(uint32_t dst, const CUtensorMap* m, uint32_t bar, int c0, int c1, int c2) {
  asm volatile("cp.async.bulk.tensor.3d.shared::cluster.global.mbarrier::complete_tx::bytes [%0], [%1, {%3, %4, %5}], [%2];" ::"r"(dst),
               "l"(m), "r"(bar), "r"(c0), "r"(c1), "r"(c2)
               : "memory");
}
constexpr uint32_t L2_NORMAL = 0x10000000u, L2_FIRST = 0x12F00000u;
__device__ __forceinline__ void tma_load_3d(uint32_t dst, const CUtensorMap* m, uint32_t bar, int c0, int c1, int c2, uint32_t pol) {
  asm volatile("{\n.reg .b64 h;\nmov.b64 h, {0, %6};\n"
               "cp.async.bulk.tensor.3d.shared::cluster.global.mbarrier::complete_tx::bytes.L2::cache_hint [%0], [%1, {%3, %4, %5}], [%2], h;\n}" ::"r"(dst),
               "l"(m), "r"(bar), "r"(c0), "r"(c1), "r"(c2), "r"(pol)
               : "memory");
}
__device__ __forceinline__ void bulk_load(uint32_t dst, const void* src, uint32_t bytes, uint32_t bar, uint32_t pol) {
  asm volatile("{\n.reg .b64 h;\nmov.b64 h, {0, %4};\n"
               "cp.async.bulk.shared::cluster.global.mbarrier::complete_tx::bytes.L2::cache_hint [%0], [%1], %2, [%3], h;\n}" ::"r"(dst),
               "l"(src), "r"(bytes), "r"(bar), "r"(pol)
               : "memory");
}
__device__ __forceinline__ void tma_load_3d_mc(uint32_t dst, const CUtensorMap* m, uint32_t bar, int c0, int c1, int c2, uint16_t mask) {
  asm volatile(
      "cp.async.bulk.tensor.3d.shared::cluster.global.mbarrier::complete_tx::bytes.multicast::cluster [%0], [%1, {%3, %4, %5}], [%2], %6;" ::"r"(dst),
      "l"(m), "r"(bar), "r"(c0), "r"(c1), "r"(c2), "h"(mask)
      : "memory");
}
__device__ __forceinline__ void tma_load_5d(uint32_t dst, const CUtensorMap* m, uint32_t bar, int c0, int c4) {
  asm volatile("cp.async.bulk.tensor.5d.shared::cluster.global.mbarrier::complete_tx::bytes [%0], [%1, {%3, 0, 0, 0, %4}], [%2];" ::"r"(dst),
               "l"(m), "r"(bar), "r"(c0), "r"(c4)
               : "memory");
}
__device__ __forceinline__ void bulk_load(uint32_t dst, const void* src, uint32_t bytes, uint32_t bar) {
  asm volatile("cp.async.bulk.shared::cluster.global.mbarrier::complete_tx::bytes [%0], [%1], %2, [%3];" ::"r"(dst), "l"(src), "r"(bytes), "r"(bar)
               : "memory");
}
__device__ __forceinline__ void bulk_load_mc(uint32_t dst, const void* src, uint32_t bytes, uint32_t bar, uint16_t mask) {
  asm volatile("cp.async.bulk.shared::cluster.global.mbarrier::complete_tx::bytes.multicast::cluster [%0], [%1], %2, [%3], %4;" ::"r"(dst),
               "l"(src), "r"(bytes), "r"(bar), "h"(mask)
               : "memory");
}
__device__ __forceinline__ void prefetch_l2(const void* src, uint32_t bytes) {
  asm volatile("cp.async.bulk.prefetch.L2.global [%0], %1;" ::"l"(src), "r"(bytes) : "memory");
}
__device__ __forceinline__ void tma_store_2d(const CUtensorMap* m, uint32_t src, int c0, int c1) {
  asm volatile("cp.async.bulk.tensor.2d.global.shared::cta.bulk_group [%0, {%2, %3}], [%1];" ::"l"(m), "r"(src), "r"(c0), "r"(c1)
               : "memory");
}
__device__ __forceinline__ void prefetch_tmap(const CUtensorMap* m) { asm volatile("prefetch.tensormap [%0];" ::"l"(m) : "memory"); }
__device__ __forceinline__ uint32_t pack_bf16(float lo, float hi) {
  uint32_t r;
  asm("cvt.rn.bf16x2.f32 %0, %1, %2;" : "=r"(r) : "f"(hi), "f"(lo));
  return r;
}
__device__ __forceinline__ float ex2(float x) {
  float y;
  asm("ex2.approx.ftz.f32 %0, %1;" : "=f"(y) : "f"(x));
  return y;
}
__device__ __forceinline__ float rcp(float x) {
  float y;
  asm("rcp.approx.ftz.f32 %0, %1;" : "=f"(y) : "f"(x));
  return y;
}
__device__ __forceinline__ void wg_fence() { asm volatile("wgmma.fence.sync.aligned;" ::: "memory"); }
__device__ __forceinline__ void wg_commit() { asm volatile("wgmma.commit_group.sync.aligned;" ::: "memory"); }
template <int N>
__device__ __forceinline__ void wg_wait() {
  asm volatile("wgmma.wait_group.sync.aligned %0;" ::"n"(N) : "memory");
}
template <int N>
__device__ __forceinline__ void fence_regs(float (&d)[N]) {
#pragma unroll
  for (int i = 0; i < N; i++) asm volatile("" : "+f"(d[i])::"memory");
}
__device__ __forceinline__ uint32_t sched_fence() {
  uint32_t t;
  asm volatile("mov.u32 %0, %%clock;" : "=r"(t)::"memory");
  return t;
}
__device__ __forceinline__ void bar_sync(int id, int n) { asm volatile("bar.sync %0, %1;" ::"r"(id), "r"(n) : "memory"); }
__device__ __forceinline__ void bar_arrive_if(bool c, int id, int n) {
  asm volatile("{\n.reg .pred p;\nsetp.ne.u32 p, %2, 0;\n@p bar.arrive %0, %1;\n}" ::"r"(id), "r"(n), "r"((uint32_t)c) : "memory");
}
__device__ __forceinline__ void bar_arrive(int id, int n) { asm volatile("bar.arrive %0, %1;" ::"r"(id), "r"(n) : "memory"); }

#define R8(a, i) "+f"(a[i]), "+f"(a[i + 1]), "+f"(a[i + 2]), "+f"(a[i + 3]), "+f"(a[i + 4]), "+f"(a[i + 5]), "+f"(a[i + 6]), "+f"(a[i + 7])
#define OP32(d, o) R8(d, o), R8(d, o + 8), R8(d, o + 16), R8(d, o + 24)
#define L32A "%0,%1,%2,%3,%4,%5,%6,%7,%8,%9,%10,%11,%12,%13,%14,%15,%16,%17,%18,%19,%20,%21,%22,%23,%24,%25,%26,%27,%28,%29,%30,%31"
#define L32B "%32,%33,%34,%35,%36,%37,%38,%39,%40,%41,%42,%43,%44,%45,%46,%47,%48,%49,%50,%51,%52,%53,%54,%55,%56,%57,%58,%59,%60,%61,%62,%63"
#define L32C "%64,%65,%66,%67,%68,%69,%70,%71,%72,%73,%74,%75,%76,%77,%78,%79,%80,%81,%82,%83,%84,%85,%86,%87,%88,%89,%90,%91,%92,%93,%94,%95"
#define WG_PRE(a, b, s, ha, hb) "{\n.reg .pred p;\n.reg .b64 da, db;\nmov.b64 da, {" a ", " ha "};\nmov.b64 db, {" b ", " hb "};\nsetp.ne.b32 p, " s ", 0;\n"

constexpr uint32_t HI128 = 0x40000040;
constexpr uint32_t HI64 = 0x80000080;
constexpr uint32_t HIQ = 0x80000040;
template <int TB>
__device__ __forceinline__ void wgmma_n128(float (&d)[64], uint32_t da, uint32_t ha, uint32_t db, uint32_t hb, int scale_d) {
  asm volatile(WG_PRE("%64", "%65", "%66", "%67", "%68") "wgmma.mma_async.sync.aligned.m64n128k16.f32.bf16.bf16 {" L32A "," L32B "}, da, db, p, 1, 1, 0, %69;\n}\n"
               : OP32(d, 0), OP32(d, 32)
               : "r"(da), "r"(db), "r"(scale_d), "r"(ha), "r"(hb), "n"(TB));
}
__device__ __forceinline__ void wgmma_n192_tb(float (&d)[96], uint32_t da, uint32_t db, int scale_d) {
  asm volatile(WG_PRE("%96", "%97", "%98", "%99", "%99") "wgmma.mma_async.sync.aligned.m64n192k16.f32.bf16.bf16 {" L32A "," L32B "," L32C "}, da, db, p, 1, 1, 0, 1;\n}\n"
               : OP32(d, 0), OP32(d, 32), OP32(d, 64)
               : "r"(da), "r"(db), "r"(scale_d), "r"(HI128));
}
__device__ __forceinline__ void wgmma_n64(float (&d)[64], uint32_t da, uint32_t db, int scale_d) {
  asm volatile(WG_PRE("%32", "%33", "%34", "%35", "%36") "wgmma.mma_async.sync.aligned.m64n64k16.f32.bf16.bf16 {" L32A "}, da, db, p, 1, 1, 0, 0;\n}\n"
               : OP32(d, 0)
               : "r"(da), "r"(db), "r"(scale_d), "r"(HIQ), "r"(HI64));
}
__device__ __forceinline__ void wgmma_n128_rs_tb(float (&d)[64], uint32_t a0, uint32_t a1, uint32_t a2, uint32_t a3, uint32_t db, int scale_d) {
  asm volatile("{\n.reg .pred p;\n.reg .b64 db;\nmov.b64 db, {%68, %70};\nsetp.ne.b32 p, %69, 0;\n"
               "wgmma.mma_async.sync.aligned.m64n128k16.f32.bf16.bf16 {" L32A "," L32B "}, {%64,%65,%66,%67}, db, p, 1, 1, 1;\n}\n"
               : OP32(d, 0), OP32(d, 32)
               : "r"(a0), "r"(a1), "r"(a2), "r"(a3), "r"(db), "r"(scale_d), "r"(HI64));
}
__device__ __forceinline__ void mma_16816(float (&c)[4], uint32_t a0, uint32_t a1, uint32_t a2, uint32_t a3, uint32_t b0, uint32_t b1) {
  asm volatile("mma.sync.aligned.m16n8k16.row.col.f32.bf16.bf16.f32 {%0,%1,%2,%3}, {%4,%5,%6,%7}, {%8,%9}, {%0,%1,%2,%3};"
               : "+f"(c[0]), "+f"(c[1]), "+f"(c[2]), "+f"(c[3])
               : "r"(a0), "r"(a1), "r"(a2), "r"(a3), "r"(b0), "r"(b1));
}
__device__ __forceinline__ uint32_t movm_t(uint32_t x) {
  uint32_t y;
  asm volatile("movmatrix.sync.aligned.m8n8.trans.b16 %0, %1;" : "=r"(y) : "r"(x));
  return y;
}
__device__ __forceinline__ void sts128(uint32_t a, uint32_t x, uint32_t y, uint32_t z, uint32_t w) {
  asm volatile("st.shared.v4.u32 [%0], {%1,%2,%3,%4};" ::"r"(a), "r"(x), "r"(y), "r"(z), "r"(w) : "memory");
}
__device__ __forceinline__ void stsm4(uint32_t a, uint32_t x, uint32_t y, uint32_t z, uint32_t w) {
  asm volatile("stmatrix.sync.aligned.m8n8.x4.shared.b16 [%0], {%1,%2,%3,%4};" ::"r"(a), "r"(x), "r"(y), "r"(z), "r"(w) : "memory");
}
__device__ __forceinline__ void ldsm4_t(uint32_t a, uint32_t (&r)[4]) {
  asm volatile("ldmatrix.sync.aligned.m8n8.x4.trans.shared.b16 {%0,%1,%2,%3}, [%4];"
               : "=r"(r[0]), "=r"(r[1]), "=r"(r[2]), "=r"(r[3])
               : "r"(a)
               : "memory");
}
__device__ __forceinline__ void stg128_if0(uint4* a, uint32_t x, uint32_t y, uint32_t z, uint32_t w, uint32_t sel) {
  asm volatile("{\n.reg .pred p;\nsetp.eq.u32 p, %5, 0;\n@p st.global.cs.v4.u32 [%0], {%1,%2,%3,%4};\n}" ::"l"(a), "r"(x), "r"(y), "r"(z), "r"(w),
               "r"(sel)
               : "memory");
}
template <int OFS>
__device__ __forceinline__ void stg128_sel(uint4* a, uint32_t x, uint32_t y, uint32_t z, uint32_t w, uint32_t sel) {
  asm volatile("{\n.reg .pred p;\nsetp.eq.u32 p, %5, 0;\n@p st.global.v4.u32 [%0+%6], {%1,%2,%3,%4};\n"
               "setp.eq.u32 p, %5, 2;\n@p st.global.cs.v4.u32 [%0+%6], {%1,%2,%3,%4};\n}" ::"l"(a), "r"(x), "r"(y), "r"(z), "r"(w), "r"(sel), "n"(OFS * 16)
               : "memory");
}
__device__ __forceinline__ void lds128(uint32_t a, uint32_t& x, uint32_t& y, uint32_t& z, uint32_t& w) {
  asm volatile("ld.shared.v4.u32 {%0,%1,%2,%3}, [%4];" : "=r"(x), "=r"(y), "=r"(z), "=r"(w) : "r"(a) : "memory");
}

constexpr int PLANE = 2048 * 16;
constexpr int PL_CTX = 0, PL_KV = 32, PL_OA = PL_KV + 64, NPLANES = PL_OA + 8;
__device__ __align__(1024) uint4 g_scr[NPLANES * PLANE];
__device__ uint4 g_carry[16 * 128];
constexpr int F_CTX = 0, F_KV = 512, F_L = 1040, F_CAR = 1056, F_EPOCH = 1072, F_END = 1072 + 132;
__device__ uint32_t g_flags[F_END];

#define NTURN 256

enum { K_KV = 1, K_L = 2, K_T = 3, K_OA = 4, K_OB = 5, K_END = 7 };
constexpr int NCLUSTERS = 66, MAXITEMS = 16, KEEP = 22;
constexpr int A_STAGE = 16384, B_SLOT = 32768;
constexpr int SM_B = 6 * A_STAGE, SM_CARRY = SM_B + 4 * B_SLOT, SM_BAR = SM_CARRY + 2048, SM_TOTAL = SM_BAR + 512;

struct Params {
  CUtensorMap mapA[3];
  CUtensorMap mapB[6];
  CUtensorMap mapO[2];
  uint4* scr;
  uint4* carry;
  uint32_t* flags;
  const uint32_t* x;
  const uint16_t* wq;
  uint32_t zero;
  uint16_t sched[NCLUSTERS * MAXITEMS];
};

__device__ __forceinline__ bool item_narrow(uint32_t item) { return (item & 0x204) == 0x204 || (item & 7) == K_T; }
__device__ __forceinline__ int item_nk(uint32_t item) {
  const uint32_t kind = item & 7;
  return (kind == K_KV ? 8 : kind == K_OB ? 64 : 16) >> item_narrow(item);
}
__device__ __forceinline__ int item_row(uint32_t kind, int g, int pos) {
  if (kind == K_L || kind == K_OA) return g == 0 ? (pos - 1) * 1024 : 64 * (3 * g - 2 + pos + (g > 5));
  return 64 * (3 * g - 1 + pos);
}

__device__ __forceinline__ void wait_flag(const uint32_t* f, uint32_t target) {
  uint32_t it = 0;
#pragma unroll 1
  while (true) {
    uint32_t v;
    asm volatile("ld.acquire.gpu.global.u32 %0, [%1];" : "=r"(v) : "l"(f) : "memory");
    if ((int)(v - target) >= 0) break;
    __nanosleep(40);
    if (++it > (1u << 18)) break;
  }
  asm volatile("fence.proxy.async.global;" ::: "memory");
}
__device__ __forceinline__ uint32_t wait_bits(const uint32_t* f, uint32_t inv, uint32_t mask) {
  uint32_t it = 0, v;
#pragma unroll 1
  while (true) {
    asm volatile("ld.acquire.gpu.global.u32 %0, [%1];" : "=r"(v) : "l"(f) : "memory");
    v ^= inv;
    if (!(~v & mask)) break;
    __nanosleep(40);
    if (++it > (1u << 18)) break;
  }
  asm volatile("fence.proxy.async.global;" ::: "memory");
  return v;
}
__device__ __forceinline__ void red_add(uint32_t* f) { asm volatile("red.relaxed.gpu.global.add.u32 [%0], 1;" ::"l"(f) : "memory"); }
__device__ __forceinline__ void red_xor(uint32_t* f, uint32_t v) {
  asm volatile("red.relaxed.gpu.global.xor.b32 [%0], %1;" ::"l"(f), "r"(v) : "memory");
}

constexpr float QS = 0.08838834764831845f * 1.4426950408889634f;
__device__ __noinline__ void attn_fallback(uint4* q, const uint4* __restrict__ k, const uint32_t* __restrict__ x,
                                           const uint16_t* __restrict__ w, int row0, int lane) {
  const int g = lane >> 2, tq = lane & 3;
  q += row0 * 16;
  k += lane ^ (lane >> 3);
  const uint4* v = k + 2 * PLANE;
  float o[16][4];
#pragma unroll
  for (int i = 0; i < 16; i++) o[i][0] = o[i][1] = o[i][2] = o[i][3] = 0.f;
  x += (row0 + g) * 512 + tq;
  w += 2 * tq * 4096 + g;
#pragma unroll 1
  for (int k0 = 0; k0 < 64; k0++, x += 8, w += 16 * 4096) {
#pragma unroll
    for (int i = 0; i < 16; i++)
      mma_16816(o[i], x[0], x[4096], x[4], x[4100], w[8 * i] | w[4096 + 8 * i] << 16, w[8 * 4096 + 8 * i] | w[9 * 4096 + 8 * i] << 16);
  }
#pragma unroll
  for (int i = 0; i < 8; i++) {
    const int c = 4 * (i >> 1), e = 2 * (i & 1);
    __stcg(q + (i >> 1) * 32 + (i & 1) * 128 + (lane ^ (lane >> 3)),
           make_uint4(pack_bf16(o[c][e], o[c][e + 1]), pack_bf16(o[c + 1][e], o[c + 1][e + 1]),
                      pack_bf16(o[c + 2][e], o[c + 2][e + 1]), pack_bf16(o[c + 3][e], o[c + 3][e + 1])));
  }
  __syncwarp();
#pragma unroll
  for (int i = 0; i < 16; i++) o[i][0] = o[i][1] = o[i][2] = o[i][3] = 0.f;
  float m0 = -INFINITY, m1 = -INFINITY, l0 = 0.f, l1 = 0.f;
#pragma unroll 1
  for (int k0 = 0; k0 < row0 + 16; k0 += 16) {
    float sc[2][4] = {{0.f, 0.f, 0.f, 0.f}, {0.f, 0.f, 0.f, 0.f}};
#pragma unroll 1
    for (int cg = 0; cg < 4; cg++) {
      const uint4 qa = __ldcg(q + cg * 32 + (lane ^ (lane >> 3)));
      const uint4 qb = __ldcg(q + 128 + cg * 32 + (lane ^ (lane >> 3)));
#pragma unroll
      for (int t = 0; t < 2; t++) {
        const uint4 kk = __ldcg(k + (k0 + 8 * t) * 16 + cg * 32);
        mma_16816(sc[t], qa.x, qb.x, qa.y, qb.y, kk.x, kk.y);
        mma_16816(sc[t], qa.z, qb.z, qa.w, qb.w, kk.z, kk.w);
      }
    }
    float x0 = -INFINITY, x1 = -INFINITY;
#pragma unroll
    for (int t = 0; t < 2; t++) {
#pragma unroll
      for (int e = 0; e < 2; e++) {
        const int key = k0 + 8 * t + 2 * tq + e;
        if (key > row0 + g) sc[t][e] = -INFINITY;
        if (key > row0 + g + 8) sc[t][2 + e] = -INFINITY;
        x0 = fmaxf(x0, sc[t][e]);
        x1 = fmaxf(x1, sc[t][2 + e]);
      }
    }
    x0 = fmaxf(x0, __shfl_xor_sync(0xffffffffu, x0, 1));
    x1 = fmaxf(x1, __shfl_xor_sync(0xffffffffu, x1, 1));
    x0 = fmaxf(x0, __shfl_xor_sync(0xffffffffu, x0, 2));
    x1 = fmaxf(x1, __shfl_xor_sync(0xffffffffu, x1, 2));
    const float n0 = fmaxf(m0, x0), n1 = fmaxf(m1, x1);
    const float a0 = ex2(m0 - n0), a1 = ex2(m1 - n1);
    m0 = n0;
    m1 = n1;
    l0 *= a0;
    l1 *= a1;
    uint32_t pa[4];
#pragma unroll
    for (int t = 0; t < 2; t++) {
      const float e0 = ex2(sc[t][0] - m0), e1 = ex2(sc[t][1] - m0);
      const float e2 = ex2(sc[t][2] - m1), e3 = ex2(sc[t][3] - m1);
      l0 += e0 + e1;
      l1 += e2 + e3;
      pa[2 * t] = pack_bf16(e0, e1);
      pa[2 * t + 1] = pack_bf16(e2, e3);
    }
#pragma unroll
    for (int cg = 0; cg < 4; cg++) {
      const uint4 va = __ldcg(v + k0 * 16 + cg * 32);
      const uint4 vb = __ldcg(v + k0 * 16 + 128 + cg * 32);
#pragma unroll
      for (int r = 0; r < 4; r++) {
        const uint32_t w0 = r == 0 ? va.x : r == 1 ? va.y : r == 2 ? va.z : va.w;
        const uint32_t w1 = r == 0 ? vb.x : r == 1 ? vb.y : r == 2 ? vb.z : vb.w;
        float(&oo)[4] = o[4 * cg + r];
        oo[0] *= a0;
        oo[1] *= a0;
        oo[2] *= a1;
        oo[3] *= a1;
        mma_16816(oo, pa[0], pa[1], pa[2], pa[3], movm_t(w0), movm_t(w1));
      }
    }
  }
  l0 += __shfl_xor_sync(0xffffffffu, l0, 1);
  l1 += __shfl_xor_sync(0xffffffffu, l1, 1);
  l0 += __shfl_xor_sync(0xffffffffu, l0, 2);
  l1 += __shfl_xor_sync(0xffffffffu, l1, 2);
  const float i0 = 1.f / l0, i1 = 1.f / l1;
  __syncwarp();
  uint32_t* o0 = reinterpret_cast<uint32_t*>(q + g * 4) + tq;
#pragma unroll
  for (int i = 0; i < 16; i++) {
    uint32_t* d = o0 + (i >> 2) * 128 + ((i & 3) ^ (g >> 1)) * 4;
    d[0] = pack_bf16(o[i][0] * i0, o[i][1] * i0);
    d[512] = pack_bf16(o[i][2] * i1, o[i][3] * i1);
  }
}

#define KB_LIMIT 1.2089258e24f
#define KB_LOW 9.094947e-13f

__device__ __forceinline__ void local_scores(float (&s)[2][4], const uint32_t (&lo)[24], const uint32_t (&hi)[24], const uint32_t* k) {
#pragma unroll
  for (int h = 0; h < 2; h++) s[h][0] = s[h][1] = s[h][2] = s[h][3] = 0.f;
#pragma unroll
  for (int c = 0; c < 4; c += 2)
#pragma unroll
    for (int h = 0; h < 8; h += 4) mma_16816(s[h >> 2], lo[h + c], hi[h + c], lo[h + c + 1], hi[h + c + 1], k[h + c], k[h + c + 1]);
}
__device__ __forceinline__ void local_attn(float (&o)[2][4][4], float (&l)[2][4], const float (&s)[3][2][4], const uint32_t (&vt)[2][4][4],
                                           bool first, int lane) {
  const int g = lane >> 2, tq = lane & 3;
  const bool h0 = 2 * tq > g, h1 = 2 * tq + 1 > g;
  const uint32_t m = (h0 ? 0xFFFFu : 0u) | (h1 ? 0xFFFF0000u : 0u);
  float u0[2], u1[2], w0[2], w1[2], mu[2], mw[2];
#pragma unroll
  for (int h = 0; h < 2; h++) {
    u0[h] = h0 ? s[0][h][0] : s[1][h][0];
    u1[h] = h1 ? s[0][h][1] : s[1][h][1];
    w0[h] = h0 ? s[1][h][2] : s[2][h][2];
    w1[h] = h1 ? s[1][h][3] : s[2][h][3];
    if (first) {
      if (h0) u0[h] = -INFINITY;
      if (h1) u1[h] = -INFINITY;
    }
    mu[h] = fmaxf(u0[h], u1[h]);
    mw[h] = fmaxf(w0[h], w1[h]);
  }
#pragma unroll
  for (int o = 1; o <= 2; o++)
#pragma unroll
    for (int h = 0; h < 2; h++) {
      mw[h] = fmaxf(mw[h], __shfl_xor_sync(0xffffffffu, mw[h], o));
      mu[h] = fmaxf(mu[h], __shfl_xor_sync(0xffffffffu, mu[h], o));
    }
  const float c = 0.17677669529663687f * 1.4426950408889634f;
#pragma unroll
  for (int h = 0; h < 2; h++) {
    const uint32_t pu = pack_bf16(ex2((u0[h] - mu[h]) * c), ex2((u1[h] - mu[h]) * c));
    const uint32_t pw = pack_bf16(ex2((w0[h] - mw[h]) * c), ex2((w1[h] - mw[h]) * c));
    l[h][0] = l[h][1] = l[h][2] = l[h][3] = 0.f;
    mma_16816(l[h], 0x3F803F80, 0u, 0u, 0x3F803F80, pu, pw);
#pragma unroll
    for (int i = 0; i < 4; i++) {
      const uint32_t(&v)[4] = vt[i >> 1][2 * h + (i & 1)];
      o[h][i][0] = o[h][i][1] = o[h][i][2] = o[h][i][3] = 0.f;
      mma_16816(o[h][i], v[0], v[1], v[2], v[3], i < 2 ? pu & m : pw & ~m, i < 2 ? pu & ~m : pw & m);
    }
  }
}

__global__ __cluster_dims__(2, 1, 1) __launch_bounds__(512, 1) void fused_kernel(const __grid_constant__ Params p) {
  extern __shared__ __align__(1024) uint8_t smem_dyn[];
  DECLARE_READY();
  const uint32_t sbase = smem_u32(smem_dyn);
  const uint32_t afull0 = sbase + SM_BAR, aempty0 = afull0 + 48, bfull0 = afull0 + 96, bempty0 = afull0 + 128, carbar = afull0 + 160,
                 pub0 = afull0 + 200;
  const uint32_t bbase = sbase + SM_B;
  const int wg = __reduce_min_sync(0xffffffffu, (int)(threadIdx.x >> 7));
  const uint32_t rank = blockIdx.x & 1;
  const uint16_t* sched = p.sched + (blockIdx.x >> 1) * MAXITEMS;

  auto fill_b = [&](uint32_t item, int t, uint32_t pb, uint32_t pol) {
    const uint32_t kind = item & 7, j = (item >> 7) & 15, sl = pb & 3;
    if (((item >> 3) & 15) == 0) mbar_arrive_n(bempty0 + 8 * sl, 1);
    mbar_expect_tx(bfull0 + 8 * sl, kind == K_L ? 24576 : 32768);
    const uint32_t nt = kind == K_KV ? j : 2 * j + rank, dst = bbase + sl * B_SLOT;
    const uint32_t cb = kind == K_T ? nt : item_narrow(item) ? nt - 8 : nt * 2 + (t >> 1 & 1);
    const uint32_t ks = item_narrow(item) ? t : (t >> 1 & ~1) + (t & 1);
    if (kind == K_OA) {
      tma_load_5d(dst, &p.mapB[K_OA], bfull0 + 8 * sl, cb * 128, ks * 4);
      tma_load_5d(dst + 16384, &p.mapB[K_OA], bfull0 + 8 * sl, cb * 128 + 64, ks * 4);
    } else if (kind == K_L) {
      tma_load_3d(dst, &p.mapB[K_L], bfull0 + 8 * sl, nt * 64, t * 64, 0, pol);
    } else {
      tma_load_3d(dst, &p.mapB[kind == K_KV ? 1 - rank : kind], bfull0 + 8 * sl, 0, ks * 128, cb * 2, pol);
    }
  };
  auto first_a = [&](uint32_t item0, uint32_t u, bool mc) {
    const bool local0 = (item0 & 7) == K_L;
    const int g0 = (item0 >> 3) & 15;
    const int row = item_row(local0 ? K_L : K_KV, g0, (u >> 1) + (g0 == 0));
    const int r = local0 ? row & 1023 : row, blk = (local0 ? (row >> 10) * 16 : 0) + 2 * (u & 1);
    if (mc) {
      mbar_expect_tx(afull0 + 8 * u, A_STAGE);
      tma_load_3d_mc(sbase + u * A_STAGE + rank * 8192, &p.mapA[local0], afull0 + 8 * u, 0, r, blk + rank, (uint16_t)3);
    } else
      for (int h = 0; h < 2; h++) tma_load_3d(sbase + u * A_STAGE + h * 8192, &p.mapA[local0], afull0 + 8 * u, 0, r, blk + h);
  };
  auto first_b = [&](uint32_t item0, uint32_t t) {
    const bool local0 = (item0 & 7) == K_L;
    const int j = (item0 >> 7) & 15;
    mbar_expect_tx(bfull0 + 8 * t, local0 ? 24576 : 32768);
    tma_load_3d(bbase + t * B_SLOT, &p.mapB[local0 ? K_L : 1 - rank], bfull0 + 8 * t, local0 ? (2 * j + rank) * 64 : 0,
                local0 ? t * 64 : (t & 1) * 128, local0 ? 0 : 4 * j + (t & 2));
    if ((item0 & 0x78) == 0) mbar_arrive_n(bempty0 + 8 * t, 1);
  };
  if (threadIdx.x == 0) {
    mbar_init(bfull0, 1);
    mbar_init(bempty0, 3);
    asm volatile("fence.mbarrier_init.release.cluster;" ::: "memory");
    first_b(sched[0], 0);
  } else if (threadIdx.x == 32) {
    mbar_init(afull0, 1);
    asm volatile("fence.mbarrier_init.release.cluster;" ::: "memory");
    mbar_expect_tx(afull0, A_STAGE);
    first_a(sched[0], 0, false);
  } else if (threadIdx.x == 64) {
    for (int i = 20; i < 35; i++) mbar_init(afull0 + 8 * i, i < 25 ? 1 : 12);
  } else if (threadIdx.x == 96) {
    for (int i = 1; i < 20; i++)
      if (i != 12 && i != 16) mbar_init(afull0 + 8 * i, i < 6 ? 1 : i < 12 ? 2 : i < 16 ? 1 : 3);
    asm volatile("fence.mbarrier_init.release.cluster;" ::: "memory");
  }
  __syncthreads();
  asm volatile("barrier.cluster.arrive.relaxed.aligned;\nbarrier.cluster.wait.aligned;" ::: "memory");

  if (wg == 0) {
    asm volatile("setmaxnreg.dec.sync.aligned.u32 32;");
    const uint32_t item0 = sched[0];
    const bool local0 = (item0 & 7) == K_L;
    const int g0 = (item0 >> 3) & 15;
    if (threadIdx.x == 96) {
#pragma unroll 1
      for (uint32_t x = local0 ? 0x6B42A593u : 0xB6A45239u; x; x >>= 4) {
        if (x & 8) first_b(item0, x & 3);
        else if (g0 != 0 || (x & 7) < 5) first_a(item0, (x & 7) - 1, true);
      }
    }
    if (__reduce_min_sync(0xffffffffu, (int)(threadIdx.x >> 5)) == 1) {
      const uint32_t e = __ldcg(p.flags + F_EPOCH + blockIdx.x) + 1;
      const uint32_t w = threadIdx.x - 32;
      uint32_t n = w < 2 || ((sched[0] >> 3) & 15) != 0 ? 2 : 0;
      uint32_t bar0 = afull0 + 16 * w, dst0 = sbase + w * (2 * A_STAGE) + rank * 8192;
      asm volatile("" : "+r"(bar0), "+r"(dst0));
      uint32_t bar, dst, par, prev = 0;
      auto position = [&]() {
        bar = bar0 + 8 * (n & 1), dst = dst0 + (n & 1) * A_STAGE, par = (~n >> 1) & 1;
        asm volatile("" : "+r"(bar), "+r"(dst), "+r"(par));
      };
      position();
      for (int it = 0; it < MAXITEMS; it++) {
        const uint32_t item = sched[it];
        const uint32_t kind = item & 7;
        if (kind == K_END) break;
        const int g = (item >> 3) & 15;
        const int nd = kind == K_T ? 8 : item_nk(kind) >> 1;
        if (kind == K_OA) wait_flag(p.flags + F_L + g, 16 * e);
        int rho = w + (item >> 11);
        if (rho >= 3) rho -= 3;
        const int row = item_row(kind, g, kind == K_T ? 2 - rho : rho + (g == 0));
        const uint32_t on = w > 2 || (g == 0 && rho == 2) ? 0 : ~0u, swap = rho == 1 ? 0 : on, base = (0x924924 >> rho) & on;
        uint32_t m = base ^ (swap & (kind == K_L ? 0xB6DB6D : (item_narrow(item) ? (prev == K_KV ? 1 : 0x6D) : prev == K_KV ? 0x861861 : 0x86186D)));
        prev = kind;
        auto step = [&](auto load) {
          if (m & 1) {
            mbar_wait(bar + 48, par);
            mbar_expect_tx(bar, A_STAGE);
            load();
            n++;
            position();
          }
          m >>= 1;
          __syncwarp();
        };
        if (kind >= K_OA) {
          const uint4* src = p.scr + (kind == K_OA ? PL_OA : PL_CTX) * PLANE + row * 16 + rank * 512;
          uint32_t heads = kind == K_OA ? ~0u : 0, need = 1;
          for (int t = 0; t <= nd; t++, need <<= 1) {
            if (~heads & need) heads = wait_bits(p.flags + F_CTX + g * 32, (e & 1) - 1, need);
            if (item_narrow(item) && t > 2) m = (base >> 2) ^ (t == nd ? swap : 0);
#pragma unroll 1
            for (int x = t == 0; x < (t == nd ? 1 : 3); x++)
              step([&]() {
                bulk_load_mc(dst, src, 8192, bar, (uint16_t)3);
                src += PLANE;
              });
          }
        } else {
          const int r = kind == K_L ? row & 1023 : row;
          int blk = (kind == K_L ? (row >> 10) * 16 : 0) + rank;
          if (kind == K_T) m ^= swap & 0x800000;
          if (it == 0) m &= m - 1, m &= m - 1, blk += 4;
#pragma unroll 1
          for (int x = 3 * nd; x; x--)
            step([&]() {
              tma_load_3d_mc(dst, &p.mapA[kind - 1], bar, 0, r, blk, (uint16_t)3);
              blk += 2;
            });
        }
      }
      if (w < 3) {
        mbar_wait(bar0 + 48, (~(n + 1) >> 1) & 1);
        mbar_wait(bar0 + 56, (~n >> 1) & 1);
      }
    } else if (threadIdx.x == 0) {
      const uint32_t e = __ldcg(p.flags + F_EPOCH + blockIdx.x) + 1;
      uint32_t pb = 4;
      for (int it = 0; it < MAXITEMS; it++) {
        const uint32_t item = sched[it];
        const uint32_t kind = item & 7;
        if (kind == K_END) break;
        const int nk = item_nk(item);
        uint32_t heads = kind == K_OB ? wait_bits(p.flags + F_CTX + ((item >> 3) & 15) * 32, (e & 1) - 1, 0) : 0;
        const int keep = ((const uint8_t*)sched)[KEEP + it];
        for (int t = it == 0 ? 4 : 0; t < nk; t++, pb++) {
          mbar_wait(bempty0 + 8 * (pb & 3), ((pb >> 2) & 1) ^ 1);
          fill_b(item, t, pb, keep & 32 ? L2_NORMAL : L2_FIRST);
          if (item_narrow(item) && kind == K_OB) {
            const uint32_t g = (item >> 3) & 15, nb = g ? 3 : 2;
            if (!(heads >> t & 2)) heads = wait_bits(p.flags + F_CTX + g * 32, (e & 1) - 1, 0);
            if (heads >> t & 2) prefetch_l2(p.scr + (PL_CTX + t + 1) * PLANE + (3 * g + 2 - nb) * 1024 + rank * nb * 512, nb * 8192);
          }
        }
        if (kind == K_T) {
          const int g = (item >> 3) & 15, j = (item >> 7) & 15;
          const uint4* src = p.scr + (PL_KV + j * 4 + rank) * PLANE;
          const int n = ((3 * g + 1) >> 1) + 1;
          uint32_t groups = 0;
          for (int t = 0; t < n; t++, src += 2048) {
            const uint32_t need = (4u << 2 * min((2 * t + 2) / 3, g)) - 1;
            if (~groups & need) groups = wait_bits(p.flags + F_KV + j * 32, (e & 1) - 1, need);
            const uint32_t nskip = t == n - 1 ? 1 + (g & 1) : 0;
            const uint32_t pol = t < (keep & 31) ? L2_NORMAL : L2_FIRST;
            uint32_t sl = pb & 3;
            mbar_wait(bempty0 + 8 * sl, ((pb >> 2) & 1) ^ 1);
            if (nskip) mbar_arrive_n(bempty0 + 8 * sl, nskip);
            mbar_expect_tx(bfull0 + 8 * sl, 32768);
            pb++;
            if (nskip == 2) {
              bulk_load(bbase + sl * B_SLOT, src, 16384, bfull0 + 8 * sl, pol);
              bulk_load(bbase + sl * B_SLOT + 16384, src + 2 * PLANE, 16384, bfull0 + 8 * sl, pol);
              continue;
            }
            bulk_load(bbase + sl * B_SLOT, src, 32768, bfull0 + 8 * sl, pol);
            sl = pb & 3;
            mbar_wait(bempty0 + 8 * sl, ((pb >> 2) & 1) ^ 1);
            if (nskip) mbar_arrive_n(bempty0 + 8 * sl, nskip);
            mbar_expect_tx(bfull0 + 8 * sl, 32768);
            bulk_load(bbase + sl * B_SLOT, src + 2 * PLANE, 32768, bfull0 + 8 * sl, pol);
            pb++;
          }
        }
      }
    } else if (threadIdx.x == 64) {
      const uint32_t pair = 2 * ((sched[0] >> 7) & 15) + rank;
      if ((sched[0] & 127) == K_L) {
        mbar_wait(carbar + 24, 0);
        asm volatile("fence.proxy.async.shared::cta;\ncp.async.bulk.global.shared::cta.bulk_group [%0], [%1], 2048;\n"
                     "cp.async.bulk.commit_group;\ncp.async.bulk.wait_group 0;\nfence.proxy.async.global;\nfence.acq_rel.gpu;" ::"l"(p.carry + pair * 128),
                     "r"(sbase + SM_CARRY - 2048)
                     : "memory");
        red_add(p.flags + F_CAR + pair);
      }
      if ((sched[0] & 127) == (K_L | 6 << 3)) {
        wait_flag(p.flags + F_CAR + pair, __ldcg(p.flags + F_EPOCH + blockIdx.x) + 1);
        mbar_expect_tx(carbar + 32, 2048);
        bulk_load(sbase + SM_CARRY, p.carry + pair * 128, 2048, carbar + 32);
      }
      for (int it = 0; it < MAXITEMS; it++) {
        const uint32_t item = sched[it];
        const uint32_t kind = item & 7;
        const int g = (item >> 3) & 15, j = (item >> 7) & 15;
        if (kind >= K_OA) break;
        mbar_wait(pub0 + 8 * it, 0);
        asm volatile("fence.acq_rel.gpu;" ::: "memory");
        if (kind == K_KV) red_xor(p.flags + F_KV + j * 32, 1u << (2 * g + rank));
        if (kind == K_L) red_add(p.flags + F_L + g);
        if (kind == K_T) red_xor(p.flags + F_CTX + g * 32, 1u << (2 * j + rank));
      }
      red_add(p.flags + F_EPOCH + blockIdx.x);
    } else if (threadIdx.x == 96) {
      for (int i = 0; i < 3; i++) prefetch_tmap(&p.mapA[i]);
      for (int i = 0; i < 6; i++) prefetch_tmap(&p.mapB[i]);
      prefetch_tmap(&p.mapO[0]);
      prefetch_tmap(&p.mapO[1]);
    }
  } else {
    asm volatile("setmaxnreg.inc.sync.aligned.u32 160;");
    const int cw = wg - 1;
    const int wq = __reduce_min_sync(0xffffffffu, (int)((threadIdx.x >> 5) & 3));
    auto turn = [&](uint32_t dep = 0) {
      bar_sync((1 + cw) | dep, NTURN);
    };
    const int fwd = cw == 0 ? 3 : cw, back = cw == 2 ? 1 : cw + 2;
    int next = fwd;
    auto pass = [&]() {
      bar_arrive(next, NTURN);
      next = fwd;
    };
    auto rank_of = [&](uint32_t item) {
      const int r = cw + (item >> 11);
      return r >= 3 ? r - 3 : r;
    };
    if (cw == 1) pass();
    if (cw == 2) { turn(); pass(); }
    const uint32_t abase = sbase + cw * (2 * A_STAGE), afull = afull0 + 16 * cw, aempty = aempty0 + 16 * cw;
    const uint32_t adesc = ((abase & 0x3FFFF) >> 4) | (1u << 16), bdesc = (bbase & 0x3FFFF) >> 4;
    uint32_t pa = 0, pb = 0;
    int it = 0;
    uint32_t item = sched[0];
    auto publish = [&](int i, uint32_t skip = 0) {
      __syncwarp();
      mbar_arrive_if0(pub0 + 8 * i, (threadIdx.x & 31) | skip);
    };
    auto test_ab = [&](uint32_t a, uint32_t b) {
      test_a(afull + 8 * (a & 1), (a >> 1) & 1);
      test_b(bfull0 + 8 * (b & 3), (b >> 2) & 1);
    };
    auto wait_ab = [&]() {
      if (!ready_ab()) {
        mbar_wait_u(afull + 8 * (pa & 1), (pa >> 1) & 1);
        mbar_wait_u(bfull0 + 8 * (pb & 3), (pb >> 2) & 1);
      }
    };
    auto release_ab = [&](uint32_t a, uint32_t b, uint32_t skip) {
      mbar_arrive_cta_if0(wq < 2 ? aempty + 8 * (a & 1) : bempty0 + 8 * (b & 3), wq < 2 ? wq : rank, (threadIdx.x & 31) | (wq == 3) | skip);
    };
    test_ab(0, 0);
    uint32_t bflag = 512u << 16;
    enum { NEW = 1, REL = 2, FWD = 4, TEST = 8, BACK = 16 };
    auto gturn = [&](auto mode_c, bool hold, auto mma, auto meanwhile) {
      constexpr int MODE = decltype(mode_c)::value;
      uint32_t da = adesc + (pa & 1) * (A_STAGE >> 4), db = bdesc + (pb & 3) * (B_SLOT >> 4) + bflag;
      asm volatile("" : "+r"(da), "+r"(db));
      if (MODE & NEW) wait_ab();
      else if (!ready_b()) mbar_wait_u(bfull0 + 8 * (pb & 3), (pb >> 2) & 1);
      turn();
      wg_fence();
      mma(da, db);
      wg_commit();
      if (!hold) pass();
      if (hold) {
      } else if (MODE & TEST) test_ab(pa + 1, pb + 1);
      else test_b(bfull0 + 8 * ((pb + 1) & 3), ((pb + 1) >> 2) & 1);
      meanwhile();
      wg_wait<0>();
      if (MODE & REL) {
        if (!hold) release_ab(pa, pb, 0);
      } else {
        mbar_arrive_if0(bempty0 + 8 * (pb & 3), threadIdx.x & 127);
      }
      if (MODE & FWD) pa++;
      if (MODE & BACK) pa--;
      __syncwarp();
      pb++;
    };
    constexpr std::true_type YES{};
    constexpr std::false_type NO{};
    constexpr std::integral_constant<int, NEW> FIRST{};
    constexpr std::integral_constant<int, REL | FWD | TEST> SECOND{};
    constexpr std::integral_constant<int, NEW | REL | FWD | TEST> ONCE{};
    constexpr std::integral_constant<int, NEW | FWD | TEST> X0{};
    constexpr std::integral_constant<int, NEW | BACK> X1{};
    constexpr std::integral_constant<int, REL | FWD> Y0{};
    auto nothing = []() {};
    auto idle = [&]() { return ((item >> 3) & 15) == 0 && rank_of(item) == 2; };
    auto skip_item = [&](int passed) {
      const int n = (item & 7) == K_T ? 10 : item_nk(item);
      publish(it);
#pragma unroll 1
      for (int i = 2 + passed; i < n; i++) {
        turn();
        pass();
      }
      pb += n;
      test_ab(pa, pb);
      item = sched[++it];
    };

    if ((item & 7) == K_L && idle()) skip_item(0);
    float lo_[2][4][4] = {}, ll[2][4] = {};
    uint4* ldst = p.scr;
    uint32_t lnone = 1;
    auto lrelease = [&]() { release_ab(1, 3, lnone); };
    auto lpack = [&](uint32_t (&r)[16]) {
      const uint32_t t = sched_fence() & p.zero;
#pragma unroll
      for (int i = 0; i < 4; i++) {
        const int h = i >> 1, e = i & 1 ? 2 : 0;
        const float f0 = rcp(__uint_as_float(__float_as_uint(ll[h][e]) | t)), f1 = rcp(__uint_as_float(__float_as_uint(ll[h][e + 1]) | t));
        const float(&r0)[4] = lo_[h][e], (&r1)[4] = lo_[h][e + 1];
        r[4 * i] = movm_t(pack_bf16(r0[0] * f0, r0[1] * f1)), r[4 * i + 1] = movm_t(pack_bf16(r0[2] * f0, r0[3] * f1));
        r[4 * i + 2] = movm_t(pack_bf16(r1[0] * f0, r1[1] * f1)), r[4 * i + 3] = movm_t(pack_bf16(r1[2] * f0, r1[3] * f1));
      }
#pragma unroll
      for (int i = 0; i < 16; i++) asm volatile("" : "+r"(r[i])::"memory");
    };
    auto lstore = [&](const uint32_t (&r)[16]) {
#pragma unroll
      for (int i = 0; i < 4; i++) stg128_if0(ldst + (i >> 1) * 32 + (i & 1) * 128, r[4 * i], r[4 * i + 1], r[4 * i + 2], r[4 * i + 3], lnone);
      publish(it - 1, lnone);
    };
    while ((item & 7) == K_L) {
      const int g = (item >> 3) & 15, j = (item >> 7) & 15;
      const int rho = rank_of(item);
      float acc[96];
      auto mma = [&](int kb, bool first) {
        return [&acc, kb, first](uint32_t da, uint32_t db) {
#pragma unroll
          for (int k = 0; k < 4; k++) wgmma_n192_tb(acc, da + kb * 512 + k * 2, db + k * 128, !(first && k == 0));
        };
      };
      gturn(FIRST, false, mma(0, true), lrelease);
      uint32_t r[16];
      gturn(SECOND, false, mma(1, false), [&]() { lpack(r); lstore(r); });
#pragma unroll 1
      for (int d = 7;;) {
        gturn(FIRST, false, mma(0, false), nothing);
        if (--d == 0) break;
        gturn(SECOND, false, mma(1, false), nothing);
      }
      const int lane = threadIdx.x & 31;
      const int from = rho ? rho : 4 * (~g & 1), to = g == 0 ? 3 * rho : rho == 2 ? 4 * (g & 1) : rho + 1;
      uint32_t own, front, vlo;
      gturn(SECOND, true, mma(1, false), [&]() {
        bar_arrive_if(rho != 2, g && rho ? back : next, NTURN);
        own = (wq < 3 ? abase + A_STAGE + wq * 2048 : sbase + SM_CARRY - 8192 + to * 2048) + lane * 16;
        front = (wq > 0 ? abase + A_STAGE + wq * 2048 - 2048 : g == 0 ? abase + A_STAGE : sbase + SM_CARRY - 8192 + from * 2048) + lane * 16;
        vlo = abase + A_STAGE + 8192 + wq * 1024 + lane * 16;
        ldst = p.scr + (PL_OA + j) * PLANE + (item_row(K_L, g, rho + (g == 0)) + wq * 16) * 16 + rank * 64 + (lane ^ (lane >> 3));
        asm volatile("" : "+r"(own), "+r"(front), "+r"(vlo), "+l"(ldst));
        lnone = 0;
        item = sched[++it];
        if (wq == 0 && g != 0) mbar_wait_u(carbar + 8 * from, ((g - (g <= 5 ? 1 : 6)) >> (rho == 0)) & 1);
      });
      if (g && rho == 0) next = back;
      fence_regs(acc);
      uint32_t lo[24], hi[24], hk[8], vt[2][4][4];
#pragma unroll
      for (int i = 0; i < 24; i++) {
        lo[i] = pack_bf16(acc[4 * i], acc[4 * i + 1]);
        hi[i] = pack_bf16(acc[4 * i + 2], acc[4 * i + 3]);
      }
      sts128(own, hi[8], hi[9], hi[10], hi[11]);
      sts128(own + 512, hi[12], hi[13], hi[14], hi[15]);
      stsm4(own + 1024, hi[16], hi[17], hi[18], hi[19]);
      stsm4(own + 1536, hi[20], hi[21], hi[22], hi[23]);
      __syncwarp();
      mbar_arrive_if0(carbar + 8 * to, lane | (wq ^ 3));
      stsm4(vlo, lo[16], lo[17], lo[18], lo[19]);
      stsm4(vlo + 512, lo[20], lo[21], lo[22], lo[23]);
      bar_sync(4 + cw, 128);
      lds128(front, hk[0], hk[1], hk[2], hk[3]);
      lds128(front + 512, hk[4], hk[5], hk[6], hk[7]);
#pragma unroll
      for (int i = 0; i < 8; i++) ldsm4_t((lane < 16 ? (i < 4 ? front : own) + 1024 : vlo - 256) + (i & 3) * 256, vt[i >> 2][i & 3]);
      float sc[3][2][4];
      local_scores(sc[2], lo, hi, hi + 8);
      local_scores(sc[1], lo, hi, lo + 8);
      local_scores(sc[0], lo, hi, hk);
      test_ab(pa, pb);
      local_attn(lo_, ll, sc, vt, g == 0 && wq == 0, lane);
      bar_arrive_if(rho == 2, back, NTURN);
    }
    if (!lnone) {
      bar_sync(4 + cw, 128);
      lrelease();
      uint32_t r[16];
      lpack(r);
      lstore(r);
    }

    bflag = 1024u << 16;
    float Y[64];
    float sc0 = 0.f, sc1 = 0.f;
    uint32_t done;
    uint4* pdst;
    auto pack = [&](uint32_t (&r)[16], const float (&acc)[64], int h, float s0, float s1) {
#pragma unroll
      for (int i = 0; i < 8; i++) {
        const int c = 32 * h + 4 * i;
        r[8 * (i >> 2) + (i & 3)] = pack_bf16(acc[c] * s0, acc[c + 1] * s0);
        r[8 * (i >> 2) + (i & 3) + 4] = pack_bf16(acc[c + 2] * s1, acc[c + 3] * s1);
      }
    };
    auto pack_now = [&](uint32_t (&r)[16], const float (&acc)[64], int h) {
      pack(r, acc, h, sc0, sc1);
#pragma unroll
      for (int i = 0; i < 16; i++) asm volatile("" : "+r"(r[i])::"memory");
    };
    auto stores = [&](auto ofs_c, const uint32_t (&r)[16], uint32_t sel) {
      constexpr int OFS = decltype(ofs_c)::value;
      stg128_sel<OFS>(pdst, r[0], r[1], r[2], r[3], sel);
      stg128_sel<OFS + 128>(pdst, r[4], r[5], r[6], r[7], sel);
      stg128_sel<OFS + 32>(pdst, r[8], r[9], r[10], r[11], sel);
      stg128_sel<OFS + 160>(pdst, r[12], r[13], r[14], r[15], sel);
    };
    constexpr std::integral_constant<int, 0> H0{};
    constexpr std::integral_constant<int, 64> H1{};
    auto flush = [&]() {
      uint32_t r[16];
      turn();
      pass();
      sched_fence();
      pack(r, Y, 0, sc0, sc1);
      stores(H0, r, done);
      turn();
      pass();
      sched_fence();
      pack(r, Y, 1, sc0, sc1);
      stores(H1, r, done);
      publish(it - 1, done & 1);
    };
    auto no_pending = [&]() {
      done = 1;
      pdst = p.scr;
#pragma unroll
      for (int i = 0; i < 64; i++) Y[i] = 0.f;
      fence_regs(Y);
    };
    no_pending();
    auto mma128 = [&](auto scr_c, float (&acc)[64], int keep) {
      return [&acc, keep](uint32_t da, uint32_t db) {
        constexpr bool SCR = decltype(scr_c)::value;
#pragma unroll
        for (int k = 0; k < 8; k++)
          wgmma_n128<1>(acc, da + (k & 1) * 2 + ((k >> 1) & 1) * (SCR ? 32 : 4) + (k >> 2) * (SCR ? 64 : 512), SCR ? HI64 : HI128,
                        db + k * 128, HI128, k != 0 || keep);
      };
    };
    auto first_two = [&](auto mode0, auto mode1, auto scr_c, float (&X)[64]) {
      uint32_t r0[16], r1[16];
      gturn(mode0, false, mma128(scr_c, X, false), [&]() { pack_now(r0, Y, 0); });
      stores(H0, r0, done);
      gturn(mode1, false, mma128(scr_c, X, true), [&]() { pack_now(r1, Y, 1); });
      stores(H1, r1, done);
      publish(it - 1, done & 1);
    };
    auto all_but_last_two = [&](auto scr_c, float (&X)[64]) {
      int n = item_nk(item);
      first_two(X0, X1, scr_c, X);
      gturn(Y0, false, mma128(scr_c, Y, false), nothing);
#pragma unroll 1
      while (true) {
        gturn(SECOND, false, mma128(scr_c, Y, true), nothing);
        gturn(X0, false, mma128(scr_c, X, true), nothing);
        gturn(X1, false, mma128(scr_c, X, true), nothing);
        if (!decltype(scr_c)::value || (n -= 4) == 4) break;
        gturn(Y0, false, mma128(scr_c, Y, true), nothing);
      }
      fence_regs(X);
    };
    while ((item & 7) < K_OA) {
      if (idle()) {
        flush();
        done = 1;
        skip_item(2);
        continue;
      }
      const uint32_t kind = item & 7;
      const int g = (item >> 3) & 15, j = (item >> 7) & 15;
      const int rho = rank_of(item);
      if (kind != K_T) {
        float X[64];
        all_but_last_two(NO, X);
        const int lane = threadIdx.x & 31;
        const int row = item_row(K_KV, g, rho + (g == 0)) + wq * 16;
        sc0 = sc1 = rank ? 1.f : QS;
        pdst = p.scr + (PL_KV + j * 4 + rank * 2 + 1) * PLANE + row * 16 + (lane ^ (lane >> 3));
        uint32_t r0[16], r1[16];
        pack(r0, X, 0, sc0, sc1);
        stores(std::integral_constant<int, -PLANE>{}, r0, 0);
        gturn(Y0, false, mma128(NO, Y, true), [&]() { pack_now(r1, X, 1); });
        stores(std::integral_constant<int, 64 - PLANE>{}, r1, 0);
        item = sched[++it];
        gturn(SECOND, false, mma128(NO, Y, true), nothing);
        test_ab(pa, pb);
        fence_regs(Y);
        done = 0;
      } else {
        float(&O)[64] = Y;
        float S[64];
        float l0 = 0.f, l1 = 0.f;
        float zlim;
        asm volatile("" : "+f"(l0), "+f"(l1));
        const uint32_t sel = threadIdx.x & 127;
        const int b = 3 * g + 1 - rho;
        first_two(ONCE, ONCE, NO, S);
#pragma unroll 1
        for (int n = 0; n < 5; n++) gturn(ONCE, false, mma128(NO, S, true), nothing);
#pragma unroll
        for (int i = 0; i < 64; i++) O[i] = 0.f;
        fence_regs(O);
        gturn(FIRST, false, mma128(NO, S, true), nothing);
        fence_regs(S);
        {
          const uint32_t lane = threadIdx.x & 31, dst = abase + (pa & 1) * A_STAGE + wq * 2048 + (lane ^ (lane >> 3)) * 16;
#pragma unroll
          for (int h = 0; h < 2; h++) {
            uint32_t r[16];
            pack(r, S, h, 1.f, 1.f);
#pragma unroll
            for (int i = 0; i < 4; i++) {
              sts128(dst + h * 8192 + (i >> 1) * 512 + (i & 1) * 1024, r[4 * i], r[4 * i + 1], r[4 * i + 2], r[4 * i + 3]);
              if (4 * h + i < 7) __nanosleep(30);
            }
          }
          asm volatile("fence.proxy.async.shared::cta;" ::: "memory");
        }
        enum { MID, LAST, HALF };
        auto round = [&](auto mode_c) {
          constexpr int MODE = decltype(mode_c)::value;
          constexpr bool INIT = MODE == LAST;
          constexpr int NI = MODE == HALF ? 8 : 16;
          const uint32_t shared = MODE == HALF ? rho == 0 : 0;
          const uint32_t tv = pb + 1 - shared;
          {
            const uint32_t dq = adesc + (pa & 1) * (A_STAGE >> 4);
            const uint32_t dk = bdesc + (pb & 3) * 2048 + (1u << 16);
            if (INIT) {
              const int lane = threadIdx.x & 31;
              const int row = (wq * 16 + (lane >> 2) - 2 * (lane & 3) + 11) << 23;
              const int r0 = row ^ (__float_as_uint(l0) & p.zero & (MODE + 16)), r1 = row ^ (__float_as_uint(l1) & p.zero & (MODE + 16));
#pragma unroll
              for (int i = 0; i < 4 * NI; i++) {
                const int c = i - 4 * (NI - 8);
                S[i] = c < 0 ? 0.f : __int_as_float((c & 2 ? r1 : r0) + ((4 * (c & 2) - 2 * (c & ~3) - (c & 1) - 11) << 23));
                asm volatile("" : "+f"(S[i])::"memory");
              }
            }
            if (!ready_b()) mbar_wait_u(bfull0 + 8 * (pb & 3), (pb >> 2) & 1);
            turn();
            wg_fence();
#pragma unroll
            for (int k = 0; k < 8; k++) {
              const uint32_t da = dq + (k >> 2) * 512 + (k & 2) * 16 + (k & 1) * 2, db = dk + (k >> 1) * 32 + (k & 1) * 2;
              if (MODE == HALF) wgmma_n64(S, da, db, k != 0 || INIT);
              else wgmma_n128<0>(S, da, HIQ, db, HI64, k != 0 || INIT);
            }
            wg_commit();
            pass();
          }
          test_b(bfull0 + 8 * (tv & 3), (tv >> 2) & 1);
          if (!ready_b()) mbar_wait_u(bfull0 + 8 * (tv & 3), (tv >> 2) & 1);
          wg_wait<0>();
#pragma unroll
          for (int i = 0; i < 4 * NI; i++) asm volatile("" : "+f"(S[i])::"memory");
          mbar_arrive_if0(bempty0 + 8 * (pb & 3), sel | shared);
          if (MODE >= LAST) mbar_arrive_cta_if0(aempty + 8 * (pa & 1), wq & 1, (sel & 31) | (wq >> 1));
          uint32_t P[2 * NI];
          if (MODE >= LAST && !INIT) {
            const int lane = threadIdx.x & 31;
            const int row = wq * 16 + (lane >> 2) - 2 * (lane & 3);
#pragma unroll
            for (int i = 0; i < 8; i++) {
#pragma unroll
              for (int e = 0; e < 2; e++) {
                if (8 * i + e > row) S[4 * (NI - 8 + i) + e] = -INFINITY;
                if (8 * i + e > row + 8) S[4 * (NI - 8 + i) + 2 + e] = -INFINITY;
              }
            }
          }
          float s0 = 0.f, s1 = 0.f, t0 = 0.f, t1 = 0.f;
#pragma unroll
          for (int i = 0; i < NI; i++) {
#pragma unroll
            for (int e = 0; e < 4; e++) S[4 * i + e] = ex2(S[4 * i + e]);
            s0 += S[4 * i];
            t0 += S[4 * i + 1];
            s1 += S[4 * i + 2];
            t1 += S[4 * i + 3];
            P[2 * i] = pack_bf16(S[4 * i], S[4 * i + 1]);
            P[2 * i + 1] = pack_bf16(S[4 * i + 2], S[4 * i + 3]);
          }
          l0 += s0 + t0;
          l1 += s1 + t1;
          uint32_t dep = (__float_as_uint(l0) ^ __float_as_uint(l1)) ^ P[2 * NI - 1];
          fence_regs(O);
#pragma unroll
          for (int i = 0; i < 2 * NI; i++) asm volatile("" : "+r"(P[i])::"memory");
          const uint32_t dv = (bdesc + (tv & 3) * 2048 + shared * 1024) | (32u << 16);
          turn(dep & p.zero);
          wg_fence();
#pragma unroll
          for (int k = 0; k < NI / 2; k++)
            wgmma_n128_rs_tb(O, P[4 * k], P[4 * k + 1], P[4 * k + 2], P[4 * k + 3], dv + k * 256, 1);
          wg_commit();
          pass();
          pb = tv + 1;
          if (MODE >= LAST) {
            const int nskip = 1 + (g & 1);
            if (rho + nskip >= 3) pb += 3 - nskip;
            pa++;
          } else {
            test_b(bfull0 + 8 * (pb & 3), (pb >> 2) & 1);
          }
          if (MODE >= LAST) {
            l0 += __shfl_xor_sync(0xffffffffu, l0, 1);
            l1 += __shfl_xor_sync(0xffffffffu, l1, 1);
            l0 += __shfl_xor_sync(0xffffffffu, l0, 2);
            l1 += __shfl_xor_sync(0xffffffffu, l1, 2);
            sc0 = rcp(l0);
            sc1 = rcp(l1);
            zlim = l0 <= KB_LIMIT && l0 >= KB_LOW && l1 <= KB_LIMIT && l1 >= KB_LOW ? 3e38f : -1.f;
          }
          wg_wait<0>();
          fence_regs(O);
          mbar_arrive_if0(bempty0 + 8 * (tv & 3), sel);
        };
#pragma unroll 1
        for (int n = b >> 1; n; n--) round(std::integral_constant<int, MID>{});
        item = sched[++it];
        if (b & 1) round(std::integral_constant<int, LAST>{});
        else round(std::integral_constant<int, HALF>{});
        test_ab(pa, pb);
        float z[4] = {0.f, 0.f, 0.f, 0.f};
#pragma unroll
        for (int i = 0; i < 32; i++) z[i & 3] = fmaf(O[2 * i], O[2 * i + 1], z[i & 3]);
        const bool bad = !(fabsf(z[0]) + fabsf(z[1]) + fabsf(z[2]) + fabsf(z[3]) <= zlim);
        const int lane = threadIdx.x & 31;
        pdst = p.scr + (PL_CTX + 2 * j + rank) * PLANE + (b * 64 + wq * 16) * 16 + (lane ^ (lane >> 3));
        done = ((const uint8_t*)sched)[KEEP + it - 1] >> 6;
        if (__any_sync(0xffffffffu, bad)) {
          attn_fallback(p.scr + (PL_CTX + 2 * j + rank) * PLANE, p.scr + (PL_KV + j * 4 + rank) * PLANE, p.x,
                        p.wq + (2 * j + rank) * 128, b * 64 + wq * 16, threadIdx.x & 31);
          publish(it - 1);
          no_pending();
          test_ab(pa, pb);
        }
      }
    }

    bool relay = true;
    if (idle()) {
      flush();
      skip_item(2);
    } else {
      const uint32_t kind = item & 7;
      const int g = (item >> 3) & 15, j = (item >> 7) & 15;
      const int row = item_row(kind, g, rank_of(item) + (g == 0)) + wq * 16;
      auto epilogue = [&](float (&acc)[64], int cb, bool pace) {
        const int lane = threadIdx.x & 31;
        const uint32_t stg = abase + ((pa - 1) & 1) * A_STAGE + wq * 4096;
        const int srow = lane & 15;
#pragma unroll
        for (int jj = 0; jj < 8; jj++) {
          const uint32_t r0 = pack_bf16(acc[8 * jj + 0], acc[8 * jj + 1]);
          const uint32_t r1 = pack_bf16(acc[8 * jj + 2], acc[8 * jj + 3]);
          const uint32_t r2 = pack_bf16(acc[8 * jj + 4], acc[8 * jj + 5]);
          const uint32_t r3 = pack_bf16(acc[8 * jj + 6], acc[8 * jj + 7]);
          const int chunk = (2 * jj + (lane >> 4)) & 7;
          const uint32_t addr = stg + (jj >> 2) * 2048 + srow * 128 + ((chunk ^ (srow & 7)) << 4);
          asm volatile("stmatrix.sync.aligned.m8n8.x4.shared.b16 [%0], {%1,%2,%3,%4};" ::"r"(addr), "r"(r0), "r"(r1), "r"(r2), "r"(r3)
                       : "memory");
          if (jj < 7 && pace) __nanosleep(30);
        }
        asm volatile("fence.proxy.async.shared::cta;" ::: "memory");
        __syncwarp();
        if (lane == 0) {
          const int col = cb * 128 + (kind == K_OA ? (row >> 10) * 2048 : 1024);
          const int r = kind == K_OA ? row & 1023 : row;
          tma_store_2d(&p.mapO[kind - K_OA], stg, col, r);
          tma_store_2d(&p.mapO[kind - K_OA], stg + 2048, col + 64, r);
          asm volatile("cp.async.bulk.commit_group;" ::: "memory");
        }
      };
      float X[64];
      relay = g == 0;
      const int last = g && rank_of(item) == 1 ? back : fwd;
      if (item_narrow(item)) {
        int n = item_nk(item);
        first_two(ONCE, ONCE, YES, X);
#pragma unroll 1
        while (--n > 1) {
          if (n == 2) next = last;
          gturn(ONCE, false, mma128(YES, X, true), nothing);
        }
        fence_regs(X);
        epilogue(X, 2 * j + rank - 8, rank_of(item) == 0);
      } else {
        all_but_last_two(YES, X);
        gturn(Y0, false, mma128(YES, Y, true), nothing);
        epilogue(X, 4 * j + 2 * rank, true);
        next = last;
        gturn(SECOND, false, mma128(YES, Y, true), nothing);
        fence_regs(Y);
        epilogue(Y, 4 * j + 2 * rank + 1, rank_of(item) == 0);
      }
      item = sched[++it];
    }
    const int rho = rank_of(item);
    uint32_t id;
    asm volatile("mov.u32 %0, %%tid.x;" : "=r"(id));
    if (rho == 0 && relay) {
      bar_sync(id >> 7, NTURN);
      bar_arrive(id < 256 ? 3 : (id >> 7) - 1, NTURN);
    }
    if (rho == 1) bar_sync(id >> 7, NTURN);
    asm volatile("cp.async.bulk.wait_group.read 0;" ::: "memory");
  }
}

typedef CUresult (*EncodeFn)(CUtensorMap*, CUtensorMapDataType, cuuint32_t, void*, const cuuint64_t*, const cuuint64_t*,
                             const cuuint32_t*, const cuuint32_t*, CUtensorMapInterleave, CUtensorMapSwizzle, CUtensorMapL2promotion,
                             CUtensorMapFloatOOBfill);

void make_map(EncodeFn enc, CUtensorMap* m, const void* ptr, uint64_t d0, uint64_t d1, uint64_t d2, uint64_t s1, uint64_t s2, uint32_t b0,
              uint32_t b1, uint32_t b2) {
  cuuint64_t gd[3] = {d0, d1, d2}, gs[2] = {s1, s2};
  cuuint32_t bd[3] = {b0, b1, b2}, es[3] = {1, 1, 1};
  enc(m, CU_TENSOR_MAP_DATA_TYPE_BFLOAT16, d2 ? 3 : 2, const_cast<void*>(ptr), gd, gs, bd, es, CU_TENSOR_MAP_INTERLEAVE_NONE,
      CU_TENSOR_MAP_SWIZZLE_128B, CU_TENSOR_MAP_L2_PROMOTION_L2_128B, CU_TENSOR_MAP_FLOAT_OOB_FILL_NONE);
}

struct HostState {
  Params p;
  const void* in[9];
  void* out;
  bool valid;
};
HostState g_hs;

const uint16_t h_sched[NCLUSTERS * MAXITEMS] = {
    690, 698, 706, 714, 722, 1425, 1561, 1977, 1601, 829, 7, 7, 7, 7, 7, 7,
    265, 851, 969, 1315, 1833, 1843, 60, 7, 7, 7, 7, 7, 7, 7, 7, 7,
    705, 643, 521, 515, 979, 1451, 957, 7, 7, 7, 7, 7, 7, 7, 7, 7,
    386, 394, 402, 410, 418, 426, 1825, 1595, 148, 7, 7, 7, 7, 7, 7, 7,
    337, 795, 897, 937, 1083, 1353, 1987, 188, 7, 7, 7, 7, 7, 7, 7, 7,
    329, 187, 1099, 1699, 661, 7, 7, 7, 7, 7, 7, 7, 7, 7, 7, 7,
    178, 186, 194, 202, 210, 1337, 1689, 1473, 1873, 701, 7, 7, 7, 7, 7, 7,
    433, 153, 331, 1305, 1163, 1457, 1707, 517, 7, 7, 7, 7, 7, 7, 7, 7,
    281, 779, 529, 523, 1059, 1307, 1555, 813, 7, 7, 7, 7, 7, 7, 7, 7,
    833, 179, 929, 1067, 1809, 1995, 52, 7, 7, 7, 7, 7, 7, 7, 7, 7,
    665, 163, 571, 57, 1945, 1569, 1419, 909, 7, 7, 7, 7, 7, 7, 7, 7,
    385, 139, 275, 963, 1545, 1739, 156, 7, 7, 7, 7, 7, 7, 7, 7, 7,
    129, 145, 307, 1075, 1209, 1875, 4, 7, 7, 7, 7, 7, 7, 7, 7, 7,
    441, 211, 1289, 1347, 1745, 717, 7, 7, 7, 7, 7, 7, 7, 7, 7, 7,
    193, 411, 595, 1211, 693, 7, 7, 7, 7, 7, 7, 7, 7, 7, 7, 7,
    393, 161, 315, 1281, 11, 1801, 1747, 84, 7, 7, 7, 7, 7, 7, 7, 7,
    689, 683, 561, 1051, 1177, 1955, 1617, 845, 7, 7, 7, 7, 7, 7, 7, 7,
    793, 835, 577, 19, 1417, 1491, 36, 7, 7, 7, 7, 7, 7, 7, 7, 7,
    673, 811, 907, 1065, 49, 1329, 1971, 981, 7, 7, 7, 7, 7, 7, 7, 7,
    681, 387, 513, 547, 81, 35, 1225, 1579, 773, 7, 7, 7, 7, 7, 7, 7,
    2, 10, 18, 26, 34, 42, 1961, 1723, 196, 7, 7, 7, 7, 7, 7, 7,
    417, 171, 1033, 1043, 1313, 1195, 1729, 653, 7, 7, 7, 7, 7, 7, 7, 7,
    201, 403, 537, 971, 1673, 1611, 76, 7, 7, 7, 7, 7, 7, 7, 7, 7,
    185, 169, 291, 569, 51, 1593, 1481, 1609, 949, 7, 7, 7, 7, 7, 7, 7,
    769, 435, 923, 1105, 1227, 853, 7, 7, 7, 7, 7, 7, 7, 7, 7, 7,
    817, 155, 587, 1921, 1483, 645, 7, 7, 7, 7, 7, 7, 7, 7, 7, 7,
    649, 147, 531, 1107, 1459, 901, 7, 7, 7, 7, 7, 7, 7, 7, 7, 7,
    642, 650, 658, 666, 674, 682, 1795, 1979, 204, 7, 7, 7, 7, 7, 7, 7,
    258, 266, 274, 282, 290, 298, 1539, 1467, 164, 7, 7, 7, 7, 7, 7, 7,
    305, 203, 961, 1331, 1867, 132, 7, 7, 7, 7, 7, 7, 7, 7, 7, 7,
    130, 138, 146, 154, 162, 170, 1697, 1851, 212, 7, 7, 7, 7, 7, 7, 7,
    514, 522, 530, 538, 546, 554, 1411, 1427, 797, 7, 7, 7, 7, 7, 7, 7,
    465, 691, 947, 1929, 1817, 1731, 20, 7, 7, 7, 7, 7, 7, 7, 7, 7,
    457, 659, 563, 3, 1321, 1441, 1443, 589, 7, 7, 7, 7, 7, 7, 7, 7,
    257, 699, 915, 1097, 1355, 941, 7, 7, 7, 7, 7, 7, 7, 7, 7, 7,
    770, 778, 786, 794, 802, 810, 1923, 1683, 549, 7, 7, 7, 7, 7, 7, 7,
    713, 451, 1057, 977, 1363, 917, 7, 7, 7, 7, 7, 7, 7, 7, 7, 7,
    946, 954, 962, 970, 978, 1283, 1217, 1705, 1865, 677, 7, 7, 7, 7, 7, 7,
    306, 314, 322, 330, 338, 1665, 1819, 1993, 805, 7, 7, 7, 7, 7, 7, 7,
    273, 675, 913, 1091, 1681, 1475, 44, 7, 7, 7, 7, 7, 7, 7, 7, 7,
    137, 723, 67, 1577, 1857, 565, 7, 7, 7, 7, 7, 7, 7, 7, 7, 7,
    297, 443, 1035, 1089, 65, 1345, 1827, 933, 7, 7, 7, 7, 7, 7, 7, 7,
    209, 177, 339, 1169, 1219, 525, 7, 7, 7, 7, 7, 7, 7, 7, 7, 7,
    825, 467, 75, 1803, 821, 7, 7, 7, 7, 7, 7, 7, 7, 7, 7, 7,
    849, 803, 539, 1081, 73, 1489, 1835, 725, 7, 7, 7, 7, 7, 7, 7, 7,
    801, 195, 9, 83, 2001, 789, 7, 7, 7, 7, 7, 7, 7, 7, 7, 7,
    697, 667, 905, 955, 1201, 1619, 12, 7, 7, 7, 7, 7, 7, 7, 7, 7,
    898, 906, 914, 922, 930, 938, 1667, 1811, 573, 7, 7, 7, 7, 7, 7, 7,
    449, 787, 267, 931, 1179, 1465, 1547, 965, 7, 7, 7, 7, 7, 7, 7, 7,
    50, 58, 66, 74, 82, 1409, 1433, 1947, 597, 7, 7, 7, 7, 7, 7, 7,
    777, 459, 585, 1323, 1969, 1587, 172, 7, 7, 7, 7, 7, 7, 7, 7, 7,
    289, 819, 939, 1185, 1931, 1841, 1849, 709, 7, 7, 7, 7, 7, 7, 7, 7,
    401, 395, 545, 555, 1161, 1203, 1985, 781, 7, 7, 7, 7, 7, 7, 7, 7,
    313, 715, 1073, 1153, 1291, 1585, 1603, 28, 7, 7, 7, 7, 7, 7, 7, 7,
    409, 827, 945, 25, 1299, 1553, 1691, 541, 7, 7, 7, 7, 7, 7, 7, 7,
    785, 707, 953, 33, 1235, 973, 7, 7, 7, 7, 7, 7, 7, 7, 7, 7,
    809, 131, 283, 1041, 1027, 41, 1187, 1713, 1737, 533, 7, 7, 7, 7, 7, 7,
    721, 419, 579, 1193, 1953, 1859, 140, 7, 7, 7, 7, 7, 7, 7, 7, 7,
    841, 771, 323, 1297, 1171, 1233, 1939, 669, 7, 7, 7, 7, 7, 7, 7, 7,
    641, 843, 17, 43, 1571, 837, 7, 7, 7, 7, 7, 7, 7, 7, 7, 7,
    321, 299, 921, 1, 27, 1937, 2003, 68, 7, 7, 7, 7, 7, 7, 7, 7,
    562, 570, 578, 586, 594, 1537, 1361, 1435, 581, 7, 7, 7, 7, 7, 7, 7,
    434, 442, 450, 458, 466, 1155, 1963, 925, 7, 7, 7, 7, 7, 7, 7, 7,
    818, 826, 834, 842, 850, 1793, 1449, 1563, 557, 7, 7, 7, 7, 7, 7, 7,
    425, 427, 1025, 1049, 59, 1721, 1715, 180, 7, 7, 7, 7, 7, 7, 7, 7,
    657, 651, 259, 553, 899, 593, 1339, 1675, 685, 7, 7, 7, 7, 7, 7, 7,
};

void setup(void* const* d_in, void* d_out) {
  void* fn = nullptr;
  cudaDriverEntryPointQueryResult qr;
  cudaGetDriverEntryPoint("cuTensorMapEncodeTiled", &fn, cudaEnableDefault, &qr);
  EncodeFn enc = (EncodeFn)fn;
  void *scr, *carry, *flags;
  cudaGetSymbolAddress(&scr, g_scr);
  cudaGetSymbolAddress(&carry, g_carry);
  cudaGetSymbolAddress(&flags, g_flags);
  Params& p = g_hs.p;
  make_map(enc, &p.mapA[2], d_in[3], 64, 2048, 16, 2048, 128, 64, 64, 1);
  make_map(enc, &p.mapA[0], d_in[4], 64, 2048, 8, 1024, 128, 64, 64, 1);
  make_map(enc, &p.mapA[1], d_in[0], 64, 1024, 32, 4096, 128, 64, 64, 1);
  make_map(enc, &p.mapB[3], d_in[5], 64, 1024, 64, 8192, 128, 64, 128, 2);
  make_map(enc, &p.mapB[1], d_in[6], 64, 512, 64, 8192, 128, 64, 128, 2);
  make_map(enc, &p.mapB[2], d_in[1], 1024, 1024, 3, 6144, 2048, 64, 64, 3);
  make_map(enc, &p.mapB[0], d_in[7], 64, 512, 64, 8192, 128, 64, 128, 2);
  make_map(enc, &p.mapB[5], d_in[8], 64, 4096, 16, 2048, 128, 64, 128, 2);
  {
    cuuint64_t gd[5] = {1024, 2, 4, 4, 32}, gs[4] = {2048, 8 * 2048, 2 * 2048, 32 * 2048};
    cuuint32_t bd[5] = {64, 2, 4, 4, 4}, es[5] = {1, 1, 1, 1, 1};
    enc(&p.mapB[4], CU_TENSOR_MAP_DATA_TYPE_BFLOAT16, 5, d_in[2], gd, gs, bd, es, CU_TENSOR_MAP_INTERLEAVE_NONE, CU_TENSOR_MAP_SWIZZLE_128B,
        CU_TENSOR_MAP_L2_PROMOTION_L2_128B, CU_TENSOR_MAP_FLOAT_OOB_FILL_NONE);
  }
  make_map(enc, &p.mapO[0], d_out, 4096, 1024, 0, 8192, 0, 64, 16, 1);
  make_map(enc, &p.mapO[1], d_out, 2048, 2048, 0, 4096, 0, 64, 16, 1);
  p.scr = (uint4*)scr;
  p.carry = (uint4*)carry;
  p.flags = (uint32_t*)flags;
  p.x = (const uint32_t*)d_in[3];
  p.wq = (const uint16_t*)d_in[5];
  p.zero = 0;
  for (int c = 0; c < NCLUSTERS; c++) {
    int rot = 0;
    for (int i = c * MAXITEMS; i < (c + 1) * MAXITEMS; i++) {
      const int kind = h_sched[i] & 7, g = (h_sched[i] >> 3) & 15;
      p.sched[i] = (uint16_t)(h_sched[i] | rot << 11);
      rot = (rot + (kind == K_T ? 1 + (g & 1) : g == 0)) % 3;
    }
  }
  int start[NCLUSTERS * MAXITEMS];
  for (int i = 0, t = 0; i < NCLUSTERS * MAXITEMS; i++) {
    const int kind = h_sched[i] & 7, g = (h_sched[i] >> 3) & 15;
    if (i % MAXITEMS == 0) t = 0;
    start[i] = t;
    t += (g ? 3 : 2) * (kind == K_L ? 13 : 8) + (kind == K_T ? 9 * g + 6 : 0);
  }
  for (int i = 0; i < NCLUSTERS * MAXITEMS; i++) {
    int keep = 0;
    for (int k = 0; k < NCLUSTERS * MAXITEMS; k++)
      if (!((h_sched[i] ^ h_sched[k]) & 0x787) && start[k] > start[i] + 3) {
        const int n = 32 | ((3 * ((h_sched[k] >> 3) & 15) + 3) >> 1);
        if (n > keep) keep = n;
      }
    if (start[i] + 9 * ((h_sched[i] >> 3) & 15) < 200) keep |= 128;
    if (i % MAXITEMS < 10) ((uint8_t*)(p.sched + i - i % MAXITEMS))[KEEP + i % MAXITEMS] = (uint8_t)keep;
  }
  cudaFuncSetAttribute(fused_kernel, cudaFuncAttributeMaxDynamicSharedMemorySize, SM_TOTAL);
  for (int i = 0; i < 9; i++) g_hs.in[i] = d_in[i];
  g_hs.out = d_out;
  g_hs.valid = true;
}

}

extern "C" void kernel_launch(void* const* d_in, const int* in_sizes, int n_in, void* d_out, int out_size) {
  (void)in_sizes;
  (void)n_in;
  (void)out_size;
  bool ok = g_hs.valid && g_hs.out == d_out;
  for (int i = 0; ok && i < 9; i++) ok = g_hs.in[i] == d_in[i];
  if (!ok) setup(d_in, d_out);
  fused_kernel<<<NCLUSTERS * 2, 512, SM_TOTAL, cudaStreamPerThread>>>(g_hs.p);
}
```

```cpp
#include <cuda_runtime.h>
#include <cuda_bf16.h>
#include <cuda.h>
#include <stdint.h>
#include <type_traits>

namespace {

typedef __nv_bfloat16 bf16;

__device__ __forceinline__ uint32_t smem_u32(const void* p) { return (uint32_t)__cvta_generic_to_shared(p); }
__device__ __forceinline__ void mbar_init(uint32_t bar, uint32_t cnt) {
  asm volatile("mbarrier.init.shared::cta.b64 [%0], %1;" ::"r"(bar), "r"(cnt) : "memory");
}
__device__ __forceinline__ void mbar_expect_tx(uint32_t bar, uint32_t bytes) {
  asm volatile("mbarrier.arrive.expect_tx.shared::cta.b64 _, [%0], %1;" ::"r"(bar), "r"(bytes) : "memory");
}
__device__ __forceinline__ void mbar_arrive_n(uint32_t bar, uint32_t n) {
  asm volatile("mbarrier.arrive.shared::cta.b64 _, [%0], %1;" ::"r"(bar), "r"(n) : "memory");
}
__device__ __forceinline__ void mbar_arrive_if0(uint32_t bar, uint32_t sel) {
  asm volatile("{\n.reg .pred p;\nsetp.eq.u32 p, %1, 0;\n@p mbarrier.arrive.shared::cta.b64 _, [%0];\n}" ::"r"(bar), "r"(sel) : "memory");
}
__device__ __forceinline__ void mbar_arrive_cta_if0(uint32_t bar, uint32_t cta, uint32_t sel) {
  asm volatile("{\n.reg .pred p;\n.reg .b32 ra;\nsetp.eq.u32 p, %2, 0;\nmapa.shared::cluster.u32 ra, %0, %1;\n"
               "@p mbarrier.arrive.shared::cluster.b64 _, [ra];\n}" ::"r"(bar),
               "r"(cta), "r"(sel)
               : "memory");
}
__device__ __forceinline__ void mbar_wait(uint32_t bar, uint32_t parity) {
  uint32_t done;
  uint32_t it = 0;
#pragma unroll 1
  while (true) {
    asm volatile("{\n.reg .pred p;\nmbarrier.try_wait.parity.shared::cta.b64 p, [%1], %2, 1000;\nselp.u32 %0, 1, 0, p;\n}"
                 : "=r"(done)
                 : "r"(bar), "r"(parity)
                 : "memory");
    if (done) break;
    if (++it > (1u << 24)) __trap();
  }
}
__device__ __forceinline__ void mbar_wait_u(uint32_t bar, uint32_t parity) {
  uint32_t it = 0;
#pragma unroll 1
  while (true) {
    uint32_t done;
    asm volatile("{\n.reg .pred p, q;\nmbarrier.try_wait.parity.shared::cta.b64 p, [%1], %2;\nvote.sync.all.pred q, p, 0xffffffff;\nselp.u32 %0, 1, 0, q;\n}"
                 : "=r"(done)
                 : "r"(bar), "r"(parity)
                 : "memory");
    if (done) break;
    if (++it > (1u << 20)) break;
  }
}
#define DECLARE_READY() asm volatile(".reg .pred RDYA, RDYB;")
__device__ __forceinline__ void test_a(uint32_t bar, uint32_t parity) {
  asm volatile("mbarrier.test_wait.parity.shared::cta.b64 RDYA, [%0], %1;" ::"r"(bar), "r"(parity) : "memory");
}
__device__ __forceinline__ void test_b(uint32_t bar, uint32_t parity) {
  asm volatile("mbarrier.test_wait.parity.shared::cta.b64 RDYB, [%0], %1;" ::"r"(bar), "r"(parity) : "memory");
}
__device__ __forceinline__ uint32_t ready_b(uint32_t dep = 0) {
  uint32_t r;
  asm volatile("{\n.reg .pred q;\nsetp.eq.and.u32 q, %1, 0, RDYB;\nvote.sync.all.pred q, q, 0xffffffff;\nselp.u32 %0, 1, 0, q;\n}" : "=r"(r) : "r"(dep) : "memory");
  return r;
}
__device__ __forceinline__ uint32_t ready_ab() {
  uint32_t r;
  asm volatile("{\n.reg .pred q;\nand.pred q, RDYA, RDYB;\nvote.sync.all.pred q, q, 0xffffffff;\nselp.u32 %0, 1, 0, q;\n}" : "=r"(r)::"memory");
  return r;
}
__device__ __forceinline__ void tma_load_3d(uint32_t dst, const CUtensorMap* m, uint32_t bar, int c0, int c1, int c2) {
  asm volatile("cp.async.bulk.tensor.3d.shared::cluster.global.mbarrier::complete_tx::bytes [%0], [%1, {%3, %4, %5}], [%2];" ::"r"(dst),
               "l"(m), "r"(bar), "r"(c0), "r"(c1), "r"(c2)
               : "memory");
}
constexpr uint32_t L2_NORMAL = 0x10000000u, L2_FIRST = 0x12F00000u;
__device__ __forceinline__ void tma_load_3d(uint32_t dst, const CUtensorMap* m, uint32_t bar, int c0, int c1, int c2, uint32_t pol) {
  asm volatile("{\n.reg .b64 h;\nmov.b64 h, {0, %6};\n"
               "cp.async.bulk.tensor.3d.shared::cluster.global.mbarrier::complete_tx::bytes.L2::cache_hint [%0], [%1, {%3, %4, %5}], [%2], h;\n}" ::"r"(dst),
               "l"(m), "r"(bar), "r"(c0), "r"(c1), "r"(c2), "r"(pol)
               : "memory");
}
__device__ __forceinline__ void bulk_load(uint32_t dst, const void* src, uint32_t bytes, uint32_t bar, uint32_t pol) {
  asm volatile("{\n.reg .b64 h;\nmov.b64 h, {0, %4};\n"
               "cp.async.bulk.shared::cluster.global.mbarrier::complete_tx::bytes.L2::cache_hint [%0], [%1], %2, [%3], h;\n}" ::"r"(dst),
               "l"(src), "r"(bytes), "r"(bar), "r"(pol)
               : "memory");
}
__device__ __forceinline__ void tma_load_3d_mc(uint32_t dst, const CUtensorMap* m, uint32_t bar, int c0, int c1, int c2, uint16_t mask) {
  asm volatile(
      "cp.async.bulk.tensor.3d.shared::cluster.global.mbarrier::complete_tx::bytes.multicast::cluster [%0], [%1, {%3, %4, %5}], [%2], %6;" ::"r"(dst),
      "l"(m), "r"(bar), "r"(c0), "r"(c1), "r"(c2), "h"(mask)
      : "memory");
}
__device__ __forceinline__ void tma_load_5d(uint32_t dst, const CUtensorMap* m, uint32_t bar, int c0, int c4) {
  asm volatile("cp.async.bulk.tensor.5d.shared::cluster.global.mbarrier::complete_tx::bytes [%0], [%1, {%3, 0, 0, 0, %4}], [%2];" ::"r"(dst),
               "l"(m), "r"(bar), "r"(c0), "r"(c4)
               : "memory");
}
__device__ __forceinline__ void bulk_load(uint32_t dst, const void* src, uint32_t bytes, uint32_t bar) {
  asm volatile("cp.async.bulk.shared::cluster.global.mbarrier::complete_tx::bytes [%0], [%1], %2, [%3];" ::"r"(dst), "l"(src), "r"(bytes), "r"(bar)
               : "memory");
}
__device__ __forceinline__ void bulk_load_mc(uint32_t dst, const void* src, uint32_t bytes, uint32_t bar, uint16_t mask) {
  asm volatile("cp.async.bulk.shared::cluster.global.mbarrier::complete_tx::bytes.multicast::cluster [%0], [%1], %2, [%3], %4;" ::"r"(dst),
               "l"(src), "r"(bytes), "r"(bar), "h"(mask)
               : "memory");
}
__device__ __forceinline__ void prefetch_l2(const void* src, uint32_t bytes) {
  asm volatile("cp.async.bulk.prefetch.L2.global [%0], %1;" ::"l"(src), "r"(bytes) : "memory");
}
__device__ __forceinline__ void tma_store_2d(const CUtensorMap* m, uint32_t src, int c0, int c1) {
  asm volatile("cp.async.bulk.tensor.2d.global.shared::cta.bulk_group [%0, {%2, %3}], [%1];" ::"l"(m), "r"(src), "r"(c0), "r"(c1)
               : "memory");
}
__device__ __forceinline__ void prefetch_tmap(const CUtensorMap* m) { asm volatile("prefetch.tensormap [%0];" ::"l"(m) : "memory"); }
__device__ __forceinline__ uint32_t pack_bf16(float lo, float hi) {
  uint32_t r;
  asm("cvt.rn.bf16x2.f32 %0, %1, %2;" : "=r"(r) : "f"(hi), "f"(lo));
  return r;
}
__device__ __forceinline__ float ex2(float x) {
  float y;
  asm("ex2.approx.ftz.f32 %0, %1;" : "=f"(y) : "f"(x));
  return y;
}
__device__ __forceinline__ float rcp(float x) {
  float y;
  asm("rcp.approx.ftz.f32 %0, %1;" : "=f"(y) : "f"(x));
  return y;
}
__device__ __forceinline__ void wg_fence() { asm volatile("wgmma.fence.sync.aligned;" ::: "memory"); }
__device__ __forceinline__ void wg_commit() { asm volatile("wgmma.commit_group.sync.aligned;" ::: "memory"); }
template <int N>
__device__ __forceinline__ void wg_wait() {
  asm volatile("wgmma.wait_group.sync.aligned %0;" ::"n"(N) : "memory");
}
template <int N>
__device__ __forceinline__ void fence_regs(float (&d)[N]) {
#pragma unroll
  for (int i = 0; i < N; i++) asm volatile("" : "+f"(d[i])::"memory");
}
__device__ __forceinline__ uint32_t sched_fence() {
  uint32_t t;
  asm volatile("mov.u32 %0, %%clock;" : "=r"(t)::"memory");
  return t;
}
__device__ __forceinline__ void bar_sync(int id, int n) { asm volatile("bar.sync %0, %1;" ::"r"(id), "r"(n) : "memory"); }
__device__ __forceinline__ void bar_arrive_if(bool c, int id, int n) {
  asm volatile("{\n.reg .pred p;\nsetp.ne.u32 p, %2, 0;\n@p bar.arrive %0, %1;\n}" ::"r"(id), "r"(n), "r"((uint32_t)c) : "memory");
}
__device__ __forceinline__ void bar_arrive(int id, int n) { asm volatile("bar.arrive %0, %1;" ::"r"(id), "r"(n) : "memory"); }

#define R8(a, i) "+f"(a[i]), "+f"(a[i + 1]), "+f"(a[i + 2]), "+f"(a[i + 3]), "+f"(a[i + 4]), "+f"(a[i + 5]), "+f"(a[i + 6]), "+f"(a[i + 7])
#define OP32(d, o) R8(d, o), R8(d, o + 8), R8(d, o + 16), R8(d, o + 24)
#define L32A "%0,%1,%2,%3,%4,%5,%6,%7,%8,%9,%10,%11,%12,%13,%14,%15,%16,%17,%18,%19,%20,%21,%22,%23,%24,%25,%26,%27,%28,%29,%30,%31"
#define L32B "%32,%33,%34,%35,%36,%37,%38,%39,%40,%41,%42,%43,%44,%45,%46,%47,%48,%49,%50,%51,%52,%53,%54,%55,%56,%57,%58,%59,%60,%61,%62,%63"
#define L32C "%64,%65,%66,%67,%68,%69,%70,%71,%72,%73,%74,%75,%76,%77,%78,%79,%80,%81,%82,%83,%84,%85,%86,%87,%88,%89,%90,%91,%92,%93,%94,%95"
#define WG_PRE(a, b, s, ha, hb) "{\n.reg .pred p;\n.reg .b64 da, db;\nmov.b64 da, {" a ", " ha "};\nmov.b64 db, {" b ", " hb "};\nsetp.ne.b32 p, " s ", 0;\n"

constexpr uint32_t HI128 = 0x40000040;
constexpr uint32_t HI64 = 0x80000080;
constexpr uint32_t HIQ = 0x80000040;
template <int TB>
__device__ __forceinline__ void wgmma_n128(float (&d)[64], uint32_t da, uint32_t ha, uint32_t db, uint32_t hb, int scale_d) {
  asm volatile(WG_PRE("%64", "%65", "%66", "%67", "%68") "wgmma.mma_async.sync.aligned.m64n128k16.f32.bf16.bf16 {" L32A "," L32B "}, da, db, p, 1, 1, 0, %69;\n}\n"
               : OP32(d, 0), OP32(d, 32)
               : "r"(da), "r"(db), "r"(scale_d), "r"(ha), "r"(hb), "n"(TB));
}
__device__ __forceinline__ void wgmma_n192_tb(float (&d)[96], uint32_t da, uint32_t db, int scale_d) {
  asm volatile(WG_PRE("%96", "%97", "%98", "%99", "%99") "wgmma.mma_async.sync.aligned.m64n192k16.f32.bf16.bf16 {" L32A "," L32B "," L32C "}, da, db, p, 1, 1, 0, 1;\n}\n"
               : OP32(d, 0), OP32(d, 32), OP32(d, 64)
               : "r"(da), "r"(db), "r"(scale_d), "r"(HI128));
}
__device__ __forceinline__ void wgmma_n64(float (&d)[64], uint32_t da, uint32_t db, int scale_d) {
  asm volatile(WG_PRE("%32", "%33", "%34", "%35", "%36") "wgmma.mma_async.sync.aligned.m64n64k16.f32.bf16.bf16 {" L32A "}, da, db, p, 1, 1, 0, 0;\n}\n"
               : OP32(d, 0)
               : "r"(da), "r"(db), "r"(scale_d), "r"(HIQ), "r"(HI64));
}
__device__ __forceinline__ void wgmma_n128_rs_tb(float (&d)[64], uint32_t a0, uint32_t a1, uint32_t a2, uint32_t a3, uint32_t db, int scale_d) {
  asm volatile("{\n.reg .pred p;\n.reg .b64 db;\nmov.b64 db, {%68, %70};\nsetp.ne.b32 p, %69, 0;\n"
               "wgmma.mma_async.sync.aligned.m64n128k16.f32.bf16.bf16 {" L32A "," L32B "}, {%64,%65,%66,%67}, db, p, 1, 1, 1;\n}\n"
               : OP32(d, 0), OP32(d, 32)
               : "r"(a0), "r"(a1), "r"(a2), "r"(a3), "r"(db), "r"(scale_d), "r"(HI64));
}
__device__ __forceinline__ void mma_16816(float (&c)[4], uint32_t a0, uint32_t a1, uint32_t a2, uint32_t a3, uint32_t b0, uint32_t b1) {
  asm volatile("mma.sync.aligned.m16n8k16.row.col.f32.bf16.bf16.f32 {%0,%1,%2,%3}, {%4,%5,%6,%7}, {%8,%9}, {%0,%1,%2,%3};"
               : "+f"(c[0]), "+f"(c[1]), "+f"(c[2]), "+f"(c[3])
               : "r"(a0), "r"(a1), "r"(a2), "r"(a3), "r"(b0), "r"(b1));
}
__device__ __forceinline__ uint32_t movm_t(uint32_t x) {
  uint32_t y;
  asm volatile("movmatrix.sync.aligned.m8n8.trans.b16 %0, %1;" : "=r"(y) : "r"(x));
  return y;
}
__device__ __forceinline__ void sts128(uint32_t a, uint32_t x, uint32_t y, uint32_t z, uint32_t w) {
  asm volatile("st.shared.v4.u32 [%0], {%1,%2,%3,%4};" ::"r"(a), "r"(x), "r"(y), "r"(z), "r"(w) : "memory");
}
__device__ __forceinline__ void stsm4(uint32_t a, uint32_t x, uint32_t y, uint32_t z, uint32_t w) {
  asm volatile("stmatrix.sync.aligned.m8n8.x4.shared.b16 [%0], {%1,%2,%3,%4};" ::"r"(a), "r"(x), "r"(y), "r"(z), "r"(w) : "memory");
}
__device__ __forceinline__ void ldsm4_t(uint32_t a, uint32_t (&r)[4]) {
  asm volatile("ldmatrix.sync.aligned.m8n8.x4.trans.shared.b16 {%0,%1,%2,%3}, [%4];"
               : "=r"(r[0]), "=r"(r[1]), "=r"(r[2]), "=r"(r[3])
               : "r"(a)
               : "memory");
}
__device__ __forceinline__ void stg128_if0(uint4* a, uint32_t x, uint32_t y, uint32_t z, uint32_t w, uint32_t sel) {
  asm volatile("{\n.reg .pred p;\nsetp.eq.u32 p, %5, 0;\n@p st.global.cs.v4.u32 [%0], {%1,%2,%3,%4};\n}" ::"l"(a), "r"(x), "r"(y), "r"(z), "r"(w),
               "r"(sel)
               : "memory");
}
template <int OFS>
__device__ __forceinline__ void stg128_sel(uint4* a, uint32_t x, uint32_t y, uint32_t z, uint32_t w, uint32_t sel) {
  asm volatile("{\n.reg .pred p;\nsetp.eq.u32 p, %5, 0;\n@p st.global.v4.u32 [%0+%6], {%1,%2,%3,%4};\n"
               "setp.eq.u32 p, %5, 2;\n@p st.global.cs.v4.u32 [%0+%6], {%1,%2,%3,%4};\n}" ::"l"(a), "r"(x), "r"(y), "r"(z), "r"(w), "r"(sel), "n"(OFS * 16)
               : "memory");
}
__device__ __forceinline__ void lds128(uint32_t a, uint32_t& x, uint32_t& y, uint32_t& z, uint32_t& w) {
  asm volatile("ld.shared.v4.u32 {%0,%1,%2,%3}, [%4];" : "=r"(x), "=r"(y), "=r"(z), "=r"(w) : "r"(a) : "memory");
}

constexpr int PLANE = 2048 * 16;
constexpr int PL_CTX = 0, PL_KV = 32, PL_OA = PL_KV + 64, NPLANES = PL_OA + 8;
__device__ __align__(1024) uint4 g_scr[NPLANES * PLANE];
__device__ uint4 g_carry[16 * 128];
constexpr int F_CTX = 0, F_KV = 512, F_L = 1040, F_CAR = 1056, F_EPOCH = 1072, F_END = 1072 + 132;
__device__ uint32_t g_flags[F_END];

#define NTURN 256

enum { K_KV = 1, K_L = 2, K_T = 3, K_OA = 4, K_OB = 5, K_END = 7 };
constexpr int NCLUSTERS = 66, MAXITEMS = 16, KEEP = 22;
constexpr int A_STAGE = 16384, B_SLOT = 32768;
constexpr int SM_B = 6 * A_STAGE, SM_CARRY = SM_B + 4 * B_SLOT, SM_BAR = SM_CARRY + 2048, SM_TOTAL = SM_BAR + 512;

struct Params {
  CUtensorMap mapA[3];
  CUtensorMap mapB[6];
  CUtensorMap mapO[2];
  uint4* scr;
  uint4* carry;
  uint32_t* flags;
  const uint32_t* x;
  const uint16_t* wq;
  uint32_t zero;
  uint16_t sched[NCLUSTERS * MAXITEMS];
};

__device__ __forceinline__ bool item_narrow(uint32_t item) { return (item & 0x204) == 0x204 || (item & 7) == K_T; }
__device__ __forceinline__ int item_nk(uint32_t item) {
  const uint32_t kind = item & 7;
  return (kind == K_KV ? 8 : kind == K_OB ? 64 : 16) >> item_narrow(item);
}
__device__ __forceinline__ int item_row(uint32_t kind, int g, int pos) {
  if (kind == K_L || kind == K_OA) return g == 0 ? (pos - 1) * 1024 : 64 * (3 * g - 2 + pos + (g > 5));
  return 64 * (3 * g - 1 + pos);
}

__device__ __forceinline__ void wait_flag(const uint32_t* f, uint32_t target) {
  uint32_t it = 0;
#pragma unroll 1
  while (true) {
    uint32_t v;
    asm volatile("ld.acquire.gpu.global.u32 %0, [%1];" : "=r"(v) : "l"(f) : "memory");
    if ((int)(v - target) >= 0) break;
    __nanosleep(40);
    if (++it > (1u << 18)) break;
  }
  asm volatile("fence.proxy.async.global;" ::: "memory");
}
__device__ __forceinline__ uint32_t wait_bits(const uint32_t* f, uint32_t inv, uint32_t mask) {
  uint32_t it = 0, v;
#pragma unroll 1
  while (true) {
    asm volatile("ld.acquire.gpu.global.u32 %0, [%1];" : "=r"(v) : "l"(f) : "memory");
    v ^= inv;
    if (!(~v & mask)) break;
    __nanosleep(40);
    if (++it > (1u << 18)) break;
  }
  asm volatile("fence.proxy.async.global;" ::: "memory");
  return v;
}
__device__ __forceinline__ void red_add(uint32_t* f) { asm volatile("red.relaxed.gpu.global.add.u32 [%0], 1;" ::"l"(f) : "memory"); }
__device__ __forceinline__ void red_xor(uint32_t* f, uint32_t v) {
  asm volatile("red.relaxed.gpu.global.xor.b32 [%0], %1;" ::"l"(f), "r"(v) : "memory");
}

constexpr float QS = 0.08838834764831845f * 1.4426950408889634f;
__device__ __noinline__ void attn_fallback(uint4* q, const uint4* __restrict__ k, const uint32_t* __restrict__ x,
                                           const uint16_t* __restrict__ w, int row0, int lane) {
  const int g = lane >> 2, tq = lane & 3;
  q += row0 * 16;
  k += lane ^ (lane >> 3);
  const uint4* v = k + 2 * PLANE;
  float o[16][4];
#pragma unroll
  for (int i = 0; i < 16; i++) o[i][0] = o[i][1] = o[i][2] = o[i][3] = 0.f;
  x += (row0 + g) * 512 + tq;
  w += 2 * tq * 4096 + g;
#pragma unroll 1
  for (int k0 = 0; k0 < 64; k0++, x += 8, w += 16 * 4096) {
#pragma unroll
    for (int i = 0; i < 16; i++)
      mma_16816(o[i], x[0], x[4096], x[4], x[4100], w[8 * i] | w[4096 + 8 * i] << 16, w[8 * 4096 + 8 * i] | w[9 * 4096 + 8 * i] << 16);
  }
#pragma unroll
  for (int i = 0; i < 8; i++) {
    const int c = 4 * (i >> 1), e = 2 * (i & 1);
    __stcg(q + (i >> 1) * 32 + (i & 1) * 128 + (lane ^ (lane >> 3)),
           make_uint4(pack_bf16(o[c][e], o[c][e + 1]), pack_bf16(o[c + 1][e], o[c + 1][e + 1]),
                      pack_bf16(o[c + 2][e], o[c + 2][e + 1]), pack_bf16(o[c + 3][e], o[c + 3][e + 1])));
  }
  __syncwarp();
#pragma unroll
  for (int i = 0; i < 16; i++) o[i][0] = o[i][1] = o[i][2] = o[i][3] = 0.f;
  float m0 = -INFINITY, m1 = -INFINITY, l0 = 0.f, l1 = 0.f;
#pragma unroll 1
  for (int k0 = 0; k0 < row0 + 16; k0 += 16) {
    float sc[2][4] = {{0.f, 0.f, 0.f, 0.f}, {0.f, 0.f, 0.f, 0.f}};
#pragma unroll 1
    for (int cg = 0; cg < 4; cg++) {
      const uint4 qa = __ldcg(q + cg * 32 + (lane ^ (lane >> 3)));
      const uint4 qb = __ldcg(q + 128 + cg * 32 + (lane ^ (lane >> 3)));
#pragma unroll
      for (int t = 0; t < 2; t++) {
        const uint4 kk = __ldcg(k + (k0 + 8 * t) * 16 + cg * 32);
        mma_16816(sc[t], qa.x, qb.x, qa.y, qb.y, kk.x, kk.y);
        mma_16816(sc[t], qa.z, qb.z, qa.w, qb.w, kk.z, kk.w);
      }
    }
    float x0 = -INFINITY, x1 = -INFINITY;
#pragma unroll
    for (int t = 0; t < 2; t++) {
#pragma unroll
      for (int e = 0; e < 2; e++) {
        const int key = k0 + 8 * t + 2 * tq + e;
        if (key > row0 + g) sc[t][e] = -INFINITY;
        if (key > row0 + g + 8) sc[t][2 + e] = -INFINITY;
        x0 = fmaxf(x0, sc[t][e]);
        x1 = fmaxf(x1, sc[t][2 + e]);
      }
    }
    x0 = fmaxf(x0, __shfl_xor_sync(0xffffffffu, x0, 1));
    x1 = fmaxf(x1, __shfl_xor_sync(0xffffffffu, x1, 1));
    x0 = fmaxf(x0, __shfl_xor_sync(0xffffffffu, x0, 2));
    x1 = fmaxf(x1, __shfl_xor_sync(0xffffffffu, x1, 2));
    const float n0 = fmaxf(m0, x0), n1 = fmaxf(m1, x1);
    const float a0 = ex2(m0 - n0), a1 = ex2(m1 - n1);
    m0 = n0;
    m1 = n1;
    l0 *= a0;
    l1 *= a1;
    uint32_t pa[4];
#pragma unroll
    for (int t = 0; t < 2; t++) {
      const float e0 = ex2(sc[t][0] - m0), e1 = ex2(sc[t][1] - m0);
      const float e2 = ex2(sc[t][2] - m1), e3 = ex2(sc[t][3] - m1);
      l0 += e0 + e1;
      l1 += e2 + e3;
      pa[2 * t] = pack_bf16(e0, e1);
      pa[2 * t + 1] = pack_bf16(e2, e3);
    }
#pragma unroll
    for (int cg = 0; cg < 4; cg++) {
      const uint4 va = __ldcg(v + k0 * 16 + cg * 32);
      const uint4 vb = __ldcg(v + k0 * 16 + 128 + cg * 32);
#pragma unroll
      for (int r = 0; r < 4; r++) {
        const uint32_t w0 = r == 0 ? va.x : r == 1 ? va.y : r == 2 ? va.z : va.w;
        const uint32_t w1 = r == 0 ? vb.x : r == 1 ? vb.y : r == 2 ? vb.z : vb.w;
        float(&oo)[4] = o[4 * cg + r];
        oo[0] *= a0;
        oo[1] *= a0;
        oo[2] *= a1;
        oo[3] *= a1;
        mma_16816(oo, pa[0], pa[1], pa[2], pa[3], movm_t(w0), movm_t(w1));
      }
    }
  }
  l0 += __shfl_xor_sync(0xffffffffu, l0, 1);
  l1 += __shfl_xor_sync(0xffffffffu, l1, 1);
  l0 += __shfl_xor_sync(0xffffffffu, l0, 2);
  l1 += __shfl_xor_sync(0xffffffffu, l1, 2);
  const float i0 = 1.f / l0, i1 = 1.f / l1;
  __syncwarp();
  uint32_t* o0 = reinterpret_cast<uint32_t*>(q + g * 4) + tq;
#pragma unroll
  for (int i = 0; i < 16; i++) {
    uint32_t* d = o0 + (i >> 2) * 128 + ((i & 3) ^ (g >> 1)) * 4;
    d[0] = pack_bf16(o[i][0] * i0, o[i][1] * i0);
    d[512] = pack_bf16(o[i][2] * i1, o[i][3] * i1);
  }
}

#define KB_LIMIT 1.2089258e24f
#define KB_LOW 9.094947e-13f

__device__ __forceinline__ void local_scores(float (&s)[2][4], const uint32_t (&lo)[24], const uint32_t (&hi)[24], const uint32_t* k) {
#pragma unroll
  for (int h = 0; h < 2; h++) s[h][0] = s[h][1] = s[h][2] = s[h][3] = 0.f;
#pragma unroll
  for (int c = 0; c < 4; c += 2)
#pragma unroll
    for (int h = 0; h < 8; h += 4) mma_16816(s[h >> 2], lo[h + c], hi[h + c], lo[h + c + 1], hi[h + c + 1], k[h + c], k[h + c + 1]);
}
__device__ __forceinline__ void local_attn(float (&o)[2][4][4], float (&l)[2][4], const float (&s)[3][2][4], const uint32_t (&vt)[2][4][4],
                                           bool first, int lane) {
  const int g = lane >> 2, tq = lane & 3;
  const bool h0 = 2 * tq > g, h1 = 2 * tq + 1 > g;
  const uint32_t m = (h0 ? 0xFFFFu : 0u) | (h1 ? 0xFFFF0000u : 0u);
  float u0[2], u1[2], w0[2], w1[2], mu[2], mw[2];
#pragma unroll
  for (int h = 0; h < 2; h++) {
    u0[h] = h0 ? s[0][h][0] : s[1][h][0];
    u1[h] = h1 ? s[0][h][1] : s[1][h][1];
    w0[h] = h0 ? s[1][h][2] : s[2][h][2];
    w1[h] = h1 ? s[1][h][3] : s[2][h][3];
    if (first) {
      if (h0) u0[h] = -INFINITY;
      if (h1) u1[h] = -INFINITY;
    }
    mu[h] = fmaxf(u0[h], u1[h]);
    mw[h] = fmaxf(w0[h], w1[h]);
  }
#pragma unroll
  for (int o = 1; o <= 2; o++)
#pragma unroll
    for (int h = 0; h < 2; h++) {
      mw[h] = fmaxf(mw[h], __shfl_xor_sync(0xffffffffu, mw[h], o));
      mu[h] = fmaxf(mu[h], __shfl_xor_sync(0xffffffffu, mu[h], o));
    }
  const float c = 0.17677669529663687f * 1.4426950408889634f;
#pragma unroll
  for (int h = 0; h < 2; h++) {
    const uint32_t pu = pack_bf16(ex2((u0[h] - mu[h]) * c), ex2((u1[h] - mu[h]) * c));
    const uint32_t pw = pack_bf16(ex2((w0[h] - mw[h]) * c), ex2((w1[h] - mw[h]) * c));
    l[h][0] = l[h][1] = l[h][2] = l[h][3] = 0.f;
    mma_16816(l[h], 0x3F803F80, 0u, 0u, 0x3F803F80, pu, pw);
#pragma unroll
    for (int i = 0; i < 4; i++) {
      const uint32_t(&v)[4] = vt[i >> 1][2 * h + (i & 1)];
      o[h][i][0] = o[h][i][1] = o[h][i][2] = o[h][i][3] = 0.f;
      mma_16816(o[h][i], v[0], v[1], v[2], v[3], i < 2 ? pu & m : pw & ~m, i < 2 ? pu & ~m : pw & m);
    }
  }
}

__global__ __cluster_dims__(2, 1, 1) __launch_bounds__(512, 1) void fused_kernel(const __grid_constant__ Params p) {
  extern __shared__ __align__(1024) uint8_t smem_dyn[];
  DECLARE_READY();
  const uint32_t sbase = smem_u32(smem_dyn);
  const uint32_t afull0 = sbase + SM_BAR, aempty0 = afull0 + 48, bfull0 = afull0 + 96, bempty0 = afull0 + 128, carbar = afull0 + 160,
                 pub0 = afull0 + 200;
  const uint32_t bbase = sbase + SM_B;
  const int wg = __reduce_min_sync(0xffffffffu, (int)(threadIdx.x >> 7));
  const uint32_t rank = blockIdx.x & 1;
  const uint16_t* sched = p.sched + (blockIdx.x >> 1) * MAXITEMS;

  auto fill_b = [&](uint32_t item, int t, uint32_t pb, uint32_t pol) {
    const uint32_t kind = item & 7, j = (item >> 7) & 15, sl = pb & 3;
    if (((item >> 3) & 15) == 0) mbar_arrive_n(bempty0 + 8 * sl, 1);
    mbar_expect_tx(bfull0 + 8 * sl, kind == K_L ? 24576 : 32768);
    const uint32_t nt = kind == K_KV ? j : 2 * j + rank, dst = bbase + sl * B_SLOT;
    const uint32_t cb = kind == K_T ? nt : item_narrow(item) ? nt - 8 : nt * 2 + (t >> 1 & 1);
    const uint32_t ks = item_narrow(item) ? t : (t >> 1 & ~1) + (t & 1);
    if (kind == K_OA) {
      tma_load_5d(dst, &p.mapB[K_OA], bfull0 + 8 * sl, cb * 128, ks * 4);
      tma_load_5d(dst + 16384, &p.mapB[K_OA], bfull0 + 8 * sl, cb * 128 + 64, ks * 4);
    } else if (kind == K_L) {
      tma_load_3d(dst, &p.mapB[K_L], bfull0 + 8 * sl, nt * 64, t * 64, 0, pol);
    } else {
      tma_load_3d(dst, &p.mapB[kind == K_KV ? 1 - rank : kind], bfull0 + 8 * sl, 0, ks * 128, cb * 2, pol);
    }
  };
  auto first_a = [&](uint32_t item0, uint32_t u, bool mc) {
    const bool local0 = (item0 & 7) == K_L;
    const int g0 = (item0 >> 3) & 15;
    const int row = item_row(local0 ? K_L : K_KV, g0, (u >> 1) + (g0 == 0));
    const int r = local0 ? row & 1023 : row, blk = (local0 ? (row >> 10) * 16 : 0) + 2 * (u & 1);
    if (mc) {
      mbar_expect_tx(afull0 + 8 * u, A_STAGE);
      tma_load_3d_mc(sbase + u * A_STAGE + rank * 8192, &p.mapA[local0], afull0 + 8 * u, 0, r, blk + rank, (uint16_t)3);
    } else
      for (int h = 0; h < 2; h++) tma_load_3d(sbase + u * A_STAGE + h * 8192, &p.mapA[local0], afull0 + 8 * u, 0, r, blk + h);
  };
  auto first_b = [&](uint32_t item0, uint32_t t) {
    const bool local0 = (item0 & 7) == K_L;
    const int j = (item0 >> 7) & 15;
    mbar_expect_tx(bfull0 + 8 * t, local0 ? 24576 : 32768);
    tma_load_3d(bbase + t * B_SLOT, &p.mapB[local0 ? K_L : 1 - rank], bfull0 + 8 * t, local0 ? (2 * j + rank) * 64 : 0,
                local0 ? t * 64 : (t & 1) * 128, local0 ? 0 : 4 * j + (t & 2));
    if ((item0 & 0x78) == 0) mbar_arrive_n(bempty0 + 8 * t, 1);
  };
  if (threadIdx.x == 0) {
    mbar_init(bfull0, 1);
    mbar_init(bempty0, 3);
    asm volatile("fence.mbarrier_init.release.cluster;" ::: "memory");
    first_b(sched[0], 0);
  } else if (threadIdx.x == 32) {
    mbar_init(afull0, 1);
    asm volatile("fence.mbarrier_init.release.cluster;" ::: "memory");
    mbar_expect_tx(afull0, A_STAGE);
    first_a(sched[0], 0, false);
  } else if (threadIdx.x == 64) {
    for (int i = 20; i < 35; i++) mbar_init(afull0 + 8 * i, i < 25 ? 1 : 12);
  } else if (threadIdx.x == 96) {
    for (int i = 1; i < 20; i++)
      if (i != 12 && i != 16) mbar_init(afull0 + 8 * i, i < 6 ? 1 : i < 12 ? 2 : i < 16 ? 1 : 3);
    asm volatile("fence.mbarrier_init.release.cluster;" ::: "memory");
  }
  __syncthreads();
  asm volatile("barrier.cluster.arrive.relaxed.aligned;\nbarrier.cluster.wait.aligned;" ::: "memory");

  if (wg == 0) {
    asm volatile("setmaxnreg.dec.sync.aligned.u32 32;");
    const uint32_t item0 = sched[0];
    const bool local0 = (item0 & 7) == K_L;
    const int g0 = (item0 >> 3) & 15;
    if (threadIdx.x == 96) {
#pragma unroll 1
      for (uint32_t x = local0 ? 0x6B42A593u : 0xB6A45239u; x; x >>= 4) {
        if (x & 8) first_b(item0, x & 3);
        else if (g0 != 0 || (x & 7) < 5) first_a(item0, (x & 7) - 1, true);
      }
    }
    if (__reduce_min_sync(0xffffffffu, (int)(threadIdx.x >> 5)) == 1) {
      const uint32_t e = __ldcg(p.flags + F_EPOCH + blockIdx.x) + 1;
      const uint32_t w = threadIdx.x - 32;
      uint32_t n = w < 2 || ((sched[0] >> 3) & 15) != 0 ? 2 : 0;
      uint32_t bar0 = afull0 + 16 * w, dst0 = sbase + w * (2 * A_STAGE) + rank * 8192;
      asm volatile("" : "+r"(bar0), "+r"(dst0));
      uint32_t bar, dst, par, prev = 0;
      auto position = [&]() {
        bar = bar0 + 8 * (n & 1), dst = dst0 + (n & 1) * A_STAGE, par = (~n >> 1) & 1;
        asm volatile("" : "+r"(bar), "+r"(dst), "+r"(par));
      };
      position();
      for (int it = 0; it < MAXITEMS; it++) {
        const uint32_t item = sched[it];
        const uint32_t kind = item & 7;
        if (kind == K_END) break;
        const int g = (item >> 3) & 15;
        const int nd = kind == K_T ? 8 : item_nk(kind) >> 1;
        if (kind == K_OA) wait_flag(p.flags + F_L + g, 16 * e);
        int rho = w + (item >> 11);
        if (rho >= 3) rho -= 3;
        const int row = item_row(kind, g, kind == K_T ? 2 - rho : rho + (g == 0));
        const uint32_t on = w > 2 || (g == 0 && rho == 2) ? 0 : ~0u, swap = rho == 1 ? 0 : on, base = (0x924924 >> rho) & on;
        uint32_t m = base ^ (swap & (kind == K_L ? 0xB6DB6D : (item_narrow(item) ? (prev == K_KV ? 1 : 0x6D) : prev == K_KV ? 0x861861 : 0x86186D)));
        prev = kind;
        auto step = [&](auto load) {
          if (m & 1) {
            mbar_wait(bar + 48, par);
            mbar_expect_tx(bar, A_STAGE);
            load();
            n++;
            position();
          }
          m >>= 1;
          __syncwarp();
        };
        if (kind >= K_OA) {
          const uint4* src = p.scr + (kind == K_OA ? PL_OA : PL_CTX) * PLANE + row * 16 + rank * 512;
          uint32_t heads = kind == K_OA ? ~0u : 0, need = 1;
          for (int t = 0; t <= nd; t++, need <<= 1) {
            if (~heads & need) heads = wait_bits(p.flags + F_CTX + g * 32, (e & 1) - 1, need);
            if (item_narrow(item) && t > 2) m = (base >> 2) ^ (t == nd ? swap : 0);
#pragma unroll 1
            for (int x = t == 0; x < (t == nd ? 1 : 3); x++)
              step([&]() {
                bulk_load_mc(dst, src, 8192, bar, (uint16_t)3);
                src += PLANE;
              });
          }
        } else {
          const int r = kind == K_L ? row & 1023 : row;
          int blk = (kind == K_L ? (row >> 10) * 16 : 0) + rank;
          if (kind == K_T) m ^= swap & 0x800000;
          if (it == 0) m &= m - 1, m &= m - 1, blk += 4;
#pragma unroll 1
          for (int x = 3 * nd; x; x--)
            step([&]() {
              tma_load_3d_mc(dst, &p.mapA[kind - 1], bar, 0, r, blk, (uint16_t)3);
              blk += 2;
            });
        }
      }
      if (w < 3) {
        mbar_wait(bar0 + 48, (~(n + 1) >> 1) & 1);
        mbar_wait(bar0 + 56, (~n >> 1) & 1);
      }
    } else if (threadIdx.x == 0) {
      const uint32_t e = __ldcg(p.flags + F_EPOCH + blockIdx.x) + 1;
      uint32_t pb = 4;
      for (int it = 0; it < MAXITEMS; it++) {
        const uint32_t item = sched[it];
        const uint32_t kind = item & 7;
        if (kind == K_END) break;
        const int nk = item_nk(item);
        uint32_t heads = kind == K_OB ? wait_bits(p.flags + F_CTX + ((item >> 3) & 15) * 32, (e & 1) - 1, 0) : 0;
        const int keep = ((const uint8_t*)sched)[KEEP + it];
        for (int t = it == 0 ? 4 : 0; t < nk; t++, pb++) {
          mbar_wait(bempty0 + 8 * (pb & 3), ((pb >> 2) & 1) ^ 1);
          fill_b(item, t, pb, keep & 32 ? L2_NORMAL : L2_FIRST);
          if (item_narrow(item) && kind == K_OB) {
            const uint32_t g = (item >> 3) & 15, nb = g ? 3 : 2;
            if (!(heads >> t & 2)) heads = wait_bits(p.flags + F_CTX + g * 32, (e & 1) - 1, 0);
            if (heads >> t & 2) prefetch_l2(p.scr + (PL_CTX + t + 1) * PLANE + (3 * g + 2 - nb) * 1024 + rank * nb * 512, nb * 8192);
          }
        }
        if (kind == K_T) {
          const int g = (item >> 3) & 15, j = (item >> 7) & 15;
          const uint4* src = p.scr + (PL_KV + j * 4 + rank) * PLANE;
          const int n = ((3 * g + 1) >> 1) + 1;
          uint32_t groups = 0;
          for (int t = 0; t < n; t++, src += 2048) {
            const uint32_t need = (4u << 2 * min((2 * t + 2) / 3, g)) - 1;
            if (~groups & need) groups = wait_bits(p.flags + F_KV + j * 32, (e & 1) - 1, need);
            const uint32_t nskip = t == n - 1 ? 1 + (g & 1) : 0;
            const uint32_t pol = t < (keep & 31) ? L2_NORMAL : L2_FIRST;
            uint32_t sl = pb & 3;
            mbar_wait(bempty0 + 8 * sl, ((pb >> 2) & 1) ^ 1);
            if (nskip) mbar_arrive_n(bempty0 + 8 * sl, nskip);
            mbar_expect_tx(bfull0 + 8 * sl, 32768);
            pb++;
            if (nskip == 2) {
              bulk_load(bbase + sl * B_SLOT, src, 16384, bfull0 + 8 * sl, pol);
              bulk_load(bbase + sl * B_SLOT + 16384, src + 2 * PLANE, 16384, bfull0 + 8 * sl, pol);
              continue;
            }
            bulk_load(bbase + sl * B_SLOT, src, 32768, bfull0 + 8 * sl, pol);
            sl = pb & 3;
            mbar_wait(bempty0 + 8 * sl, ((pb >> 2) & 1) ^ 1);
            if (nskip) mbar_arrive_n(bempty0 + 8 * sl, nskip);
            mbar_expect_tx(bfull0 + 8 * sl, 32768);
            bulk_load(bbase + sl * B_SLOT, src + 2 * PLANE, 32768, bfull0 + 8 * sl, pol);
            pb++;
          }
        }
      }
    } else if (threadIdx.x == 64) {
      const uint32_t pair = 2 * ((sched[0] >> 7) & 15) + rank;
      if ((sched[0] & 127) == K_L) {
        mbar_wait(carbar + 24, 0);
        asm volatile("fence.proxy.async.shared::cta;\ncp.async.bulk.global.shared::cta.bulk_group [%0], [%1], 2048;\n"
                     "cp.async.bulk.commit_group;\ncp.async.bulk.wait_group 0;\nfence.proxy.async.global;\nfence.acq_rel.gpu;" ::"l"(p.carry + pair * 128),
                     "r"(sbase + SM_CARRY - 2048)
                     : "memory");
        red_add(p.flags + F_CAR + pair);
      }
      if ((sched[0] & 127) == (K_L | 6 << 3)) {
        wait_flag(p.flags + F_CAR + pair, __ldcg(p.flags + F_EPOCH + blockIdx.x) + 1);
        mbar_expect_tx(carbar + 32, 2048);
        bulk_load(sbase + SM_CARRY, p.carry + pair * 128, 2048, carbar + 32);
      }
      for (int it = 0; it < MAXITEMS; it++) {
        const uint32_t item = sched[it];
        const uint32_t kind = item & 7;
        const int g = (item >> 3) & 15, j = (item >> 7) & 15;
        if (kind >= K_OA) break;
        mbar_wait(pub0 + 8 * it, 0);
        asm volatile("fence.acq_rel.gpu;" ::: "memory");
        if (kind == K_KV) red_xor(p.flags + F_KV + j * 32, 1u << (2 * g + rank));
        if (kind == K_L) red_add(p.flags + F_L + g);
        if (kind == K_T) red_xor(p.flags + F_CTX + g * 32, 1u << (2 * j + rank));
      }
      red_add(p.flags + F_EPOCH + blockIdx.x);
    } else if (threadIdx.x == 96) {
      for (int i = 0; i < 3; i++) prefetch_tmap(&p.mapA[i]);
      for (int i = 0; i < 6; i++) prefetch_tmap(&p.mapB[i]);
      prefetch_tmap(&p.mapO[0]);
      prefetch_tmap(&p.mapO[1]);
    }
  } else {
    asm volatile("setmaxnreg.inc.sync.aligned.u32 160;");
    const int cw = wg - 1;
    const int wq = __reduce_min_sync(0xffffffffu, (int)((threadIdx.x >> 5) & 3));
    auto turn = [&](uint32_t dep = 0) {
      bar_sync((1 + cw) | dep, NTURN);
    };
    const int fwd = cw == 0 ? 3 : cw, back = cw == 2 ? 1 : cw + 2;
    int next = fwd;
    auto pass = [&]() {
      bar_arrive(next, NTURN);
      next = fwd;
    };
    auto rank_of = [&](uint32_t item) {
      const int r = cw + (item >> 11);
      return r >= 3 ? r - 3 : r;
    };
    if (cw == 1) pass();
    if (cw == 2) { turn(); pass(); }
    const uint32_t abase = sbase + cw * (2 * A_STAGE), afull = afull0 + 16 * cw, aempty = aempty0 + 16 * cw;
    const uint32_t adesc = ((abase & 0x3FFFF) >> 4) | (1u << 16), bdesc = (bbase & 0x3FFFF) >> 4;
    uint32_t pa = 0, pb = 0;
    int it = 0;
    uint32_t item = sched[0];
    auto publish = [&](int i, uint32_t skip = 0) {
      __syncwarp();
      mbar_arrive_if0(pub0 + 8 * i, (threadIdx.x & 31) | skip);
    };
    auto test_ab = [&](uint32_t a, uint32_t b) {
      test_a(afull + 8 * (a & 1), (a >> 1) & 1);
      test_b(bfull0 + 8 * (b & 3), (b >> 2) & 1);
    };
    auto wait_ab = [&]() {
      if (!ready_ab()) {
        mbar_wait_u(afull + 8 * (pa & 1), (pa >> 1) & 1);
        mbar_wait_u(bfull0 + 8 * (pb & 3), (pb >> 2) & 1);
      }
    };
    auto release_ab = [&](uint32_t a, uint32_t b, uint32_t skip) {
      mbar_arrive_cta_if0(wq < 2 ? aempty + 8 * (a & 1) : bempty0 + 8 * (b & 3), wq < 2 ? wq : rank, (threadIdx.x & 31) | (wq == 3) | skip);
    };
    test_ab(0, 0);
    uint32_t bflag = 512u << 16;
    enum { NEW = 1, REL = 2, FWD = 4, TEST = 8, BACK = 16 };
    auto gturn = [&](auto mode_c, bool hold, auto mma, auto meanwhile) {
      constexpr int MODE = decltype(mode_c)::value;
      uint32_t da = adesc + (pa & 1) * (A_STAGE >> 4), db = bdesc + (pb & 3) * (B_SLOT >> 4) + bflag;
      asm volatile("" : "+r"(da), "+r"(db));
      if (MODE & NEW) wait_ab();
      else if (!ready_b()) mbar_wait_u(bfull0 + 8 * (pb & 3), (pb >> 2) & 1);
      turn();
      wg_fence();
      mma(da, db);
      wg_commit();
      if (!hold) pass();
      if (hold) {
      } else if (MODE & TEST) test_ab(pa + 1, pb + 1);
      else test_b(bfull0 + 8 * ((pb + 1) & 3), ((pb + 1) >> 2) & 1);
      meanwhile();
      wg_wait<0>();
      if (MODE & REL) {
        if (!hold) release_ab(pa, pb, 0);
      } else {
        mbar_arrive_if0(bempty0 + 8 * (pb & 3), threadIdx.x & 127);
      }
      if (MODE & FWD) pa++;
      if (MODE & BACK) pa--;
      __syncwarp();
      pb++;
    };
    constexpr std::true_type YES{};
    constexpr std::false_type NO{};
    constexpr std::integral_constant<int, NEW> FIRST{};
    constexpr std::integral_constant<int, REL | FWD | TEST> SECOND{};
    constexpr std::integral_constant<int, NEW | REL | FWD | TEST> ONCE{};
    constexpr std::integral_constant<int, NEW | FWD | TEST> X0{};
    constexpr std::integral_constant<int, NEW | BACK> X1{};
    constexpr std::integral_constant<int, REL | FWD> Y0{};
    auto nothing = []() {};
    auto idle = [&]() { return ((item >> 3) & 15) == 0 && rank_of(item) == 2; };
    auto skip_item = [&](int passed) {
      const int n = (item & 7) == K_T ? 10 : item_nk(item);
      publish(it);
#pragma unroll 1
      for (int i = 2 + passed; i < n; i++) {
        turn();
        pass();
      }
      pb += n;
      test_ab(pa, pb);
      item = sched[++it];
    };

    if ((item & 7) == K_L && idle()) skip_item(0);
    float lo_[2][4][4] = {}, ll[2][4] = {};
    uint4* ldst = p.scr;
    uint32_t lnone = 1;
    auto lrelease = [&]() { release_ab(1, 3, lnone); };
    auto lpack = [&](uint32_t (&r)[16]) {
      const uint32_t t = sched_fence() & p.zero;
#pragma unroll
      for (int i = 0; i < 4; i++) {
        const int h = i >> 1, e = i & 1 ? 2 : 0;
        const float f0 = rcp(__uint_as_float(__float_as_uint(ll[h][e]) | t)), f1 = rcp(__uint_as_float(__float_as_uint(ll[h][e + 1]) | t));
        const float(&r0)[4] = lo_[h][e], (&r1)[4] = lo_[h][e + 1];
        r[4 * i] = movm_t(pack_bf16(r0[0] * f0, r0[1] * f1)), r[4 * i + 1] = movm_t(pack_bf16(r0[2] * f0, r0[3] * f1));
        r[4 * i + 2] = movm_t(pack_bf16(r1[0] * f0, r1[1] * f1)), r[4 * i + 3] = movm_t(pack_bf16(r1[2] * f0, r1[3] * f1));
      }
#pragma unroll
      for (int i = 0; i < 16; i++) asm volatile("" : "+r"(r[i])::"memory");
    };
    auto lstore = [&](const uint32_t (&r)[16]) {
#pragma unroll
      for (int i = 0; i < 4; i++) stg128_if0(ldst + (i >> 1) * 32 + (i & 1) * 128, r[4 * i], r[4 * i + 1], r[4 * i + 2], r[4 * i + 3], lnone);
      publish(it - 1, lnone);
    };
    while ((item & 7) == K_L) {
      const int g = (item >> 3) & 15, j = (item >> 7) & 15;
      const int rho = rank_of(item);
      float acc[96];
      auto mma = [&](int kb, bool first) {
        return [&acc, kb, first](uint32_t da, uint32_t db) {
#pragma unroll
          for (int k = 0; k < 4; k++) wgmma_n192_tb(acc, da + kb * 512 + k * 2, db + k * 128, !(first && k == 0));
        };
      };
      gturn(FIRST, false, mma(0, true), lrelease);
      uint32_t r[16];
      gturn(SECOND, false, mma(1, false), [&]() { lpack(r); lstore(r); });
#pragma unroll 1
      for (int d = 7;;) {
        gturn(FIRST, false, mma(0, false), nothing);
        if (--d == 0) break;
        gturn(SECOND, false, mma(1, false), nothing);
      }
      const int lane = threadIdx.x & 31;
      const int from = rho ? rho : 4 * (~g & 1), to = g == 0 ? 3 * rho : rho == 2 ? 4 * (g & 1) : rho + 1;
      uint32_t own, front, vlo;
      gturn(SECOND, true, mma(1, false), [&]() {
        bar_arrive_if(rho != 2, g && rho ? back : next, NTURN);
        own = (wq < 3 ? abase + A_STAGE + wq * 2048 : sbase + SM_CARRY - 8192 + to * 2048) + lane * 16;
        front = (wq > 0 ? abase + A_STAGE + wq * 2048 - 2048 : g == 0 ? abase + A_STAGE : sbase + SM_CARRY - 8192 + from * 2048) + lane * 16;
        vlo = abase + A_STAGE + 8192 + wq * 1024 + lane * 16;
        ldst = p.scr + (PL_OA + j) * PLANE + (item_row(K_L, g, rho + (g == 0)) + wq * 16) * 16 + rank * 64 + (lane ^ (lane >> 3));
        asm volatile("" : "+r"(own), "+r"(front), "+r"(vlo), "+l"(ldst));
        lnone = 0;
        item = sched[++it];
        if (wq == 0 && g != 0) mbar_wait_u(carbar + 8 * from, ((g - (g <= 5 ? 1 : 6)) >> (rho == 0)) & 1);
      });
      if (g && rho == 0) next = back;
      fence_regs(acc);
      uint32_t lo[24], hi[24], hk[8], vt[2][4][4];
#pragma unroll
      for (int i = 0; i < 24; i++) {
        lo[i] = pack_bf16(acc[4 * i], acc[4 * i + 1]);
        hi[i] = pack_bf16(acc[4 * i + 2], acc[4 * i + 3]);
      }
      sts128(own, hi[8], hi[9], hi[10], hi[11]);
      sts128(own + 512, hi[12], hi[13], hi[14], hi[15]);
      stsm4(own + 1024, hi[16], hi[17], hi[18], hi[19]);
      stsm4(own + 1536, hi[20], hi[21], hi[22], hi[23]);
      __syncwarp();
      mbar_arrive_if0(carbar + 8 * to, lane | (wq ^ 3));
      stsm4(vlo, lo[16], lo[17], lo[18], lo[19]);
      stsm4(vlo + 512, lo[20], lo[21], lo[22], lo[23]);
      bar_sync(4 + cw, 128);
      lds128(front, hk[0], hk[1], hk[2], hk[3]);
      lds128(front + 512, hk[4], hk[5], hk[6], hk[7]);
#pragma unroll
      for (int i = 0; i < 8; i++) ldsm4_t((lane < 16 ? (i < 4 ? front : own) + 1024 : vlo - 256) + (i & 3) * 256, vt[i >> 2][i & 3]);
      float sc[3][2][4];
      local_scores(sc[2], lo, hi, hi + 8);
      local_scores(sc[1], lo, hi, lo + 8);
      local_scores(sc[0], lo, hi, hk);
      test_ab(pa, pb);
      local_attn(lo_, ll, sc, vt, g == 0 && wq == 0, lane);
      bar_arrive_if(rho == 2, back, NTURN);
    }
    if (!lnone) {
      bar_sync(4 + cw, 128);
      lrelease();
      uint32_t r[16];
      lpack(r);
      lstore(r);
    }

    bflag = 1024u << 16;
    float Y[64];
    float sc0 = 0.f, sc1 = 0.f;
    uint32_t done;
    uint4* pdst;
    auto pack = [&](uint32_t (&r)[16], const float (&acc)[64], int h, float s0, float s1) {
#pragma unroll
      for (int i = 0; i < 8; i++) {
        const int c = 32 * h + 4 * i;
        r[8 * (i >> 2) + (i & 3)] = pack_bf16(acc[c] * s0, acc[c + 1] * s0);
        r[8 * (i >> 2) + (i & 3) + 4] = pack_bf16(acc[c + 2] * s1, acc[c + 3] * s1);
      }
    };
    auto pack_now = [&](uint32_t (&r)[16], const float (&acc)[64], int h) {
      pack(r, acc, h, sc0, sc1);
#pragma unroll
      for (int i = 0; i < 16; i++) asm volatile("" : "+r"(r[i])::"memory");
    };
    auto stores = [&](auto ofs_c, const uint32_t (&r)[16], uint32_t sel) {
      constexpr int OFS = decltype(ofs_c)::value;
      stg128_sel<OFS>(pdst, r[0], r[1], r[2], r[3], sel);
      stg128_sel<OFS + 128>(pdst, r[4], r[5], r[6], r[7], sel);
      stg128_sel<OFS + 32>(pdst, r[8], r[9], r[10], r[11], sel);
      stg128_sel<OFS + 160>(pdst, r[12], r[13], r[14], r[15], sel);
    };
    constexpr std::integral_constant<int, 0> H0{};
    constexpr std::integral_constant<int, 64> H1{};
    auto flush = [&]() {
      uint32_t r[16];
      turn();
      pass();
      sched_fence();
      pack(r, Y, 0, sc0, sc1);
      stores(H0, r, done);
      turn();
      pass();
      sched_fence();
      pack(r, Y, 1, sc0, sc1);
      stores(H1, r, done);
      publish(it - 1, done & 1);
    };
    auto no_pending = [&]() {
      done = 1;
      pdst = p.scr;
#pragma unroll
      for (int i = 0; i < 64; i++) Y[i] = 0.f;
      fence_regs(Y);
    };
    no_pending();
    auto mma128 = [&](auto scr_c, float (&acc)[64], int keep) {
      return [&acc, keep](uint32_t da, uint32_t db) {
        constexpr bool SCR = decltype(scr_c)::value;
#pragma unroll
        for (int k = 0; k < 8; k++)
          wgmma_n128<1>(acc, da + (k & 1) * 2 + ((k >> 1) & 1) * (SCR ? 32 : 4) + (k >> 2) * (SCR ? 64 : 512), SCR ? HI64 : HI128,
                        db + k * 128, HI128, k != 0 || keep);
      };
    };
    auto first_two = [&](auto mode0, auto mode1, auto scr_c, float (&X)[64]) {
      uint32_t r0[16], r1[16];
      gturn(mode0, false, mma128(scr_c, X, false), [&]() { pack_now(r0, Y, 0); });
      stores(H0, r0, done);
      gturn(mode1, false, mma128(scr_c, X, true), [&]() { pack_now(r1, Y, 1); });
      stores(H1, r1, done);
      publish(it - 1, done & 1);
    };
    auto all_but_last_two = [&](auto scr_c, float (&X)[64]) {
      int n = item_nk(item);
      first_two(X0, X1, scr_c, X);
      gturn(Y0, false, mma128(scr_c, Y, false), nothing);
#pragma unroll 1
      while (true) {
        gturn(SECOND, false, mma128(scr_c, Y, true), nothing);
        gturn(X0, false, mma128(scr_c, X, true), nothing);
        gturn(X1, false, mma128(scr_c, X, true), nothing);
        if (!decltype(scr_c)::value || (n -= 4) == 4) break;
        gturn(Y0, false, mma128(scr_c, Y, true), nothing);
      }
      fence_regs(X);
    };
    while ((item & 7) < K_OA) {
      if (idle()) {
        flush();
        done = 1;
        skip_item(2);
        continue;
      }
      const uint32_t kind = item & 7;
      const int g = (item >> 3) & 15, j = (item >> 7) & 15;
      const int rho = rank_of(item);
      if (kind != K_T) {
        float X[64];
        all_but_last_two(NO, X);
        const int lane = threadIdx.x & 31;
        const int row = item_row(K_KV, g, rho + (g == 0)) + wq * 16;
        sc0 = sc1 = rank ? 1.f : QS;
        pdst = p.scr + (PL_KV + j * 4 + rank * 2 + 1) * PLANE + row * 16 + (lane ^ (lane >> 3));
        uint32_t r0[16], r1[16];
        pack(r0, X, 0, sc0, sc1);
        stores(std::integral_constant<int, -PLANE>{}, r0, 0);
        gturn(Y0, false, mma128(NO, Y, true), [&]() { pack_now(r1, X, 1); });
        stores(std::integral_constant<int, 64 - PLANE>{}, r1, 0);
        item = sched[++it];
        gturn(SECOND, false, mma128(NO, Y, true), nothing);
        test_ab(pa, pb);
        fence_regs(Y);
        done = 0;
      } else {
        float(&O)[64] = Y;
        float S[64];
        float l0 = 0.f, l1 = 0.f;
        float zlim;
        asm volatile("" : "+f"(l0), "+f"(l1));
        const uint32_t sel = threadIdx.x & 127;
        const int b = 3 * g + 1 - rho;
        first_two(ONCE, ONCE, NO, S);
#pragma unroll 1
        for (int n = 0; n < 5; n++) gturn(ONCE, false, mma128(NO, S, true), nothing);
#pragma unroll
        for (int i = 0; i < 64; i++) O[i] = 0.f;
        fence_regs(O);
        gturn(FIRST, false, mma128(NO, S, true), nothing);
        fence_regs(S);
        {
          const uint32_t lane = threadIdx.x & 31, dst = abase + (pa & 1) * A_STAGE + wq * 2048 + (lane ^ (lane >> 3)) * 16;
#pragma unroll
          for (int h = 0; h < 2; h++) {
            uint32_t r[16];
            pack(r, S, h, 1.f, 1.f);
#pragma unroll
            for (int i = 0; i < 4; i++) {
              sts128(dst + h * 8192 + (i >> 1) * 512 + (i & 1) * 1024, r[4 * i], r[4 * i + 1], r[4 * i + 2], r[4 * i + 3]);
              if (4 * h + i < 7) __nanosleep(30);
            }
          }
          asm volatile("fence.proxy.async.shared::cta;" ::: "memory");
        }
        enum { MID, LAST, HALF };
        auto round = [&](auto mode_c) {
          constexpr int MODE = decltype(mode_c)::value;
          constexpr bool INIT = MODE == LAST;
          constexpr int NI = MODE == HALF ? 8 : 16;
          const uint32_t shared = MODE == HALF ? rho == 0 : 0;
          const uint32_t tv = pb + 1 - shared;
          {
            const uint32_t dq = adesc + (pa & 1) * (A_STAGE >> 4);
            const uint32_t dk = bdesc + (pb & 3) * 2048 + (1u << 16);
            if (INIT) {
              const int lane = threadIdx.x & 31;
              const int row = (wq * 16 + (lane >> 2) - 2 * (lane & 3) + 11) << 23;
              const int r0 = row ^ (__float_as_uint(l0) & p.zero & (MODE + 16)), r1 = row ^ (__float_as_uint(l1) & p.zero & (MODE + 16));
#pragma unroll
              for (int i = 0; i < 4 * NI; i++) {
                const int c = i - 4 * (NI - 8);
                S[i] = c < 0 ? 0.f : __int_as_float((c & 2 ? r1 : r0) + ((4 * (c & 2) - 2 * (c & ~3) - (c & 1) - 11) << 23));
                asm volatile("" : "+f"(S[i])::"memory");
              }
            }
            if (!ready_b()) mbar_wait_u(bfull0 + 8 * (pb & 3), (pb >> 2) & 1);
            turn();
            wg_fence();
#pragma unroll
            for (int k = 0; k < 8; k++) {
              const uint32_t da = dq + (k >> 2) * 512 + (k & 2) * 16 + (k & 1) * 2, db = dk + (k >> 1) * 32 + (k & 1) * 2;
              if (MODE == HALF) wgmma_n64(S, da, db, k != 0 || INIT);
              else wgmma_n128<0>(S, da, HIQ, db, HI64, k != 0 || INIT);
            }
            wg_commit();
            pass();
          }
          test_b(bfull0 + 8 * (tv & 3), (tv >> 2) & 1);
          if (!ready_b()) mbar_wait_u(bfull0 + 8 * (tv & 3), (tv >> 2) & 1);
          wg_wait<0>();
#pragma unroll
          for (int i = 0; i < 4 * NI; i++) asm volatile("" : "+f"(S[i])::"memory");
          mbar_arrive_if0(bempty0 + 8 * (pb & 3), sel | shared);
          if (MODE >= LAST) mbar_arrive_cta_if0(aempty + 8 * (pa & 1), wq & 1, (sel & 31) | (wq >> 1));
          uint32_t P[2 * NI];
          if (MODE >= LAST && !INIT) {
            const int lane = threadIdx.x & 31;
            const int row = wq * 16 + (lane >> 2) - 2 * (lane & 3);
#pragma unroll
            for (int i = 0; i < 8; i++) {
#pragma unroll
              for (int e = 0; e < 2; e++) {
                if (8 * i + e > row) S[4 * (NI - 8 + i) + e] = -INFINITY;
                if (8 * i + e > row + 8) S[4 * (NI - 8 + i) + 2 + e] = -INFINITY;
              }
            }
          }
          float s0 = 0.f, s1 = 0.f, t0 = 0.f, t1 = 0.f;
#pragma unroll
          for (int i = 0; i < NI; i++) {
#pragma unroll
            for (int e = 0; e < 4; e++) S[4 * i + e] = ex2(S[4 * i + e]);
            s0 += S[4 * i];
            t0 += S[4 * i + 1];
            s1 += S[4 * i + 2];
            t1 += S[4 * i + 3];
            P[2 * i] = pack_bf16(S[4 * i], S[4 * i + 1]);
            P[2 * i + 1] = pack_bf16(S[4 * i + 2], S[4 * i + 3]);
          }
          l0 += s0 + t0;
          l1 += s1 + t1;
          uint32_t dep = (__float_as_uint(l0) ^ __float_as_uint(l1)) ^ P[2 * NI - 1];
          fence_regs(O);
#pragma unroll
          for (int i = 0; i < 2 * NI; i++) asm volatile("" : "+r"(P[i])::"memory");
          const uint32_t dv = (bdesc + (tv & 3) * 2048 + shared * 1024) | (32u << 16);
          turn(dep & p.zero);
          wg_fence();
#pragma unroll
          for (int k = 0; k < NI / 2; k++)
            wgmma_n128_rs_tb(O, P[4 * k], P[4 * k + 1], P[4 * k + 2], P[4 * k + 3], dv + k * 256, 1);
          wg_commit();
          pass();
          pb = tv + 1;
          if (MODE >= LAST) {
            const int nskip = 1 + (g & 1);
            if (rho + nskip >= 3) pb += 3 - nskip;
            pa++;
          } else {
            test_b(bfull0 + 8 * (pb & 3), (pb >> 2) & 1);
          }
          if (MODE >= LAST) {
            l0 += __shfl_xor_sync(0xffffffffu, l0, 1);
            l1 += __shfl_xor_sync(0xffffffffu, l1, 1);
            l0 += __shfl_xor_sync(0xffffffffu, l0, 2);
            l1 += __shfl_xor_sync(0xffffffffu, l1, 2);
            sc0 = rcp(l0);
            sc1 = rcp(l1);
            zlim = l0 <= KB_LIMIT && l0 >= KB_LOW && l1 <= KB_LIMIT && l1 >= KB_LOW ? 3e38f : -1.f;
          }
          wg_wait<0>();
          fence_regs(O);
          mbar_arrive_if0(bempty0 + 8 * (tv & 3), sel);
        };
#pragma unroll 1
        for (int n = b >> 1; n; n--) round(std::integral_constant<int, MID>{});
        item = sched[++it];
        if (b & 1) round(std::integral_constant<int, LAST>{});
        else round(std::integral_constant<int, HALF>{});
        test_ab(pa, pb);
        float z[4] = {0.f, 0.f, 0.f, 0.f};
#pragma unroll
        for (int i = 0; i < 32; i++) z[i & 3] = fmaf(O[2 * i], O[2 * i + 1], z[i & 3]);
        const bool bad = !(fabsf(z[0]) + fabsf(z[1]) + fabsf(z[2]) + fabsf(z[3]) <= zlim);
        const int lane = threadIdx.x & 31;
        pdst = p.scr + (PL_CTX + 2 * j + rank) * PLANE + (b * 64 + wq * 16) * 16 + (lane ^ (lane >> 3));
        done = ((const uint8_t*)sched)[KEEP + it - 1] >> 6;
        if (__any_sync(0xffffffffu, bad)) {
          attn_fallback(p.scr + (PL_CTX + 2 * j + rank) * PLANE, p.scr + (PL_KV + j * 4 + rank) * PLANE, p.x,
                        p.wq + (2 * j + rank) * 128, b * 64 + wq * 16, threadIdx.x & 31);
          publish(it - 1);
          no_pending();
          test_ab(pa, pb);
        }
      }
    }

    bool relay = true;
    if (idle()) {
      flush();
      skip_item(2);
    } else {
      const uint32_t kind = item & 7;
      const int g = (item >> 3) & 15, j = (item >> 7) & 15;
      const int row = item_row(kind, g, rank_of(item) + (g == 0)) + wq * 16;
      auto epilogue = [&](float (&acc)[64], int cb, bool pace) {
        const int lane = threadIdx.x & 31;
        const uint32_t stg = abase + ((pa - 1) & 1) * A_STAGE + wq * 4096;
        const int srow = lane & 15;
#pragma unroll
        for (int jj = 0; jj < 8; jj++) {
          const uint32_t r0 = pack_bf16(acc[8 * jj + 0], acc[8 * jj + 1]);
          const uint32_t r1 = pack_bf16(acc[8 * jj + 2], acc[8 * jj + 3]);
          const uint32_t r2 = pack_bf16(acc[8 * jj + 4], acc[8 * jj + 5]);
          const uint32_t r3 = pack_bf16(acc[8 * jj + 6], acc[8 * jj + 7]);
          const int chunk = (2 * jj + (lane >> 4)) & 7;
          const uint32_t addr = stg + (jj >> 2) * 2048 + srow * 128 + ((chunk ^ (srow & 7)) << 4);
          asm volatile("stmatrix.sync.aligned.m8n8.x4.shared.b16 [%0], {%1,%2,%3,%4};" ::"r"(addr), "r"(r0), "r"(r1), "r"(r2), "r"(r3)
                       : "memory");
          if (jj < 7 && pace) __nanosleep(30);
        }
        asm volatile("fence.proxy.async.shared::cta;" ::: "memory");
        __syncwarp();
        if (lane == 0) {
          const int col = cb * 128 + (kind == K_OA ? (row >> 10) * 2048 : 1024);
          const int r = kind == K_OA ? row & 1023 : row;
          tma_store_2d(&p.mapO[kind - K_OA], stg, col, r);
          tma_store_2d(&p.mapO[kind - K_OA], stg + 2048, col + 64, r);
          asm volatile("cp.async.bulk.commit_group;" ::: "memory");
        }
      };
      float X[64];
      relay = g == 0;
      const int last = g && rank_of(item) == 1 ? back : fwd;
      if (item_narrow(item)) {
        int n = item_nk(item);
        first_two(ONCE, ONCE, YES, X);
#pragma unroll 1
        while (--n > 1) {
          if (n == 2) next = last;
          gturn(ONCE, false, mma128(YES, X, true), nothing);
        }
        fence_regs(X);
        epilogue(X, 2 * j + rank - 8, rank_of(item) == 0);
      } else {
        all_but_last_two(YES, X);
        gturn(Y0, false, mma128(YES, Y, true), nothing);
        epilogue(X, 4 * j + 2 * rank, true);
        next = last;
        gturn(SECOND, false, mma128(YES, Y, true), nothing);
        fence_regs(Y);
        epilogue(Y, 4 * j + 2 * rank + 1, rank_of(item) == 0);
      }
      item = sched[++it];
    }
    const int rho = rank_of(item);
    uint32_t id;
    asm volatile("mov.u32 %0, %%tid.x;" : "=r"(id));
    if (rho == 0 && relay) {
      bar_sync(id >> 7, NTURN);
      bar_arrive(id < 256 ? 3 : (id >> 7) - 1, NTURN);
    }
    if (rho == 1) bar_sync(id >> 7, NTURN);
    asm volatile("cp.async.bulk.wait_group.read 0;" ::: "memory");
  }
}

typedef CUresult (*EncodeFn)(CUtensorMap*, CUtensorMapDataType, cuuint32_t, void*, const cuuint64_t*, const cuuint64_t*,
                             const cuuint32_t*, const cuuint32_t*, CUtensorMapInterleave, CUtensorMapSwizzle, CUtensorMapL2promotion,
                             CUtensorMapFloatOOBfill);

void make_map(EncodeFn enc, CUtensorMap* m, const void* ptr, uint64_t d0, uint64_t d1, uint64_t d2, uint64_t s1, uint64_t s2, uint32_t b0,
              uint32_t b1, uint32_t b2) {
  cuuint64_t gd[3] = {d0, d1, d2}, gs[2] = {s1, s2};
  cuuint32_t bd[3] = {b0, b1, b2}, es[3] = {1, 1, 1};
  enc(m, CU_TENSOR_MAP_DATA_TYPE_BFLOAT16, d2 ? 3 : 2, const_cast<void*>(ptr), gd, gs, bd, es, CU_TENSOR_MAP_INTERLEAVE_NONE,
      CU_TENSOR_MAP_SWIZZLE_128B, CU_TENSOR_MAP_L2_PROMOTION_L2_128B, CU_TENSOR_MAP_FLOAT_OOB_FILL_NONE);
}

struct HostState {
  Params p;
  const void* in[9];
  void* out;
  bool valid;
};
HostState g_hs;

const uint16_t h_sched[NCLUSTERS * MAXITEMS] = {
    809, 851, 35, 1553, 1457, 1587, 148, 7, 7, 7, 7, 7, 7, 7, 7, 7,
    690, 698, 706, 714, 722, 1665, 1947, 1993, 837, 7, 7, 7, 7, 7, 7, 7,
    265, 835, 1043, 1177, 1201, 1875, 52, 7, 7, 7, 7, 7, 7, 7, 7, 7,
    721, 667, 587, 1219, 981, 7, 7, 7, 7, 7, 7, 7, 7, 7, 7, 7,
    209, 787, 537, 971, 1937, 1611, 204, 7, 7, 7, 7, 7, 7, 7, 7, 7,
    281, 643, 513, 547, 3, 1097, 1355, 805, 7, 7, 7, 7, 7, 7, 7, 7,
    337, 425, 339, 1315, 1961, 1971, 12, 7, 7, 7, 7, 7, 7, 7, 7, 7,
    306, 314, 322, 330, 338, 1155, 1353, 1995, 132, 7, 7, 7, 7, 7, 7, 7,
    817, 827, 569, 59, 1593, 1715, 140, 7, 7, 7, 7, 7, 7, 7, 7, 7,
    386, 394, 402, 410, 418, 426, 1539, 1555, 821, 7, 7, 7, 7, 7, 7, 7,
    273, 819, 939, 1417, 1803, 1849, 1481, 677, 7, 7, 7, 7, 7, 7, 7, 7,
    689, 683, 1033, 1075, 1681, 1867, 60, 7, 7, 7, 7, 7, 7, 7, 7, 7,
    137, 795, 897, 907, 593, 1331, 1585, 1609, 949, 7, 7, 7, 7, 7, 7, 7,
    313, 387, 331, 1089, 1299, 1697, 1675, 829, 7, 7, 7, 7, 7, 7, 7, 7,
    258, 266, 274, 282, 290, 298, 1569, 1851, 20, 7, 7, 7, 7, 7, 7, 7,
    641, 843, 1067, 1433, 1827, 669, 7, 7, 7, 7, 7, 7, 7, 7, 7, 7,
    777, 803, 523, 1027, 43, 1699, 917, 7, 7, 7, 7, 7, 7, 7, 7, 7,
    385, 401, 323, 1281, 1339, 1547, 781, 7, 7, 7, 7, 7, 7, 7, 7, 7,
    329, 779, 545, 555, 1105, 1425, 1483, 645, 7, 7, 7, 7, 7, 7, 7, 7,
    649, 675, 579, 1193, 1577, 1731, 76, 7, 7, 7, 7, 7, 7, 7, 7, 7,
    705, 811, 979, 1579, 717, 7, 7, 7, 7, 7, 7, 7, 7, 7, 7, 7,
    681, 417, 307, 953, 1153, 1235, 789, 7, 7, 7, 7, 7, 7, 7, 7, 7,
    305, 659, 267, 931, 1171, 1561, 1835, 517, 7, 7, 7, 7, 7, 7, 7, 7,
    770, 778, 786, 794, 802, 810, 1953, 1979, 44, 7, 7, 7, 7, 7, 7, 7,
    785, 131, 315, 1073, 49, 1801, 1945, 1987, 172, 7, 7, 7, 7, 7, 7, 7,
    129, 187, 1, 1051, 1329, 1843, 797, 7, 7, 7, 7, 7, 7, 7, 7, 7,
    2, 10, 18, 26, 34, 42, 1449, 1595, 84, 7, 7, 7, 7, 7, 7, 7,
    697, 651, 259, 553, 947, 1163, 2003, 4, 7, 7, 7, 7, 7, 7, 7, 7,
    769, 691, 955, 73, 1963, 853, 7, 7, 7, 7, 7, 7, 7, 7, 7, 7,
    130, 138, 146, 154, 162, 170, 1411, 1811, 845, 7, 7, 7, 7, 7, 7, 7,
    257, 395, 275, 963, 1825, 1739, 28, 7, 7, 7, 7, 7, 7, 7, 7, 7,
    898, 906, 914, 922, 930, 938, 1795, 1683, 597, 7, 7, 7, 7, 7, 7, 7,
    713, 715, 585, 1305, 1227, 701, 7, 7, 7, 7, 7, 7, 7, 7, 7, 7,
    321, 203, 25, 1291, 1929, 1619, 180, 7, 7, 7, 7, 7, 7, 7, 7, 7,
    161, 179, 899, 1065, 41, 1185, 1225, 1833, 1931, 589, 7, 7, 7, 7, 7, 7,
    818, 826, 834, 842, 850, 1409, 1819, 1873, 941, 7, 7, 7, 7, 7, 7, 7,
    801, 419, 913, 1091, 1441, 1475, 36, 7, 7, 7, 7, 7, 7, 7, 7, 7,
    849, 467, 75, 1419, 813, 7, 7, 7, 7, 7, 7, 7, 7, 7, 7, 7,
    178, 186, 194, 202, 210, 1283, 1451, 549, 7, 7, 7, 7, 7, 7, 7, 7,
    393, 707, 1057, 83, 1489, 709, 7, 7, 7, 7, 7, 7, 7, 7, 7, 7,
    665, 195, 17, 19, 1809, 1841, 1465, 1617, 661, 7, 7, 7, 7, 7, 7, 7,
    201, 147, 563, 1081, 1187, 1705, 1857, 533, 7, 7, 7, 7, 7, 7, 7, 7,
    177, 163, 539, 33, 1313, 1195, 1865, 965, 7, 7, 7, 7, 7, 7, 7, 7,
    833, 443, 1107, 1435, 973, 7, 7, 7, 7, 7, 7, 7, 7, 7, 7, 7,
    793, 459, 961, 1307, 1817, 1603, 196, 7, 7, 7, 7, 7, 7, 7, 7, 7,
    169, 409, 283, 929, 1083, 1939, 1985, 581, 7, 7, 7, 7, 7, 7, 7, 7,
    673, 723, 969, 1347, 1601, 693, 7, 7, 7, 7, 7, 7, 7, 7, 7, 7,
    657, 171, 923, 1161, 57, 1345, 1571, 653, 7, 7, 7, 7, 7, 7, 7, 7,
    562, 570, 578, 586, 594, 1921, 1691, 1737, 525, 7, 7, 7, 7, 7, 7, 7,
    289, 139, 529, 571, 1321, 1545, 1955, 909, 7, 7, 7, 7, 7, 7, 7, 7,
    841, 411, 905, 915, 11, 65, 1689, 1859, 68, 7, 7, 7, 7, 7, 7, 7,
    193, 435, 1041, 1059, 1673, 1491, 212, 7, 7, 7, 7, 7, 7, 7, 7, 7,
    449, 433, 291, 937, 51, 1233, 1713, 2001, 557, 7, 7, 7, 7, 7, 7, 7,
    441, 699, 1099, 1443, 685, 7, 7, 7, 7, 7, 7, 7, 7, 7, 7, 7,
    465, 211, 1289, 1179, 1721, 1723, 156, 7, 7, 7, 7, 7, 7, 7, 7, 7,
    185, 403, 515, 921, 945, 977, 1323, 1969, 1729, 573, 7, 7, 7, 7, 7, 7,
    514, 522, 530, 538, 546, 554, 1923, 1427, 933, 7, 7, 7, 7, 7, 7, 7,
    297, 451, 577, 1297, 1363, 957, 7, 7, 7, 7, 7, 7, 7, 7, 7, 7,
    145, 427, 1025, 1049, 27, 81, 1747, 188, 7, 7, 7, 7, 7, 7, 7, 7,
    457, 155, 595, 1211, 541, 7, 7, 7, 7, 7, 7, 7, 7, 7, 7, 7,
    50, 58, 66, 74, 82, 1537, 1361, 1563, 725, 7, 7, 7, 7, 7, 7, 7,
    642, 650, 658, 666, 674, 682, 1667, 1467, 164, 7, 7, 7, 7, 7, 7, 7,
    825, 299, 561, 1035, 1169, 1203, 1745, 565, 7, 7, 7, 7, 7, 7, 7, 7,
    946, 954, 962, 970, 978, 1337, 1217, 1473, 1977, 925, 7, 7, 7, 7, 7, 7,
    434, 442, 450, 458, 466, 1793, 1209, 1459, 901, 7, 7, 7, 7, 7, 7, 7,
    153, 771, 521, 531, 9, 67, 1707, 773, 7, 7, 7, 7, 7, 7, 7, 7,
};

void setup(void* const* d_in, void* d_out) {
  void* fn = nullptr;
  cudaDriverEntryPointQueryResult qr;
  cudaGetDriverEntryPoint("cuTensorMapEncodeTiled", &fn, cudaEnableDefault, &qr);
  EncodeFn enc = (EncodeFn)fn;
  void *scr, *carry, *flags;
  cudaGetSymbolAddress(&scr, g_scr);
  cudaGetSymbolAddress(&carry, g_carry);
  cudaGetSymbolAddress(&flags, g_flags);
  Params& p = g_hs.p;
  make_map(enc, &p.mapA[2], d_in[3], 64, 2048, 16, 2048, 128, 64, 64, 1);
  make_map(enc, &p.mapA[0], d_in[4], 64, 2048, 8, 1024, 128, 64, 64, 1);
  make_map(enc, &p.mapA[1], d_in[0], 64, 1024, 32, 4096, 128, 64, 64, 1);
  make_map(enc, &p.mapB[3], d_in[5], 64, 1024, 64, 8192, 128, 64, 128, 2);
  make_map(enc, &p.mapB[1], d_in[6], 64, 512, 64, 8192, 128, 64, 128, 2);
  make_map(enc, &p.mapB[2], d_in[1], 1024, 1024, 3, 6144, 2048, 64, 64, 3);
  make_map(enc, &p.mapB[0], d_in[7], 64, 512, 64, 8192, 128, 64, 128, 2);
  make_map(enc, &p.mapB[5], d_in[8], 64, 4096, 16, 2048, 128, 64, 128, 2);
  {
    cuuint64_t gd[5] = {1024, 2, 4, 4, 32}, gs[4] = {2048, 8 * 2048, 2 * 2048, 32 * 2048};
    cuuint32_t bd[5] = {64, 2, 4, 4, 4}, es[5] = {1, 1, 1, 1, 1};
    enc(&p.mapB[4], CU_TENSOR_MAP_DATA_TYPE_BFLOAT16, 5, d_in[2], gd, gs, bd, es, CU_TENSOR_MAP_INTERLEAVE_NONE, CU_TENSOR_MAP_SWIZZLE_128B,
        CU_TENSOR_MAP_L2_PROMOTION_L2_128B, CU_TENSOR_MAP_FLOAT_OOB_FILL_NONE);
  }
  make_map(enc, &p.mapO[0], d_out, 4096, 1024, 0, 8192, 0, 64, 16, 1);
  make_map(enc, &p.mapO[1], d_out, 2048, 2048, 0, 4096, 0, 64, 16, 1);
  p.scr = (uint4*)scr;
  p.carry = (uint4*)carry;
  p.flags = (uint32_t*)flags;
  p.x = (const uint32_t*)d_in[3];
  p.wq = (const uint16_t*)d_in[5];
  p.zero = 0;
  for (int c = 0; c < NCLUSTERS; c++) {
    int rot = 0;
    for (int i = c * MAXITEMS; i < (c + 1) * MAXITEMS; i++) {
      const int kind = h_sched[i] & 7, g = (h_sched[i] >> 3) & 15;
      p.sched[i] = (uint16_t)(h_sched[i] | rot << 11);
      rot = (rot + (kind == K_T ? 1 + (g & 1) : g == 0)) % 3;
    }
  }
  int start[NCLUSTERS * MAXITEMS];
  for (int i = 0, t = 0; i < NCLUSTERS * MAXITEMS; i++) {
    const int kind = h_sched[i] & 7, g = (h_sched[i] >> 3) & 15;
    if (i % MAXITEMS == 0) t = 0;
    start[i] = t;
    t += (g ? 3 : 2) * (kind == K_L ? 13 : 8) + (kind == K_T ? 9 * g + 6 : 0);
  }
  for (int i = 0; i < NCLUSTERS * MAXITEMS; i++) {
    int keep = 0;
    for (int k = 0; k < NCLUSTERS * MAXITEMS; k++)
      if (!((h_sched[i] ^ h_sched[k]) & 0x787) && start[k] > start[i] + 3) {
        const int n = 32 | ((3 * ((h_sched[k] >> 3) & 15) + 3) >> 1);
        if (n > keep) keep = n;
      }
    if (start[i] + 9 * ((h_sched[i] >> 3) & 15) < 200) keep |= 128;
    if (i % MAXITEMS < 10) ((uint8_t*)(p.sched + i - i % MAXITEMS))[KEEP + i % MAXITEMS] = (uint8_t)keep;
  }
  cudaFuncSetAttribute(fused_kernel, cudaFuncAttributeMaxDynamicSharedMemorySize, SM_TOTAL);
  for (int i = 0; i < 9; i++) g_hs.in[i] = d_in[i];
  g_hs.out = d_out;
  g_hs.valid = true;
}

}

extern "C" void kernel_launch(void* const* d_in, const int* in_sizes, int n_in, void* d_out, int out_size) {
  (void)in_sizes;
  (void)n_in;
  (void)out_size;
  bool ok = g_hs.valid && g_hs.out == d_out;
  for (int i = 0; ok && i < 9; i++) ok = g_hs.in[i] == d_in[i];
  if (!ok) setup(d_in, d_out);
  fused_kernel<<<NCLUSTERS * 2, 512, SM_TOTAL, cudaStreamPerThread>>>(g_hs.p);
}
```
